```python
import torch

def _softmax(x, axis=-1):
    return torch.softmax(x, dim=axis)
def _gelu(x):
    return torch.nn.functional.gelu(x, approximate="tanh")
def _silu(x):
    return torch.nn.functional.silu(x)
def _sigmoid(x):
    return torch.sigmoid(x)
def _layernorm(x, axis=-1, eps=1e-5):
    m = x.mean(dim=axis, keepdim=True)
    v = x.var(dim=axis, keepdim=True, unbiased=False)
    return (x - m) / torch.sqrt(v + eps)
def _scatter_add(tgt, idx, src, axis=0):
    return tgt.clone().index_add_(axis, idx, src)
def _segment_sum(src, seg, n):
    out = torch.zeros((n,) + src.shape[1:], dtype=src.dtype)
    return out.index_add_(0, seg, src)
def _pad(x, pw):
    flat = tuple(v for pair in reversed(pw) for v in pair)
    return torch.nn.functional.pad(x, flat)

kernel_name = 'concat_heads__grouped_kv_mqa__linear_attn_block__prompt'

def setup_inputs():

    _w = (lambda a: (lambda t: t.to(torch.bfloat16) if t.is_floating_point() else t)(torch.as_tensor(a)))
    def _A_setup():
        B, S, D, H = 1, 2048, 640, 32
        Dh = D // H
        return {
            "x": _w((lambda *s: torch.randn(*s, dtype=torch.bfloat16) * 0.05)(B, S, D)),
            "wq": _w((lambda *s: torch.randn(*s, dtype=torch.bfloat16) * 0.8)(D, H * Dh)),
            "wk": _w((lambda *s: torch.randn(*s, dtype=torch.bfloat16) * 0.8)(D, Dh)),
            "wv": _w((lambda *s: torch.randn(*s, dtype=torch.bfloat16) * 0.05)(D, Dh)),
            "wo": _w((lambda *s: torch.randn(*s, dtype=torch.bfloat16) * 0.05)(H * Dh, D)),
        }
    _A_in = _A_setup()

    def _B_setup():
        B, S, D = 1, 2048, 640
        return {
            "x": _w((lambda *s: torch.randn(*s, dtype=torch.bfloat16) * 0.05)(B, S, D)),
            "wqkv": _w((lambda *s: torch.randn(*s, dtype=torch.bfloat16) * 0.4)(D, 3 * D)),
            "wo": _w((lambda *s: torch.randn(*s, dtype=torch.bfloat16) * 0.05)(D, D)),
        }
    _B_in = _B_setup()

    return {
        "A_x": _A_in["x"],
        "A_wq": _A_in["wq"],
        "A_wk": _A_in["wk"],
        "A_wv": _A_in["wv"],
        "A_wo": _A_in["wo"],
        "B_x": _B_in["x"],
        "B_wqkv": _B_in["wqkv"],
        "B_wo": _B_in["wo"],
    }

def reference(A_x, A_wq, A_wk, A_wv, A_wo, B_x, B_wqkv, B_wo):
    def _A_ref(x, wq, wk, wv, wo):
        B, S, D = x.shape
        H = 32
        Dh = D // H
        q = (lambda x, *d: x.permute(*d))((x @ wq).reshape(B, S, H, Dh), 0, 2, 1, 3)
        k = x @ wk
        v = x @ wv
        scores = torch.einsum("bhqd,bkd->bhqk", q, k) * (Dh ** -0.5)
        p = _softmax(scores, axis=-1)
        o = torch.einsum("bhqk,bkd->bhqd", p, v)
        return (lambda x, *d: x.permute(*d))(o, 0, 2, 1, 3).reshape(B, S, H * Dh) @ wo

    def _B_ref(x, wqkv, wo):
        B, S, D = x.shape
        H = 32; Dh = D // H
        qkv = (lambda x, *d: x.permute(*d))((x @ wqkv).reshape(B, S, 3, H, Dh), 2, 0, 3, 1, 4)
        q, k, v = qkv[0], qkv[1], qkv[2]
        phi = lambda t: torch.where(t > 0, t + 1, torch.exp(t)) + 1e-6
        pq, pk = phi(q), phi(k)
        kv = torch.einsum("bhsd,bhse->bhde", pk, v)
        z = torch.einsum("bhsd->bhd", pk)
        num = torch.einsum("bhqd,bhde->bhqe", pq, kv)
        den = torch.einsum("bhqd,bhd->bhq", pq, z)[..., None] + 1e-6
        o = num / den
        return (lambda x, *d: x.permute(*d))(o, 0, 2, 1, 3).reshape(B, S, D) @ wo

    a = _A_ref(A_x, A_wq, A_wk, A_wv, A_wo)
    b = _B_ref(B_x, B_wqkv, B_wo)
    return torch.concatenate([a, b], axis=-1)
```

```cpp
#include <cuda_runtime.h>
#include <cuda_bf16.h>
#include <cuda.h>
#include <stdint.h>

namespace {

constexpr int NCTA = 128;
constexpr int NTHR = 640;

constexpr uint32_t OFF_STAGE = 0;
constexpr uint32_t STAGE_BYTES = 32768;
constexpr uint32_t OFF_RING = 98304;
constexpr uint32_t RING_BYTES = 24576;
constexpr uint32_t OFF_WRAW = OFF_RING;
constexpr uint32_t OFF_X16 = OFF_RING + 51200;
constexpr uint32_t OFF_EP = 172032;
constexpr uint32_t OFF_PK = OFF_EP;
constexpr uint32_t OFF_V = OFF_EP + 20480;
constexpr uint32_t OFF_WKV = OFF_EP;
constexpr uint32_t OFF_KVB = OFF_V;
constexpr uint32_t OFF_Q1 = OFF_EP;
constexpr uint32_t OFF_Q2 = 217088;
constexpr uint32_t QPITCH = 176;
constexpr uint32_t OFF_MISC = 228352;
constexpr uint32_t OFF_BAR = OFF_MISC;
constexpr uint32_t BAR_FULL_G = OFF_BAR, BAR_EMPTY_G = OFF_BAR + 24, BAR_FULL_KV = OFF_BAR + 48, BAR_KVIN = OFF_BAR + 72;
constexpr uint32_t OFF_CNT = OFF_BAR + 96;
constexpr uint32_t OFF_STAT = OFF_BAR + 112;
constexpr uint32_t OFF_IMG = OFF_MISC + 256;
constexpr uint32_t SMEM_BYTES = OFF_IMG + 1536;

#define MUFU_MASK 0xA4
#define PVG 0

constexpr float LOG2E = 1.4426950408889634f;
constexpr float QSCALE = 0.22360679774997896f * LOG2E;

struct Params {
    CUtensorMap xa, xa16, wq, xb, wqkv, woa, wob, oa, ob;
    const __nv_bfloat16* wk;
    const __nv_bfloat16* wv;
    __nv_bfloat16* out;
};

}

__device__ __align__(1024) uint8_t g_kv[256 * 768];
__device__ __align__(1024) __nv_bfloat16 g_oa[2048 * 640];
__device__ __align__(1024) __nv_bfloat16 g_ob[2048 * 640];
__device__ __align__(16) float g_part[128 * 1920];
__device__ unsigned long long g_flag_kv[128];
__device__ uint32_t g_flag_b1[128], g_flag_b2[128], g_flag_a[512];
__device__ uint32_t g_epoch;
#define TS(k)

namespace {

template<uint32_t HB> __device__ __forceinline__ void wg_rs_n24_tb1(float (&d)[12], uint32_t a0, uint32_t a1, uint32_t a2, uint32_t a3, uint32_t lb) {
    asm volatile("{\n.reg .pred p;\n.reg .b64 db;\nsetp.ne.b32 p, 1, 0;\nmov.b64 db, {%16, %17};\n"
        "wgmma.mma_async.sync.aligned.m64n24k16.f32.bf16.bf16 {%0, %1, %2, %3, %4, %5, %6, %7, %8, %9, %10, %11}, {%12, %13, %14, %15}, db, p, 1, 1, 1;\n}\n"
        : "+f"(d[0]), "+f"(d[1]), "+f"(d[2]), "+f"(d[3]), "+f"(d[4]), "+f"(d[5]), "+f"(d[6]), "+f"(d[7]), "+f"(d[8]), "+f"(d[9]), "+f"(d[10]), "+f"(d[11])
        : "r"(a0), "r"(a1), "r"(a2), "r"(a3), "r"(lb), "n"(HB));
}
template<uint32_t HB> __device__ __forceinline__ void wg_rs_n64_tb0(float (&d)[32], uint32_t a0, uint32_t a1, uint32_t a2, uint32_t a3, uint32_t lb) {
    asm volatile("{\n.reg .pred p;\n.reg .b64 db;\nsetp.ne.b32 p, 1, 0;\nmov.b64 db, {%36, %37};\n"
        "wgmma.mma_async.sync.aligned.m64n64k16.f32.bf16.bf16 {%0, %1, %2, %3, %4, %5, %6, %7, %8, %9, %10, %11, %12, %13, %14, %15, %16, %17, %18, %19, %20, %21, %22, %23, %24, %25, %26, %27, %28, %29, %30, %31}, {%32, %33, %34, %35}, db, p, 1, 1, 0;\n}\n"
        : "+f"(d[0]), "+f"(d[1]), "+f"(d[2]), "+f"(d[3]), "+f"(d[4]), "+f"(d[5]), "+f"(d[6]), "+f"(d[7]), "+f"(d[8]), "+f"(d[9]), "+f"(d[10]), "+f"(d[11]), "+f"(d[12]), "+f"(d[13]), "+f"(d[14]), "+f"(d[15]), "+f"(d[16]), "+f"(d[17]), "+f"(d[18]), "+f"(d[19]), "+f"(d[20]), "+f"(d[21]), "+f"(d[22]), "+f"(d[23]), "+f"(d[24]), "+f"(d[25]), "+f"(d[26]), "+f"(d[27]), "+f"(d[28]), "+f"(d[29]), "+f"(d[30]), "+f"(d[31])
        : "r"(a0), "r"(a1), "r"(a2), "r"(a3), "r"(lb), "n"(HB));
}
template<uint32_t HB> __device__ __forceinline__ void wg_rs_n64_tb0_init(float (&d)[32], uint32_t a0, uint32_t a1, uint32_t a2, uint32_t a3, uint32_t lb) {
    asm volatile("{\n.reg .pred p;\n.reg .b64 db;\nsetp.ne.b32 p, 0, 0;\nmov.b64 db, {%36, %37};\n"
        "wgmma.mma_async.sync.aligned.m64n64k16.f32.bf16.bf16 {%0, %1, %2, %3, %4, %5, %6, %7, %8, %9, %10, %11, %12, %13, %14, %15, %16, %17, %18, %19, %20, %21, %22, %23, %24, %25, %26, %27, %28, %29, %30, %31}, {%32, %33, %34, %35}, db, p, 1, 1, 0;\n}\n"
        : "=f"(d[0]), "=f"(d[1]), "=f"(d[2]), "=f"(d[3]), "=f"(d[4]), "=f"(d[5]), "=f"(d[6]), "=f"(d[7]), "=f"(d[8]), "=f"(d[9]), "=f"(d[10]), "=f"(d[11]), "=f"(d[12]), "=f"(d[13]), "=f"(d[14]), "=f"(d[15]), "=f"(d[16]), "=f"(d[17]), "=f"(d[18]), "=f"(d[19]), "=f"(d[20]), "=f"(d[21]), "=f"(d[22]), "=f"(d[23]), "=f"(d[24]), "=f"(d[25]), "=f"(d[26]), "=f"(d[27]), "=f"(d[28]), "=f"(d[29]), "=f"(d[30]), "=f"(d[31])
        : "r"(a0), "r"(a1), "r"(a2), "r"(a3), "r"(lb), "n"(HB));
}
template<uint32_t HA, uint32_t HB> __device__ __forceinline__ void wg_ss_n16_ta1_tb0(float (&d)[8], uint32_t la, uint32_t lb) {
    asm volatile("{\n.reg .pred p;\n.reg .b64 da, db;\nsetp.ne.b32 p, 1, 0;\nmov.b64 da, {%8, %10};\nmov.b64 db, {%9, %11};\n"
        "wgmma.mma_async.sync.aligned.m64n16k16.f32.bf16.bf16 {%0, %1, %2, %3, %4, %5, %6, %7}, da, db, p, 1, 1, 1, 0;\n}\n"
        : "+f"(d[0]), "+f"(d[1]), "+f"(d[2]), "+f"(d[3]), "+f"(d[4]), "+f"(d[5]), "+f"(d[6]), "+f"(d[7])
        : "r"(la), "r"(lb), "n"(HA), "n"(HB));
}
template<uint32_t HA, uint32_t HB> __device__ __forceinline__ void wg_ss_n16_ta1_tb0_init(float (&d)[8], uint32_t la, uint32_t lb) {
    asm volatile("{\n.reg .pred p;\n.reg .b64 da, db;\nsetp.ne.b32 p, 0, 0;\nmov.b64 da, {%8, %10};\nmov.b64 db, {%9, %11};\n"
        "wgmma.mma_async.sync.aligned.m64n16k16.f32.bf16.bf16 {%0, %1, %2, %3, %4, %5, %6, %7}, da, db, p, 1, 1, 1, 0;\n}\n"
        : "=f"(d[0]), "=f"(d[1]), "=f"(d[2]), "=f"(d[3]), "=f"(d[4]), "=f"(d[5]), "=f"(d[6]), "=f"(d[7])
        : "r"(la), "r"(lb), "n"(HA), "n"(HB));
}
template<uint32_t HA, uint32_t HB> __device__ __forceinline__ void wg_ss_n32_ta1_tb1(float (&d)[16], uint32_t la, uint32_t lb) {
    asm volatile("{\n.reg .pred p;\n.reg .b64 da, db;\nsetp.ne.b32 p, 1, 0;\nmov.b64 da, {%16, %18};\nmov.b64 db, {%17, %19};\n"
        "wgmma.mma_async.sync.aligned.m64n32k16.f32.bf16.bf16 {%0, %1, %2, %3, %4, %5, %6, %7, %8, %9, %10, %11, %12, %13, %14, %15}, da, db, p, 1, 1, 1, 1;\n}\n"
        : "+f"(d[0]), "+f"(d[1]), "+f"(d[2]), "+f"(d[3]), "+f"(d[4]), "+f"(d[5]), "+f"(d[6]), "+f"(d[7]), "+f"(d[8]), "+f"(d[9]), "+f"(d[10]), "+f"(d[11]), "+f"(d[12]), "+f"(d[13]), "+f"(d[14]), "+f"(d[15])
        : "r"(la), "r"(lb), "n"(HA), "n"(HB));
}
template<uint32_t HA, uint32_t HB> __device__ __forceinline__ void wg_ss_n72_ta1_tb1(float (&d)[36], uint32_t la, uint32_t lb) {
    asm volatile("{\n.reg .pred p;\n.reg .b64 da, db;\nsetp.ne.b32 p, 1, 0;\nmov.b64 da, {%36, %38};\nmov.b64 db, {%37, %39};\n"
        "wgmma.mma_async.sync.aligned.m64n72k16.f32.bf16.bf16 {%0, %1, %2, %3, %4, %5, %6, %7, %8, %9, %10, %11, %12, %13, %14, %15, %16, %17, %18, %19, %20, %21, %22, %23, %24, %25, %26, %27, %28, %29, %30, %31, %32, %33, %34, %35}, da, db, p, 1, 1, 1, 1;\n}\n"
        : "+f"(d[0]), "+f"(d[1]), "+f"(d[2]), "+f"(d[3]), "+f"(d[4]), "+f"(d[5]), "+f"(d[6]), "+f"(d[7]), "+f"(d[8]), "+f"(d[9]), "+f"(d[10]), "+f"(d[11]), "+f"(d[12]), "+f"(d[13]), "+f"(d[14]), "+f"(d[15]), "+f"(d[16]), "+f"(d[17]), "+f"(d[18]), "+f"(d[19]), "+f"(d[20]), "+f"(d[21]), "+f"(d[22]), "+f"(d[23]), "+f"(d[24]), "+f"(d[25]), "+f"(d[26]), "+f"(d[27]), "+f"(d[28]), "+f"(d[29]), "+f"(d[30]), "+f"(d[31]), "+f"(d[32]), "+f"(d[33]), "+f"(d[34]), "+f"(d[35])
        : "r"(la), "r"(lb), "n"(HA), "n"(HB));
}
template<uint32_t HA, uint32_t HB> __device__ __forceinline__ void wg_ss_n80_ta0_tb1(float (&d)[40], uint32_t la, uint32_t lb) {
    asm volatile("{\n.reg .pred p;\n.reg .b64 da, db;\nsetp.ne.b32 p, 1, 0;\nmov.b64 da, {%40, %42};\nmov.b64 db, {%41, %43};\n"
        "wgmma.mma_async.sync.aligned.m64n80k16.f32.bf16.bf16 {%0, %1, %2, %3, %4, %5, %6, %7, %8, %9, %10, %11, %12, %13, %14, %15, %16, %17, %18, %19, %20, %21, %22, %23, %24, %25, %26, %27, %28, %29, %30, %31, %32, %33, %34, %35, %36, %37, %38, %39}, da, db, p, 1, 1, 0, 1;\n}\n"
        : "+f"(d[0]), "+f"(d[1]), "+f"(d[2]), "+f"(d[3]), "+f"(d[4]), "+f"(d[5]), "+f"(d[6]), "+f"(d[7]), "+f"(d[8]), "+f"(d[9]), "+f"(d[10]), "+f"(d[11]), "+f"(d[12]), "+f"(d[13]), "+f"(d[14]), "+f"(d[15]), "+f"(d[16]), "+f"(d[17]), "+f"(d[18]), "+f"(d[19]), "+f"(d[20]), "+f"(d[21]), "+f"(d[22]), "+f"(d[23]), "+f"(d[24]), "+f"(d[25]), "+f"(d[26]), "+f"(d[27]), "+f"(d[28]), "+f"(d[29]), "+f"(d[30]), "+f"(d[31]), "+f"(d[32]), "+f"(d[33]), "+f"(d[34]), "+f"(d[35]), "+f"(d[36]), "+f"(d[37]), "+f"(d[38]), "+f"(d[39])
        : "r"(la), "r"(lb), "n"(HA), "n"(HB));
}
template<uint32_t HA, uint32_t HB> __device__ __forceinline__ void wg_ss_n80_ta0_tb1_init(float (&d)[40], uint32_t la, uint32_t lb) {
    asm volatile("{\n.reg .pred p;\n.reg .b64 da, db;\nsetp.ne.b32 p, 0, 0;\nmov.b64 da, {%40, %42};\nmov.b64 db, {%41, %43};\n"
        "wgmma.mma_async.sync.aligned.m64n80k16.f32.bf16.bf16 {%0, %1, %2, %3, %4, %5, %6, %7, %8, %9, %10, %11, %12, %13, %14, %15, %16, %17, %18, %19, %20, %21, %22, %23, %24, %25, %26, %27, %28, %29, %30, %31, %32, %33, %34, %35, %36, %37, %38, %39}, da, db, p, 1, 1, 0, 1;\n}\n"
        : "=f"(d[0]), "=f"(d[1]), "=f"(d[2]), "=f"(d[3]), "=f"(d[4]), "=f"(d[5]), "=f"(d[6]), "=f"(d[7]), "=f"(d[8]), "=f"(d[9]), "=f"(d[10]), "=f"(d[11]), "=f"(d[12]), "=f"(d[13]), "=f"(d[14]), "=f"(d[15]), "=f"(d[16]), "=f"(d[17]), "=f"(d[18]), "=f"(d[19]), "=f"(d[20]), "=f"(d[21]), "=f"(d[22]), "=f"(d[23]), "=f"(d[24]), "=f"(d[25]), "=f"(d[26]), "=f"(d[27]), "=f"(d[28]), "=f"(d[29]), "=f"(d[30]), "=f"(d[31]), "=f"(d[32]), "=f"(d[33]), "=f"(d[34]), "=f"(d[35]), "=f"(d[36]), "=f"(d[37]), "=f"(d[38]), "=f"(d[39])
        : "r"(la), "r"(lb), "n"(HA), "n"(HB));
}
template<uint32_t HA, uint32_t HB> __device__ __forceinline__ void wg_ss_n88_ta0_tb1(float (&d)[44], uint32_t la, uint32_t lb) {
    asm volatile("{\n.reg .pred p;\n.reg .b64 da, db;\nsetp.ne.b32 p, 1, 0;\nmov.b64 da, {%44, %46};\nmov.b64 db, {%45, %47};\n"
        "wgmma.mma_async.sync.aligned.m64n88k16.f32.bf16.bf16 {%0, %1, %2, %3, %4, %5, %6, %7, %8, %9, %10, %11, %12, %13, %14, %15, %16, %17, %18, %19, %20, %21, %22, %23, %24, %25, %26, %27, %28, %29, %30, %31, %32, %33, %34, %35, %36, %37, %38, %39, %40, %41, %42, %43}, da, db, p, 1, 1, 0, 1;\n}\n"
        : "+f"(d[0]), "+f"(d[1]), "+f"(d[2]), "+f"(d[3]), "+f"(d[4]), "+f"(d[5]), "+f"(d[6]), "+f"(d[7]), "+f"(d[8]), "+f"(d[9]), "+f"(d[10]), "+f"(d[11]), "+f"(d[12]), "+f"(d[13]), "+f"(d[14]), "+f"(d[15]), "+f"(d[16]), "+f"(d[17]), "+f"(d[18]), "+f"(d[19]), "+f"(d[20]), "+f"(d[21]), "+f"(d[22]), "+f"(d[23]), "+f"(d[24]), "+f"(d[25]), "+f"(d[26]), "+f"(d[27]), "+f"(d[28]), "+f"(d[29]), "+f"(d[30]), "+f"(d[31]), "+f"(d[32]), "+f"(d[33]), "+f"(d[34]), "+f"(d[35]), "+f"(d[36]), "+f"(d[37]), "+f"(d[38]), "+f"(d[39]), "+f"(d[40]), "+f"(d[41]), "+f"(d[42]), "+f"(d[43])
        : "r"(la), "r"(lb), "n"(HA), "n"(HB));
}

#define WG_FENCE() asm volatile("wgmma.fence.sync.aligned;" ::: "memory")
#define WG_COMMIT() asm volatile("wgmma.commit_group.sync.aligned;" ::: "memory")
#define WG_WAIT(n) asm volatile("wgmma.wait_group.sync.aligned %0;" :: "n"(n) : "memory")
template <int NR> __device__ __forceinline__ void fence_regs(float (&d)[NR]) {
#pragma unroll
    for (int i = 0; i < NR; i++) asm volatile("" : "+f"(d[i]) :: "memory");
}
template <int NR> __device__ __forceinline__ void zero_regs(float (&d)[NR]) {
#pragma unroll
    for (int i = 0; i < NR; i++) asm volatile("mov.b32 %0, 0;" : "=f"(d[i]) :: "memory");
}
constexpr uint32_t SW128 = 1u << 30;
__device__ __forceinline__ constexpr uint32_t dlo(uint32_t lbo) { return (lbo >> 4) << 16; }

__device__ __forceinline__ void bar_sync(int id, int n) { asm volatile("bar.sync %0, %1;" :: "r"(id), "r"(n) : "memory"); }
__device__ __forceinline__ void bar_arrive(int id, int n) { asm volatile("bar.arrive %0, %1;" :: "r"(id), "r"(n) : "memory"); }
__device__ __forceinline__ void mbar_init(uint32_t bar, uint32_t cnt) { asm volatile("mbarrier.init.shared::cta.b64 [%0], %1;" :: "r"(bar), "r"(cnt) : "memory"); }
__device__ __forceinline__ void mbar_arrive(uint32_t bar) { asm volatile("mbarrier.arrive.shared::cta.b64 _, [%0];" :: "r"(bar) : "memory"); }
__device__ __forceinline__ void mbar_expect(uint32_t bar, uint32_t bytes) { asm volatile("mbarrier.arrive.expect_tx.shared::cta.b64 _, [%0], %1;" :: "r"(bar), "r"(bytes) : "memory"); }
__device__ __forceinline__ void mbar_wait(uint32_t bar, uint32_t parity) {
    uint32_t ok, spin = 0;
#pragma unroll 1
    do {
        asm volatile("{\n.reg .pred p;\nmbarrier.try_wait.parity.shared::cta.b64 p, [%1], %2;\nselp.u32 %0, 1, 0, p;\n}" : "=r"(ok) : "r"(bar), "r"(parity) : "memory");
        if (ok) return;
    } while (++spin < (1u << 15));
}
__device__ __forceinline__ void tma2d(uint32_t dst, const CUtensorMap* m, int x, int y, uint32_t bar) {
    asm volatile("cp.async.bulk.tensor.2d.shared::cluster.global.mbarrier::complete_tx::bytes [%0], [%1, {%2, %3}], [%4];"
                 :: "r"(dst), "l"(m), "r"(x), "r"(y), "r"(bar) : "memory");
}
__device__ __forceinline__ void bulk1d(uint32_t dst, const void* src, uint32_t bytes, uint32_t bar) {
    asm volatile("cp.async.bulk.shared::cluster.global.mbarrier::complete_tx::bytes [%0], [%1], %2, [%3];"
                 :: "r"(dst), "l"(src), "r"(bytes), "r"(bar) : "memory");
}
__device__ __forceinline__ void fence_async() { asm volatile("fence.proxy.async.global;" ::: "memory"); }
__device__ __forceinline__ void fence_async_smem() { asm volatile("fence.proxy.async.shared::cta;" ::: "memory"); }
__device__ __forceinline__ void st_release(uint32_t* p, uint32_t v) { asm volatile("st.release.gpu.global.u32 [%0], %1;" :: "l"(p), "r"(v) : "memory"); }
__device__ __forceinline__ uint32_t ld_acquire(const uint32_t* p) { uint32_t v; asm volatile("ld.acquire.gpu.global.u32 %0, [%1];" : "=r"(v) : "l"(p) : "memory"); return v; }
__device__ __forceinline__ unsigned long long ld_acquire64(const unsigned long long* p) { unsigned long long v; asm volatile("ld.acquire.gpu.global.u64 %0, [%1];" : "=l"(v) : "l"(p) : "memory"); return v; }
__device__ __forceinline__ void poll_flag(const uint32_t* p, bool active, uint32_t tag) {
    uint32_t spin = 0;
    if (active) {
#pragma unroll 1
        while (ld_acquire(p) != tag) { if (++spin > (1u << 17)) break; }
    }
    __syncwarp();
}
__device__ __forceinline__ uint32_t lds32(uint32_t a) { uint32_t v; asm volatile("ld.shared.u32 %0, [%1];" : "=r"(v) : "r"(a) : "memory"); return v; }
__device__ __forceinline__ void sts32(uint32_t a, uint32_t v) { asm volatile("st.shared.u32 [%0], %1;" :: "r"(a), "r"(v) : "memory"); }
__device__ __forceinline__ void sts16(uint32_t a, uint16_t v) { asm volatile("st.shared.u16 [%0], %1;" :: "r"(a), "h"(v) : "memory"); }
__device__ __forceinline__ void sts64(uint32_t a, uint32_t x, uint32_t y) { asm volatile("st.shared.v2.u32 [%0], {%1, %2};" :: "r"(a), "r"(x), "r"(y) : "memory"); }
__device__ __forceinline__ void sts128(uint32_t a, uint32_t x, uint32_t y, uint32_t z, uint32_t w) { asm volatile("st.shared.v4.u32 [%0], {%1, %2, %3, %4};" :: "r"(a), "r"(x), "r"(y), "r"(z), "r"(w) : "memory"); }
__device__ __forceinline__ uint2 lds64(uint32_t a) { uint2 v; asm volatile("ld.shared.v2.u32 {%0, %1}, [%2];" : "=r"(v.x), "=r"(v.y) : "r"(a) : "memory"); return v; }
__device__ __forceinline__ uint4 lds128(uint32_t a) { uint4 v; asm volatile("ld.shared.v4.u32 {%0, %1, %2, %3}, [%4];" : "=r"(v.x), "=r"(v.y), "=r"(v.z), "=r"(v.w) : "r"(a) : "memory"); return v; }
__device__ __forceinline__ float ex2f(float x) { float y; asm("ex2.approx.ftz.f32 %0, %1;" : "=f"(y) : "f"(x)); return y; }
__device__ __forceinline__ float rcpf(float x) { float y; asm("div.full.f32 %0, 0f3F800000, %1;" : "=f"(y) : "f"(x)); return y; }
__device__ __forceinline__ uint32_t pack_bf16(float lo, float hi) { uint32_t r; asm("cvt.rn.bf16x2.f32 %0, %1, %2;" : "=r"(r) : "f"(hi), "f"(lo)); return r; }
__device__ __forceinline__ float bf_lo(uint32_t v) { return __uint_as_float(v << 16); }
__device__ __forceinline__ float bf_hi(uint32_t v) { return __uint_as_float(v & 0xFFFF0000u); }
__device__ __forceinline__ float phi(float t) { return (t > 0.f ? t + 1.f : ex2f(t * LOG2E)) + 1e-6f; }

__device__ __forceinline__ uint32_t exp2_pair(float t0, float t1, uint32_t ca) {
    uint32_t y, u, g;
    asm("prmt.b32 %0, %1, %2, 0x6521;" : "=r"(y) : "r"(__float_as_uint(t0)), "r"(__float_as_uint(t1)));
    u = y & 0x007F007Fu;
    asm("{.reg .b32 c; mov.b32 c, 0xF963F963; fma.rn.f16x2 %0, %1, c, %2;}" : "=r"(g) : "r"(u), "r"(ca));
    asm("mul.rn.f16x2 %0, %1, %2;" : "=r"(g) : "r"(g), "r"(u));
    return y - g;
}

constexpr uint32_t HI_K = 768 >> 4, HI_V = 128 >> 4;
constexpr uint32_t LO_K = dlo(128), LO_V = dlo(768) + 24;

template <int J> __device__ __forceinline__ void exp_steps(const float (&s)[32], uint32_t (&p)[16], float (&o)[12], uint32_t lo, uint32_t ca) {
    if constexpr (J < 4) {
#pragma unroll
        for (int g = 2 * J; g < 2 * J + 2; g++) {
            if ((MUFU_MASK >> g) & 1) {
                p[2 * g] = pack_bf16(ex2f(s[4 * g]), ex2f(s[4 * g + 1]));
                p[2 * g + 1] = pack_bf16(ex2f(s[4 * g + 2]), ex2f(s[4 * g + 3]));
            } else {
                p[2 * g] = exp2_pair(s[4 * g], s[4 * g + 1], ca);
                p[2 * g + 1] = exp2_pair(s[4 * g + 2], s[4 * g + 3], ca);
            }
        }
        if constexpr (PVG == 1) {
            WG_FENCE();
            wg_rs_n24_tb1<HI_V>(o, p[4 * J], p[4 * J + 1], p[4 * J + 2], p[4 * J + 3], lo + LO_V + J * 96);
        }
        if constexpr (PVG == 2 && (J & 1)) {
            WG_FENCE();
            wg_rs_n24_tb1<HI_V>(o, p[4 * J - 4], p[4 * J - 3], p[4 * J - 2], p[4 * J - 1], lo + LO_V + (J - 1) * 96);
            wg_rs_n24_tb1<HI_V>(o, p[4 * J], p[4 * J + 1], p[4 * J + 2], p[4 * J + 3], lo + LO_V + J * 96);
        }
        exp_steps<J + 1>(s, p, o, lo, ca);
    }
}

struct Ring { uint32_t slot, phase; };

__device__ __forceinline__ void ring_release(uint32_t sb, int n) {
    if (n + 3 < 16) {
        if ((threadIdx.x & 31) == 0) {
            const uint32_t slot = n % 3;
            uint32_t old;
            asm volatile("atom.acq_rel.cta.shared::cta.add.u32 %0, [%1], 1;" : "=r"(old) : "r"(sb + OFF_CNT + slot * 4) : "memory");
            if ((old & 15) == 15) {
                mbar_expect(sb + BAR_FULL_KV + slot * 8, RING_BYTES);
                bulk1d(sb + OFF_RING + slot * RING_BYTES, g_kv + ((n + 3) & 7) * RING_BYTES, RING_BYTES, sb + BAR_FULL_KV + slot * 8);
            }
        }
        __syncwarp();
    }
}

template <bool FAST>
__device__ __forceinline__ void attend(uint32_t sb, Ring& r, int pass, const uint32_t (&q)[6], float (&o)[12]) {
    uint32_t ca = 0x357F357Fu;
    asm volatile("" : "+r"(ca));
    float m0 = -INFINITY, m1 = -INFINITY;
#pragma unroll 1
    for (int c = 0; c < 8; c++) {
        mbar_wait(sb + BAR_FULL_KV + r.slot * 8, r.phase);
        const uint32_t lo0 = (sb + OFF_RING + r.slot * RING_BYTES) >> 4;
#pragma unroll 1
        for (uint32_t lo = lo0; lo < lo0 + 4 * 384; lo += 384) {
            float s[32];
            uint32_t p[16];
            WG_FENCE();
            wg_rs_n64_tb0_init<HI_K>(s, q[0], q[1], q[2], q[3], lo + LO_K);
            wg_rs_n64_tb0<HI_K>(s, q[4], q[5], 0u, 0u, lo + LO_K + 16);
            WG_COMMIT();
            WG_WAIT(0);
            fence_regs(s);
            if (lo == lo0 && c > 0) ring_release(sb, pass * 8 + c - 1);
            if constexpr (FAST) {
                exp_steps<0>(s, p, o, lo, ca);
            } else {
                fence_regs(o);
                float x0 = m0, x1 = m1;
#pragma unroll
                for (int g = 0; g < 8; g++) {
                    if (!((MUFU_MASK >> g) & 1)) {
#pragma unroll
                        for (int e = 0; e < 4; e++) s[4 * g + e] *= 2.f;
                    }
                    x0 = fmaxf(x0, fmaxf(s[4 * g], s[4 * g + 1]));
                    x1 = fmaxf(x1, fmaxf(s[4 * g + 2], s[4 * g + 3]));
                }
                x0 = fmaxf(x0, __shfl_xor_sync(~0u, x0, 1)); x0 = fmaxf(x0, __shfl_xor_sync(~0u, x0, 2));
                x1 = fmaxf(x1, __shfl_xor_sync(~0u, x1, 1)); x1 = fmaxf(x1, __shfl_xor_sync(~0u, x1, 2));
                const float a0 = ex2f(m0 - x0), a1 = ex2f(m1 - x1);
                m0 = x0; m1 = x1;
#pragma unroll
                for (int b = 0; b < 3; b++) { o[4 * b] *= a0; o[4 * b + 1] *= a0; o[4 * b + 2] *= a1; o[4 * b + 3] *= a1; }
#pragma unroll
                for (int g = 0; g < 8; g++) {
                    p[2 * g] = pack_bf16(ex2f(s[4 * g] - x0), ex2f(s[4 * g + 1] - x0));
                    p[2 * g + 1] = pack_bf16(ex2f(s[4 * g + 2] - x1), ex2f(s[4 * g + 3] - x1));
                }
            }
            if constexpr (!FAST || PVG == 0) {
                WG_FENCE();
#pragma unroll
                for (int k = 0; k < 4; k++) wg_rs_n24_tb1<HI_V>(o, p[4 * k], p[4 * k + 1], p[4 * k + 2], p[4 * k + 3], lo + LO_V + k * 96);
            }
            WG_COMMIT();
            WG_WAIT(0);
            fence_regs(o);
        }
        if (++r.slot == 3) { r.slot = 0; r.phase ^= 1; }
    }
    WG_WAIT(0);
    fence_regs(o);
    ring_release(sb, pass * 8 + 7);
}

__device__ __forceinline__ void gemm_issue(const Params& P, uint32_t sb, int it, int i, int j) {
    const int pass = it / 10, c = it - pass * 10, s = it % 3;
    if (it >= 3) mbar_wait(sb + BAR_EMPTY_G + s * 8, (it / 3 - 1) & 1);
    const CUtensorMap* mx = pass == 0 ? &P.xa : pass <= 3 ? &P.xb : pass == 4 ? &P.ob : &P.oa;
    const CUtensorMap* mw = pass == 0 ? &P.wq : pass <= 3 ? &P.wqkv : pass == 4 ? &P.wob : &P.woa;
    const int col = 80 * j + (pass == 1 ? 640 : pass == 2 ? 1280 : 0);
    const uint32_t st = sb + OFF_STAGE + s * STAGE_BYTES, bar = sb + BAR_FULL_G + s * 8;
    mbar_expect(bar, STAGE_BYTES);
    tma2d(st, mx, 64 * c, 128 * i, bar);
    tma2d(st + 16384, mw, col, 64 * c, bar);
    tma2d(st + 24576, mw, col + 64, 64 * c, bar);
}

template <bool FIRST>
__device__ __forceinline__ void gemm_step(const Params& P, uint32_t sb, int it, int limit, int i, int j, float (&a)[40], float (&b)[40]) {
    const int s = it % 3;
    mbar_wait(sb + BAR_FULL_G + s * 8, (it / 3) & 1);
    const uint32_t lx = ((sb + OFF_STAGE + s * STAGE_BYTES) >> 4) + dlo(16);
    const uint32_t lw = ((sb + OFF_STAGE + s * STAGE_BYTES + 16384) >> 4) + dlo(8192);
    WG_FENCE();
    if constexpr (FIRST) {
        wg_ss_n80_ta0_tb1_init<SW128 | 64, SW128 | 64>(a, lx, lw);
        wg_ss_n80_ta0_tb1_init<SW128 | 64, SW128 | 64>(b, lx + 512, lw);
    }
#pragma unroll
    for (int k = FIRST; k < 4; k++) {
        wg_ss_n80_ta0_tb1<SW128 | 64, SW128 | 64>(a, lx + 2 * k, lw + 128 * k);
        wg_ss_n80_ta0_tb1<SW128 | 64, SW128 | 64>(b, lx + 512 + 2 * k, lw + 128 * k);
    }
    WG_COMMIT();
    WG_WAIT(0);
    if ((threadIdx.x & 31) == 0) {
        mbar_arrive(sb + BAR_EMPTY_G + s * 8);
        if (threadIdx.x == 512 && it + 3 < limit) gemm_issue(P, sb, it + 3, i, j);
    }
    __syncwarp();
}
__device__ __forceinline__ void gemm_pass(const Params& P, uint32_t sb, int it0, int limit, int i, int j, float (&a)[40], float (&b)[40]) {
    zero_regs(a); zero_regs(b);
#pragma unroll 1
    for (int it = it0; it < it0 + 10; it++) gemm_step<false>(P, sb, it, limit, i, j, a, b);
    fence_regs(a); fence_regs(b);
}

__device__ __forceinline__ void store_tile(__nv_bfloat16* dst, int pitch, const float (&a)[40]) {
#pragma unroll
    for (int b = 0; b < 10; b++) {
        *reinterpret_cast<uint32_t*>(dst + 8 * b) = pack_bf16(a[4 * b], a[4 * b + 1]);
        *reinterpret_cast<uint32_t*>(dst + 8 * pitch + 8 * b) = pack_bf16(a[4 * b + 2], a[4 * b + 3]);
    }
}

__device__ __forceinline__ void linear_out(uint32_t sb, int half, __nv_bfloat16* dst, int q) {
    float d[44]; zero_regs(d);
    const uint32_t la = ((sb + OFF_PK + half * 10240) >> 4) + dlo(128), lb = ((sb + OFF_KVB) >> 4) + dlo(1408);
    WG_FENCE();
    wg_ss_n88_ta0_tb1<80, 8>(d, la, lb);
#pragma unroll
    for (int k = 1; k < 5; k++) wg_ss_n88_ta0_tb1<80, 8>(d, la + 16 * k, lb + 176 * k);
    WG_COMMIT();
    WG_WAIT(0);
    fence_regs(d);
    float r0[4], r1[4];
    const int base = (threadIdx.x & 31) & ~3;
#pragma unroll
    for (int h = 0; h < 4; h++) {
        r0[h] = rcpf(__shfl_sync(~0u, d[40 + (h & 1)], base + (h >> 1)) + 1e-6f);
        r1[h] = rcpf(__shfl_sync(~0u, d[42 + (h & 1)], base + (h >> 1)) + 1e-6f);
    }
#pragma unroll
    for (int b = 0; b < 10; b++) {
        const int hl = (8 * b) / 20, hh = (8 * b + 6) / 20;
        const bool up = hl != hh && q >= 2;
        const float s0 = up ? r0[hh] : r0[hl], s1 = up ? r1[hh] : r1[hl];
        *reinterpret_cast<uint32_t*>(dst + 8 * b) = pack_bf16(d[4 * b] * s0, d[4 * b + 1] * s0);
        *reinterpret_cast<uint32_t*>(dst + 8 * 640 + 8 * b) = pack_bf16(d[4 * b + 2] * s1, d[4 * b + 3] * s1);
    }
}

__global__ void __launch_bounds__(NTHR, 1) fused_kernel(const __grid_constant__ Params P) {
    extern __shared__ __align__(1024) uint8_t smem[];
    const uint32_t sb = (uint32_t)__cvta_generic_to_shared(smem);
    const int tid = threadIdx.x, lane = tid & 31, wg = tid >> 7, warp = (tid >> 5) & 3;
    const int cta = blockIdx.x, i = cta >> 3, j = cta & 7;
    const int q = lane & 3, r0 = 16 * warp + (lane >> 2);
    TS(wg == 4 ? 0 : 16);

    if (tid == 512) {
#pragma unroll
        for (int s = 0; s < 3; s++) {
            mbar_init(sb + BAR_FULL_G + s * 8, 1);
            mbar_init(sb + BAR_EMPTY_G + s * 8, 4);
            mbar_init(sb + BAR_FULL_KV + s * 8, 1);
            sts32(sb + OFF_CNT + s * 4, 0);
        }
        mbar_init(sb + BAR_KVIN, 1);
        asm volatile("fence.mbarrier_init.release.cluster;" ::: "memory");
        fence_async_smem();
        mbar_expect(sb + BAR_KVIN, 51200 + 20480);
        bulk1d(sb + OFF_WRAW, P.wk, 25600, sb + BAR_KVIN);
        bulk1d(sb + OFF_WRAW + 25600, P.wv, 25600, sb + BAR_KVIN);
#pragma unroll 1
        for (int c = 0; c < 10; c++) tma2d(sb + OFF_X16 + c * 2048, &P.xa16, 64 * c, 16 * cta, sb + BAR_KVIN);
#pragma unroll 1
        for (int it = 0; it < 3; it++) gemm_issue(P, sb, it, i, j);
    }
    const uint32_t tag = *(volatile uint32_t*)&g_epoch + 1;
    __syncthreads();

    if (wg < 4) {
        asm volatile("setmaxnreg.dec.sync.aligned.u32 88;");
        mbar_wait(sb + BAR_KVIN, 0);
#pragma unroll 1
        for (int u = tid; u < 6400; u += 512) {
            const int mat = u >= 3200, rem = u - mat * 3200, k = rem / 5, m0 = mat * 20 + 4 * (rem - 5 * k);
            const uint2 v = lds64(sb + OFF_WRAW + u * 8);
            sts64(sb + OFF_WKV + (k >> 3) * 640 + (m0 >> 3) * 128 + (k & 7) * 16 + (m0 & 7) * 2, v.x, v.y);
        }
        fence_async_smem();
        bar_sync(1, 512);
        if (wg == 0) {
            float d[8];
            const uint32_t la = ((sb + OFF_WKV) >> 4) + dlo(640), lb = ((sb + OFF_X16) >> 4) + dlo(16);
            WG_FENCE();
            wg_ss_n16_ta1_tb0_init<8, SW128 | 64>(d, la, lb);
#pragma unroll
            for (int k = 1; k < 40; k++) wg_ss_n16_ta1_tb0<8, SW128 | 64>(d, la + 80 * k, lb + (k >> 2) * 128 + (k & 3) * 2);
            WG_COMMIT();
            if (tid < 16) {
                const int g = tid >> 3;
                const bool mu = (MUFU_MASK >> ((2 * cta + g) & 7)) & 1;
                const uint32_t a = sb + OFF_IMG + g * 768 + (tid & 7) * 16 + 8;
                sts64(a + 256, mu ? 0u : 0x3F00433Fu, mu ? 0u : 0x00003B4Au);
                sts64(a + 640, 0x00003F80u, 0u);
            }
            WG_WAIT(0);
            fence_regs(d);
            bar_arrive(2, 256);
#pragma unroll
            for (int hh = 0; hh < 2; hh++) {
                const int m = r0 + 8 * hh;
                if (m < 40) {
                    const int isv = m >= 20, dd = m - 20 * isv;
#pragma unroll
                    for (int g = 0; g < 2; g++) {
                        const bool mu = (MUFU_MASK >> ((2 * cta + g) & 7)) & 1;
                        const float sc = (isv || mu) ? 1.f : 0.5f;
                        const uint32_t pr = pack_bf16(d[4 * g + 2 * hh] * sc, d[4 * g + 2 * hh + 1] * sc);
                        const uint32_t a = sb + OFF_IMG + g * 768 + (3 * isv + (dd >> 3)) * 128 + (dd & 7) * 2 + 2 * q * 16;
                        sts16(a, (uint16_t)pr);
                        sts16(a + 16, (uint16_t)(pr >> 16));
                    }
                }
            }
            bar_sync(3, 128);
            if (warp == 0) {
#pragma unroll
                for (int u = 0; u < 3; u++) {
                    const uint4 v = lds128(sb + OFF_IMG + (lane + 32 * u) * 16);
                    *reinterpret_cast<uint4*>(g_kv + cta * 1536 + (lane + 32 * u) * 16) = v;
                }
                const int key = lane & 15, g = key >> 3;
                const uint32_t a = sb + OFF_IMG + g * 768 + (lane >> 4) * 384 + (key & 7) * 16;
                const uint4 w0 = lds128(a), w1 = lds128(a + 128);
                const uint2 w2 = lds64(a + 256);
                const uint32_t w[10] = {w0.x, w0.y, w0.z, w0.w, w1.x, w1.y, w1.z, w1.w, w2.x, w2.y};
                float n2 = 0.f;
                uint32_t mx = 0;
#pragma unroll
                for (int e = 0; e < 10; e++) {
                    n2 = fmaf(bf_lo(w[e]), bf_lo(w[e]), n2);
                    n2 = fmaf(bf_hi(w[e]), bf_hi(w[e]), n2);
                    mx = max(mx, max(w[e] & 0x7FFFu, (w[e] >> 16) & 0x7FFFu));
                }
                if (!((MUFU_MASK >> ((2 * cta + g) & 7)) & 1)) n2 *= 4.f;
                uint32_t st = lane < 16 ? min(((__float_as_uint(n2) & 0x7FFFFFFFu) + 0xFFFFu) >> 16, 0x7FFFu) : mx;
#pragma unroll
                for (int x = 1; x < 16; x <<= 1) st = max(st, __shfl_xor_sync(~0u, st, x));
                const uint32_t sv = __shfl_sync(~0u, st, 16);
                fence_async();
                __threadfence();
                __syncwarp();
                if (lane == 0) {
                    const unsigned long long f = ((unsigned long long)tag << 32) | (st << 16) | sv;
                    asm volatile("st.release.gpu.global.u64 [%0], %1;" :: "l"(g_flag_kv + cta), "l"(f) : "memory");
                }
            }
            TS(17);
        } else if (wg == 1 && warp == 0) {
            uint32_t sk = 0, sv = 0;
#pragma unroll
            for (int u = 0; u < 4; u++) {
                unsigned long long f;
                uint32_t spin = 0;
#pragma unroll 1
                while ((uint32_t)((f = ld_acquire64(g_flag_kv + lane + 32 * u)) >> 32) != tag) { if (++spin > (1u << 17)) break; }
                sk = max(sk, ((uint32_t)f >> 16));
                sv = max(sv, (uint32_t)f & 0xFFFFu);
            }
            sk = __reduce_max_sync(~0u, sk);
            sv = __reduce_max_sync(~0u, sv);
            if (lane == 0) {
                const bool vok = sv == 0 || (sv >= ((127 - 40) << 7) && sv <= ((127 + 40) << 7));
                sts32(sb + OFF_STAT, vok ? sk << 16 : 0x7FC00000u);
                fence_async();
#pragma unroll
                for (int s = 0; s < 3; s++) {
                    mbar_expect(sb + BAR_FULL_KV + s * 8, RING_BYTES);
                    bulk1d(sb + OFF_RING + s * RING_BYTES, g_kv + s * RING_BYTES, RING_BYTES, sb + BAR_FULL_KV + s * 8);
                }
            }
            __syncwarp();
            TS(18);
        }
        bar_sync(4, 640);
        Ring ring{0, 0};
#pragma unroll 1
        for (int pass = 0; pass < 2; pass++) {
            uint32_t qf[6];
            const uint32_t qa = sb + (pass ? OFF_Q2 : OFF_Q1) + r0 * QPITCH + wg * 40 + q * 4;
            qf[0] = lds32(qa); qf[1] = lds32(qa + 8 * QPITCH);
            qf[2] = lds32(qa + 16); qf[3] = lds32(qa + 8 * QPITCH + 16);
            qf[4] = q < 2 ? lds32(qa + 32) : 0u; qf[5] = q < 2 ? lds32(qa + 8 * QPITCH + 32) : 0u;
            if (pass == 0) { bar_arrive(5, 640); mbar_wait(sb + BAR_FULL_KV, 0); if (wg == 0) TS(19); }
            float n0 = 0.f, n1 = 0.f;
#pragma unroll
            for (int e = 0; e < 3; e++) {
                n0 = fmaf(bf_lo(qf[2 * e]), bf_lo(qf[2 * e]), fmaf(bf_hi(qf[2 * e]), bf_hi(qf[2 * e]), n0));
                n1 = fmaf(bf_lo(qf[2 * e + 1]), bf_lo(qf[2 * e + 1]), fmaf(bf_hi(qf[2 * e + 1]), bf_hi(qf[2 * e + 1]), n1));
            }
            n0 += __shfl_xor_sync(~0u, n0, 1); n0 += __shfl_xor_sync(~0u, n0, 2);
            n1 += __shfl_xor_sync(~0u, n1, 1); n1 += __shfl_xor_sync(~0u, n1, 2);
            const float k2 = __uint_as_float(lds32(sb + OFF_STAT));
            const uint32_t bad = !(n0 * k2 <= 4000.f && n1 * k2 <= 4000.f);
            uint32_t anybad;
            asm volatile("{\n.reg .pred p, r;\nsetp.ne.u32 p, %1, 0;\nbar.red.or.pred r, %2, 128, p;\nselp.u32 %0, 1, 0, r;\n}" : "=r"(anybad) : "r"(bad), "r"(8 + wg) : "memory");
            float o[12];
#pragma unroll
            for (int k = 0; k < 12; k++) o[k] = 0.f;
            fence_regs(o);
            if (!anybad) {
                if (q >= 2) qf[4] = qf[5] = q == 2 ? 0x3F803F80u : 0x00003F80u;
                attend<true>(sb, ring, pass, qf, o);
            } else {
                attend<false>(sb, ring, pass, qf, o);
            }
            const float i0 = rcpf(__shfl_sync(~0u, o[8], (lane & ~3) | 2)), i1 = rcpf(__shfl_sync(~0u, o[10], (lane & ~3) | 2));
            __nv_bfloat16* dst = g_oa + (128 * i + 64 * pass + r0) * 640 + 20 * (4 * j + wg) + 2 * q;
#pragma unroll
            for (int b = 0; b < 3; b++) {
                if (b < 2 || q < 2) {
                    *reinterpret_cast<uint32_t*>(dst + 8 * b) = pack_bf16(o[4 * b] * i0, o[4 * b + 1] * i0);
                    *reinterpret_cast<uint32_t*>(dst + 8 * 640 + 8 * b) = pack_bf16(o[4 * b + 2] * i1, o[4 * b + 3] * i1);
                }
            }
            if (wg == 0) TS(20 + pass);
        }
        fence_async();
        __threadfence();
        bar_sync(8 + wg, 128);
        if ((tid & 127) == 0) st_release(g_flag_a + cta * 4 + wg, tag);
        TS(22 + wg);
    } else {
        asm volatile("setmaxnreg.inc.sync.aligned.u32 128;");
        const uint32_t ep = (lane >> 2) * 16 + q * 4;
#pragma unroll 1
        for (int pass = 0; pass < 6; pass++) {
        if (pass == 4) {
#pragma unroll 1
        for (int u = tid - 512; u < 880; u += 128) sts128(sb + OFF_KVB + u * 16, 0u, 0u, 0u, 0u);
        if (warp == 0) poll_flag(g_flag_b1 + (lane & 15) * 8 + j, lane < 16, tag);
        bar_sync(6, 128);
        TS(7);
#pragma unroll 1
        for (int f = tid - 512; f < 480; f += 128) {
            float4 s = make_float4(0.f, 0.f, 0.f, 0.f);
#pragma unroll 1
            for (int x0 = 0; x0 < 16; x0 += 8) {
                float4 v[8];
#pragma unroll
                for (int x = 0; x < 8; x++) v[x] = __ldcg(reinterpret_cast<const float4*>(g_part + ((x0 + x) * 8 + j) * 1920) + f);
#pragma unroll
                for (int x = 0; x < 8; x++) { s.x += v[x].x; s.y += v[x].y; s.z += v[x].z; s.w += v[x].w; }
            }
            const int m = f / 6, e0 = (f - 6 * m) * 4, h = m / 20;
            const uint32_t x0 = sb + OFF_KVB + (m >> 3) * 1408 + (m & 7) * 16;
            if (e0 < 20) {
                const int n = 20 * h + e0;
                sts64(x0 + (n >> 3) * 128 + (n & 7) * 2, pack_bf16(s.x, s.y), pack_bf16(s.z, s.w));
            } else {
                sts16(x0 + 1280 + h * 2, (uint16_t)pack_bf16(s.x, 0.f));
            }
        }
        fence_async_smem();
        bar_sync(6, 128);
        {
            __nv_bfloat16* dst = g_ob + (128 * i + r0) * 640 + 80 * j + 2 * q;
#pragma unroll 1
            for (int half = 0; half < 2; half++) linear_out(sb, half, dst + half * 64 * 640, q);
        }
        fence_async();
        __threadfence();
        bar_sync(6, 128);
        if (warp == 0) {
            if (lane == 0) st_release(g_flag_b2 + cta, tag);
            poll_flag(g_flag_b2 + i * 8 + (lane & 7), lane < 8, tag);
            if (lane == 0) {
                fence_async();
#pragma unroll 1
                for (int it = 40; it < 43; it++) gemm_issue(P, sb, it, i, j);
            }
            __syncwarp();
        }
        TS(8);
        }
        float a[40], b[40];
        gemm_pass(P, sb, 10 * pass, pass < 4 ? 40 : 10 * pass + 10, i, j, a, b);
        if (pass == 0) {
        TS(1);
        bar_sync(2, 256);
#pragma unroll
        for (int k = 0; k < 10; k++) {
            const uint32_t x = sb + r0 * QPITCH + k * 16 + q * 4;
            sts32(x + OFF_Q1, pack_bf16(a[4 * k] * QSCALE, a[4 * k + 1] * QSCALE));
            sts32(x + OFF_Q1 + 8 * QPITCH, pack_bf16(a[4 * k + 2] * QSCALE, a[4 * k + 3] * QSCALE));
            sts32(x + OFF_Q2, pack_bf16(b[4 * k] * QSCALE, b[4 * k + 1] * QSCALE));
            sts32(x + OFF_Q2 + 8 * QPITCH, pack_bf16(b[4 * k + 2] * QSCALE, b[4 * k + 3] * QSCALE));
        }
        bar_arrive(4, 640);
        TS(2);
        } else if (pass == 1 || pass == 3) {
        TS(pass == 1 ? 3 : 6);
        if (pass == 1) bar_sync(5, 640);
#pragma unroll
        for (int k = 0; k < 10; k++) {
            const uint32_t x = sb + OFF_PK + 2 * warp * 1280 + k * 128 + ep;
            sts32(x, pack_bf16(phi(a[4 * k]), phi(a[4 * k + 1])));
            sts32(x + 1280, pack_bf16(phi(a[4 * k + 2]), phi(a[4 * k + 3])));
            sts32(x + 8 * 1280, pack_bf16(phi(b[4 * k]), phi(b[4 * k + 1])));
            sts32(x + 9 * 1280, pack_bf16(phi(b[4 * k + 2]), phi(b[4 * k + 3])));
        }
        if (pass == 1) {
            const int t = tid - 512;
            const uint32_t x = sb + OFF_V + (t >> 3) * 1536 + (t & 7) * 16;
            sts128(x, 0x3F80u, 0u, 0u, 0u);
            sts128(x + 11 * 128, 0x3F80u, 0u, 0u, 0u);
        }
        } else if (pass == 2) {
        TS(4);
#pragma unroll
        for (int k = 0; k < 10; k++) {
            const uint32_t x = sb + OFF_V + 2 * warp * 1536 + (k + 1) * 128 + ep;
            sts32(x, pack_bf16(a[4 * k], a[4 * k + 1]));
            sts32(x + 1536, pack_bf16(a[4 * k + 2], a[4 * k + 3]));
            sts32(x + 8 * 1536, pack_bf16(b[4 * k], b[4 * k + 1]));
            sts32(x + 9 * 1536, pack_bf16(b[4 * k + 2], b[4 * k + 3]));
        }
        fence_async_smem();
        bar_sync(6, 128);
        {
            float d1[36], d2[16]; zero_regs(d1); zero_regs(d2);
            const uint32_t la = ((sb + OFF_PK) >> 4) + dlo(1280), lb = ((sb + OFF_V) >> 4) + dlo(1536);
            WG_FENCE();
            wg_ss_n72_ta1_tb1<8, 8>(d1, la, lb);
            wg_ss_n32_ta1_tb1<8, 8>(d2, la + 16, lb + 64);
#pragma unroll
            for (int k = 1; k < 8; k++) {
                wg_ss_n72_ta1_tb1<8, 8>(d1, la + 160 * k, lb + 192 * k);
                wg_ss_n32_ta1_tb1<8, 8>(d2, la + 16 + 160 * k, lb + 64 + 192 * k);
            }
            WG_COMMIT();
            WG_WAIT(0);
            fence_regs(d1); fence_regs(d2);
            float* part = g_part + cta * 1920;
#pragma unroll
            for (int hh = 0; hh < 2; hh++) {
                const int m = r0 + 8 * hh;
                if (m < 60) {
                    const int h20 = (m / 20) * 20;
                    if (q == 0) part[m * 24 + 20] = d1[2 * hh];
#pragma unroll
                    for (int k = 1; k < 9; k++) {
                        const int e = 8 * (k - 1) + 2 * q - h20;
                        if (e >= 0 && e < 20) *reinterpret_cast<float2*>(part + m * 24 + e) = make_float2(d1[4 * k + 2 * hh], d1[4 * k + 2 * hh + 1]);
                    }
                }
                if (m >= 44) {
                    if (q == 0) part[(m + 16) * 24 + 20] = d2[12 + 2 * hh];
#pragma unroll
                    for (int k = 0; k < 3; k++) {
                        const int e = 8 * k + 2 * q - 4;
                        if (e >= 0) *reinterpret_cast<float2*>(part + (m + 16) * 24 + e) = make_float2(d2[4 * k + 2 * hh], d2[4 * k + 2 * hh + 1]);
                    }
                }
            }
            __threadfence();
            bar_sync(6, 128);
            if (tid == 512) st_release(g_flag_b1 + cta, tag);
        }
        TS(5);
        } else {
        __nv_bfloat16* out = P.out + (128 * i + r0) * 1280 + 80 * j + 2 * q + (pass == 4 ? 640 : 0);
        store_tile(out, 1280, a);
        store_tile(out + 64 * 1280, 1280, b);
        TS(pass == 4 ? 9 : 11);
        if (pass == 4 && warp == 0) {
            poll_flag(g_flag_a + i * 32 + lane, true, tag);
            if (lane == 0) {
                fence_async();
#pragma unroll 1
                for (int it = 50; it < 53; it++) gemm_issue(P, sb, it, i, j);
            }
            __syncwarp();
            TS(10);
        }
        }
        }
        if (cta == 0 && tid == 512) *(volatile uint32_t*)&g_epoch = tag;
    }
}

typedef CUresult (*EncodeFn)(CUtensorMap*, CUtensorMapDataType, cuuint32_t, void*, const cuuint64_t*, const cuuint64_t*,
                             const cuuint32_t*, const cuuint32_t*, CUtensorMapInterleave, CUtensorMapSwizzle,
                             CUtensorMapL2promotion, CUtensorMapFloatOOBfill);

void make_map(EncodeFn enc, CUtensorMap* m, const void* p, uint64_t cols, uint64_t rows, uint32_t box_rows) {
    cuuint64_t dims[2] = {cols, rows}, strides[1] = {cols * 2};
    cuuint32_t box[2] = {64, box_rows}, es[2] = {1, 1};
    enc(m, CU_TENSOR_MAP_DATA_TYPE_BFLOAT16, 2, const_cast<void*>(p), dims, strides, box, es, CU_TENSOR_MAP_INTERLEAVE_NONE,
        CU_TENSOR_MAP_SWIZZLE_128B, CU_TENSOR_MAP_L2_PROMOTION_L2_128B, CU_TENSOR_MAP_FLOAT_OOB_FILL_NONE);
}

}

extern "C" void kernel_launch(void* const* d_in, const int* in_sizes, int n_in, void* d_out, int out_size) {
    static EncodeFn enc = nullptr;
    static void *oa = nullptr, *ob = nullptr;
    if (!enc) {
        void* fn = nullptr;
        cudaDriverEntryPointQueryResult qr;
        cudaGetDriverEntryPoint("cuTensorMapEncodeTiled", &fn, cudaEnableDefault, &qr);
        enc = (EncodeFn)fn;
        cudaGetSymbolAddress(&oa, g_oa);
        cudaGetSymbolAddress(&ob, g_ob);
        cudaFuncSetAttribute(fused_kernel, cudaFuncAttributeMaxDynamicSharedMemorySize, SMEM_BYTES);
    }
    Params P;
    make_map(enc, &P.xa, d_in[0], 640, 2048, 128);
    make_map(enc, &P.xa16, d_in[0], 640, 2048, 16);
    make_map(enc, &P.wq, d_in[1], 640, 640, 64);
    make_map(enc, &P.xb, d_in[5], 640, 2048, 128);
    make_map(enc, &P.wqkv, d_in[6], 1920, 640, 64);
    make_map(enc, &P.woa, d_in[4], 640, 640, 64);
    make_map(enc, &P.wob, d_in[7], 640, 640, 64);
    make_map(enc, &P.oa, oa, 640, 2048, 128);
    make_map(enc, &P.ob, ob, 640, 2048, 128);
    P.wk = (const __nv_bfloat16*)d_in[2];
    P.wv = (const __nv_bfloat16*)d_in[3];
    P.out = (__nv_bfloat16*)d_out;
    fused_kernel<<<NCTA, NTHR, SMEM_BYTES, cudaStreamPerThread>>>(P);
}
```

```cpp
#include <cuda_runtime.h>
#include <cuda_bf16.h>
#include <cuda.h>
#include <stdint.h>

namespace {

constexpr int NCTA = 128;
constexpr int NTHR = 768;

constexpr uint32_t OFF_STAGE = 0;
constexpr uint32_t STAGE_BYTES = 32768;
constexpr uint32_t OFF_RING = 98304;
constexpr uint32_t RING_BYTES = 24576;
constexpr uint32_t OFF_WRAW = OFF_RING;
constexpr uint32_t OFF_X16 = OFF_RING + 51200;
constexpr uint32_t OFF_EP = 172032;
constexpr uint32_t OFF_PK = OFF_EP;
constexpr uint32_t OFF_V = OFF_EP + 20480;
constexpr uint32_t OFF_WKV = OFF_EP;
constexpr uint32_t OFF_KVB = OFF_V;
constexpr uint32_t OFF_Q1 = OFF_EP;
constexpr uint32_t OFF_Q2 = 217088;
constexpr uint32_t QPITCH = 176;
constexpr uint32_t OFF_MISC = 228352;
constexpr uint32_t OFF_BAR = OFF_MISC;
constexpr uint32_t BAR_FULL_G = OFF_BAR, BAR_EMPTY_G = OFF_BAR + 24, BAR_FULL_KV = OFF_BAR + 48, BAR_EMPTY_KV = OFF_BAR + 72, BAR_KVIN = OFF_BAR + 96, BAR_DEP = OFF_BAR + 104;
constexpr uint32_t OFF_PUB = OFF_BAR + 120;
constexpr uint32_t OFF_STAT = OFF_BAR + 128;
constexpr uint32_t OFF_IMG = OFF_MISC + 256;
constexpr uint32_t OFF_TS = OFF_IMG + 1536;
constexpr uint32_t SMEM_BYTES = OFF_TS + 256;

#define MUFU_MASK 0xA4
#define PVG 1

#define NPASS 6
constexpr float LOG2E = 1.4426950408889634f;
constexpr float QSCALE = 0.22360679774997896f * LOG2E;

struct Params {
    CUtensorMap xa, xa16, wq, xb, wqkv, woa, wob, oa, ob;
    const __nv_bfloat16* wk;
    const __nv_bfloat16* wv;
    __nv_bfloat16* out;
};

}

__device__ __align__(1024) uint8_t g_kv[256 * 768];
__device__ __align__(1024) __nv_bfloat16 g_oa[2048 * 640];
__device__ __align__(1024) __nv_bfloat16 g_ob[2048 * 640];
__device__ __align__(16) float g_part[128 * 1920];
__device__ unsigned long long g_flag_kv[128];
__device__ uint32_t g_flag_b1[128], g_flag_b2[128], g_flag_a[512];
__device__ uint32_t g_epoch;
#define TS(k)
#define TC(k)

namespace {

template<uint32_t HB> __device__ __forceinline__ void wg_rs_n24_tb1(float (&d)[12], uint32_t a0, uint32_t a1, uint32_t a2, uint32_t a3, uint32_t lb) {
    asm volatile("{\n.reg .pred p;\n.reg .b64 db;\nsetp.ne.b32 p, 1, 0;\nmov.b64 db, {%16, %17};\n"
        "wgmma.mma_async.sync.aligned.m64n24k16.f32.bf16.bf16 {%0, %1, %2, %3, %4, %5, %6, %7, %8, %9, %10, %11}, {%12, %13, %14, %15}, db, p, 1, 1, 1;\n}\n"
        : "+f"(d[0]), "+f"(d[1]), "+f"(d[2]), "+f"(d[3]), "+f"(d[4]), "+f"(d[5]), "+f"(d[6]), "+f"(d[7]), "+f"(d[8]), "+f"(d[9]), "+f"(d[10]), "+f"(d[11])
        : "r"(a0), "r"(a1), "r"(a2), "r"(a3), "r"(lb), "n"(HB));
}
template<uint32_t HB> __device__ __forceinline__ void wg_rs_n64_tb0(float (&d)[32], uint32_t a0, uint32_t a1, uint32_t a2, uint32_t a3, uint32_t lb) {
    asm volatile("{\n.reg .pred p;\n.reg .b64 db;\nsetp.ne.b32 p, 1, 0;\nmov.b64 db, {%36, %37};\n"
        "wgmma.mma_async.sync.aligned.m64n64k16.f32.bf16.bf16 {%0, %1, %2, %3, %4, %5, %6, %7, %8, %9, %10, %11, %12, %13, %14, %15, %16, %17, %18, %19, %20, %21, %22, %23, %24, %25, %26, %27, %28, %29, %30, %31}, {%32, %33, %34, %35}, db, p, 1, 1, 0;\n}\n"
        : "+f"(d[0]), "+f"(d[1]), "+f"(d[2]), "+f"(d[3]), "+f"(d[4]), "+f"(d[5]), "+f"(d[6]), "+f"(d[7]), "+f"(d[8]), "+f"(d[9]), "+f"(d[10]), "+f"(d[11]), "+f"(d[12]), "+f"(d[13]), "+f"(d[14]), "+f"(d[15]), "+f"(d[16]), "+f"(d[17]), "+f"(d[18]), "+f"(d[19]), "+f"(d[20]), "+f"(d[21]), "+f"(d[22]), "+f"(d[23]), "+f"(d[24]), "+f"(d[25]), "+f"(d[26]), "+f"(d[27]), "+f"(d[28]), "+f"(d[29]), "+f"(d[30]), "+f"(d[31])
        : "r"(a0), "r"(a1), "r"(a2), "r"(a3), "r"(lb), "n"(HB));
}
template<uint32_t HB> __device__ __forceinline__ void wg_rs_n64_tb0_init(float (&d)[32], uint32_t a0, uint32_t a1, uint32_t a2, uint32_t a3, uint32_t lb) {
    asm volatile("{\n.reg .pred p;\n.reg .b64 db;\nsetp.ne.b32 p, 0, 0;\nmov.b64 db, {%36, %37};\n"
        "wgmma.mma_async.sync.aligned.m64n64k16.f32.bf16.bf16 {%0, %1, %2, %3, %4, %5, %6, %7, %8, %9, %10, %11, %12, %13, %14, %15, %16, %17, %18, %19, %20, %21, %22, %23, %24, %25, %26, %27, %28, %29, %30, %31}, {%32, %33, %34, %35}, db, p, 1, 1, 0;\n}\n"
        : "=f"(d[0]), "=f"(d[1]), "=f"(d[2]), "=f"(d[3]), "=f"(d[4]), "=f"(d[5]), "=f"(d[6]), "=f"(d[7]), "=f"(d[8]), "=f"(d[9]), "=f"(d[10]), "=f"(d[11]), "=f"(d[12]), "=f"(d[13]), "=f"(d[14]), "=f"(d[15]), "=f"(d[16]), "=f"(d[17]), "=f"(d[18]), "=f"(d[19]), "=f"(d[20]), "=f"(d[21]), "=f"(d[22]), "=f"(d[23]), "=f"(d[24]), "=f"(d[25]), "=f"(d[26]), "=f"(d[27]), "=f"(d[28]), "=f"(d[29]), "=f"(d[30]), "=f"(d[31])
        : "r"(a0), "r"(a1), "r"(a2), "r"(a3), "r"(lb), "n"(HB));
}
template<uint32_t HA, uint32_t HB> __device__ __forceinline__ void wg_ss_n16_ta1_tb0(float (&d)[8], uint32_t la, uint32_t lb) {
    asm volatile("{\n.reg .pred p;\n.reg .b64 da, db;\nsetp.ne.b32 p, 1, 0;\nmov.b64 da, {%8, %10};\nmov.b64 db, {%9, %11};\n"
        "wgmma.mma_async.sync.aligned.m64n16k16.f32.bf16.bf16 {%0, %1, %2, %3, %4, %5, %6, %7}, da, db, p, 1, 1, 1, 0;\n}\n"
        : "+f"(d[0]), "+f"(d[1]), "+f"(d[2]), "+f"(d[3]), "+f"(d[4]), "+f"(d[5]), "+f"(d[6]), "+f"(d[7])
        : "r"(la), "r"(lb), "n"(HA), "n"(HB));
}
template<uint32_t HA, uint32_t HB> __device__ __forceinline__ void wg_ss_n16_ta1_tb0_init(float (&d)[8], uint32_t la, uint32_t lb) {
    asm volatile("{\n.reg .pred p;\n.reg .b64 da, db;\nsetp.ne.b32 p, 0, 0;\nmov.b64 da, {%8, %10};\nmov.b64 db, {%9, %11};\n"
        "wgmma.mma_async.sync.aligned.m64n16k16.f32.bf16.bf16 {%0, %1, %2, %3, %4, %5, %6, %7}, da, db, p, 1, 1, 1, 0;\n}\n"
        : "=f"(d[0]), "=f"(d[1]), "=f"(d[2]), "=f"(d[3]), "=f"(d[4]), "=f"(d[5]), "=f"(d[6]), "=f"(d[7])
        : "r"(la), "r"(lb), "n"(HA), "n"(HB));
}
template<uint32_t HA, uint32_t HB> __device__ __forceinline__ void wg_ss_n32_ta1_tb1(float (&d)[16], uint32_t la, uint32_t lb) {
    asm volatile("{\n.reg .pred p;\n.reg .b64 da, db;\nsetp.ne.b32 p, 1, 0;\nmov.b64 da, {%16, %18};\nmov.b64 db, {%17, %19};\n"
        "wgmma.mma_async.sync.aligned.m64n32k16.f32.bf16.bf16 {%0, %1, %2, %3, %4, %5, %6, %7, %8, %9, %10, %11, %12, %13, %14, %15}, da, db, p, 1, 1, 1, 1;\n}\n"
        : "+f"(d[0]), "+f"(d[1]), "+f"(d[2]), "+f"(d[3]), "+f"(d[4]), "+f"(d[5]), "+f"(d[6]), "+f"(d[7]), "+f"(d[8]), "+f"(d[9]), "+f"(d[10]), "+f"(d[11]), "+f"(d[12]), "+f"(d[13]), "+f"(d[14]), "+f"(d[15])
        : "r"(la), "r"(lb), "n"(HA), "n"(HB));
}
template<uint32_t HA, uint32_t HB> __device__ __forceinline__ void wg_ss_n72_ta1_tb1(float (&d)[36], uint32_t la, uint32_t lb) {
    asm volatile("{\n.reg .pred p;\n.reg .b64 da, db;\nsetp.ne.b32 p, 1, 0;\nmov.b64 da, {%36, %38};\nmov.b64 db, {%37, %39};\n"
        "wgmma.mma_async.sync.aligned.m64n72k16.f32.bf16.bf16 {%0, %1, %2, %3, %4, %5, %6, %7, %8, %9, %10, %11, %12, %13, %14, %15, %16, %17, %18, %19, %20, %21, %22, %23, %24, %25, %26, %27, %28, %29, %30, %31, %32, %33, %34, %35}, da, db, p, 1, 1, 1, 1;\n}\n"
        : "+f"(d[0]), "+f"(d[1]), "+f"(d[2]), "+f"(d[3]), "+f"(d[4]), "+f"(d[5]), "+f"(d[6]), "+f"(d[7]), "+f"(d[8]), "+f"(d[9]), "+f"(d[10]), "+f"(d[11]), "+f"(d[12]), "+f"(d[13]), "+f"(d[14]), "+f"(d[15]), "+f"(d[16]), "+f"(d[17]), "+f"(d[18]), "+f"(d[19]), "+f"(d[20]), "+f"(d[21]), "+f"(d[22]), "+f"(d[23]), "+f"(d[24]), "+f"(d[25]), "+f"(d[26]), "+f"(d[27]), "+f"(d[28]), "+f"(d[29]), "+f"(d[30]), "+f"(d[31]), "+f"(d[32]), "+f"(d[33]), "+f"(d[34]), "+f"(d[35])
        : "r"(la), "r"(lb), "n"(HA), "n"(HB));
}
template<uint32_t HA, uint32_t HB> __device__ __forceinline__ void wg_ss_n80_ta0_tb1(float (&d)[40], uint32_t la, uint32_t lb) {
    asm volatile("{\n.reg .pred p;\n.reg .b64 da, db;\nsetp.ne.b32 p, 1, 0;\nmov.b64 da, {%40, %42};\nmov.b64 db, {%41, %43};\n"
        "wgmma.mma_async.sync.aligned.m64n80k16.f32.bf16.bf16 {%0, %1, %2, %3, %4, %5, %6, %7, %8, %9, %10, %11, %12, %13, %14, %15, %16, %17, %18, %19, %20, %21, %22, %23, %24, %25, %26, %27, %28, %29, %30, %31, %32, %33, %34, %35, %36, %37, %38, %39}, da, db, p, 1, 1, 0, 1;\n}\n"
        : "+f"(d[0]), "+f"(d[1]), "+f"(d[2]), "+f"(d[3]), "+f"(d[4]), "+f"(d[5]), "+f"(d[6]), "+f"(d[7]), "+f"(d[8]), "+f"(d[9]), "+f"(d[10]), "+f"(d[11]), "+f"(d[12]), "+f"(d[13]), "+f"(d[14]), "+f"(d[15]), "+f"(d[16]), "+f"(d[17]), "+f"(d[18]), "+f"(d[19]), "+f"(d[20]), "+f"(d[21]), "+f"(d[22]), "+f"(d[23]), "+f"(d[24]), "+f"(d[25]), "+f"(d[26]), "+f"(d[27]), "+f"(d[28]), "+f"(d[29]), "+f"(d[30]), "+f"(d[31]), "+f"(d[32]), "+f"(d[33]), "+f"(d[34]), "+f"(d[35]), "+f"(d[36]), "+f"(d[37]), "+f"(d[38]), "+f"(d[39])
        : "r"(la), "r"(lb), "n"(HA), "n"(HB));
}
template<uint32_t HA, uint32_t HB> __device__ __forceinline__ void wg_ss_n88_ta0_tb1(float (&d)[44], uint32_t la, uint32_t lb) {
    asm volatile("{\n.reg .pred p;\n.reg .b64 da, db;\nsetp.ne.b32 p, 1, 0;\nmov.b64 da, {%44, %46};\nmov.b64 db, {%45, %47};\n"
        "wgmma.mma_async.sync.aligned.m64n88k16.f32.bf16.bf16 {%0, %1, %2, %3, %4, %5, %6, %7, %8, %9, %10, %11, %12, %13, %14, %15, %16, %17, %18, %19, %20, %21, %22, %23, %24, %25, %26, %27, %28, %29, %30, %31, %32, %33, %34, %35, %36, %37, %38, %39, %40, %41, %42, %43}, da, db, p, 1, 1, 0, 1;\n}\n"
        : "+f"(d[0]), "+f"(d[1]), "+f"(d[2]), "+f"(d[3]), "+f"(d[4]), "+f"(d[5]), "+f"(d[6]), "+f"(d[7]), "+f"(d[8]), "+f"(d[9]), "+f"(d[10]), "+f"(d[11]), "+f"(d[12]), "+f"(d[13]), "+f"(d[14]), "+f"(d[15]), "+f"(d[16]), "+f"(d[17]), "+f"(d[18]), "+f"(d[19]), "+f"(d[20]), "+f"(d[21]), "+f"(d[22]), "+f"(d[23]), "+f"(d[24]), "+f"(d[25]), "+f"(d[26]), "+f"(d[27]), "+f"(d[28]), "+f"(d[29]), "+f"(d[30]), "+f"(d[31]), "+f"(d[32]), "+f"(d[33]), "+f"(d[34]), "+f"(d[35]), "+f"(d[36]), "+f"(d[37]), "+f"(d[38]), "+f"(d[39]), "+f"(d[40]), "+f"(d[41]), "+f"(d[42]), "+f"(d[43])
        : "r"(la), "r"(lb), "n"(HA), "n"(HB));
}

#define WG_FENCE() asm volatile("wgmma.fence.sync.aligned;" ::: "memory")
#define WG_COMMIT() asm volatile("wgmma.commit_group.sync.aligned;" ::: "memory")
#define WG_WAIT(n) asm volatile("wgmma.wait_group.sync.aligned %0;" :: "n"(n) : "memory")
template <int NR> __device__ __forceinline__ void fence_regs(float (&d)[NR]) {
#pragma unroll
    for (int i = 0; i < NR; i++) asm volatile("" : "+f"(d[i]) :: "memory");
}
template <int NR> __device__ __forceinline__ void zero_regs(float (&d)[NR]) {
#pragma unroll
    for (int i = 0; i < NR; i++) asm volatile("mov.b32 %0, 0;" : "=f"(d[i]) :: "memory");
}
constexpr uint32_t SW128 = 1u << 30;
__device__ __forceinline__ constexpr uint32_t dlo(uint32_t lbo) { return (lbo >> 4) << 16; }

__device__ __forceinline__ void bar_sync(int id, int n) { asm volatile("bar.sync %0, %1;" :: "r"(id), "r"(n) : "memory"); }
__device__ __forceinline__ void bar_arrive(int id, int n) { asm volatile("bar.arrive %0, %1;" :: "r"(id), "r"(n) : "memory"); }
__device__ __forceinline__ void mbar_init(uint32_t bar, uint32_t cnt) { asm volatile("mbarrier.init.shared::cta.b64 [%0], %1;" :: "r"(bar), "r"(cnt) : "memory"); }
__device__ __forceinline__ void mbar_arrive(uint32_t bar) { asm volatile("mbarrier.arrive.shared::cta.b64 _, [%0];" :: "r"(bar) : "memory"); }
__device__ __forceinline__ void mbar_expect(uint32_t bar, uint32_t bytes) { asm volatile("mbarrier.arrive.expect_tx.shared::cta.b64 _, [%0], %1;" :: "r"(bar), "r"(bytes) : "memory"); }
__device__ __forceinline__ void mbar_wait(uint32_t bar, uint32_t parity) {
    asm volatile("{\n.reg .pred p;\n.reg .u32 n;\nmov.u32 n, 0;\n"
                 "MW_LOOP:\nmbarrier.try_wait.parity.shared::cta.b64 p, [%0], %1;\n@p bra.uni MW_DONE;\n"
                 "add.u32 n, n, 1;\nsetp.lt.u32 p, n, 32768;\n@p bra.uni MW_LOOP;\nMW_DONE:\n}"
                 :: "r"(bar), "r"(parity) : "memory");
}
__device__ __forceinline__ void count_wait(uint32_t addr, uint32_t seen, uint32_t need) {
    asm volatile("{\n.reg .pred p;\n.reg .u32 n, v;\nmov.u32 n, 0;\nmov.u32 v, %1;\n"
                 "CW_LOOP:\nsetp.ge.u32 p, v, %2;\n@p bra.uni CW_DONE;\nld.volatile.shared.u32 v, [%0];\n"
                 "add.u32 n, n, 1;\nsetp.lt.u32 p, n, 0x400000;\n@p bra.uni CW_LOOP;\nCW_DONE:\n}"
                 :: "r"(addr), "r"(seen), "r"(need) : "memory");
}
__device__ __forceinline__ void tma2d(uint32_t dst, const CUtensorMap* m, int x, int y, uint32_t bar) {
    asm volatile("cp.async.bulk.tensor.2d.shared::cluster.global.mbarrier::complete_tx::bytes [%0], [%1, {%2, %3}], [%4];"
                 :: "r"(dst), "l"(m), "r"(x), "r"(y), "r"(bar) : "memory");
}
__device__ __forceinline__ void bulk1d(uint32_t dst, const void* src, uint32_t bytes, uint32_t bar) {
    asm volatile("cp.async.bulk.shared::cluster.global.mbarrier::complete_tx::bytes [%0], [%1], %2, [%3];"
                 :: "r"(dst), "l"(src), "r"(bytes), "r"(bar) : "memory");
}
__device__ __forceinline__ bool elect_one() {
    uint32_t p;
    asm volatile("{\n.reg .pred p;\nelect.sync _|p, 0xffffffff;\nselp.u32 %0, 1, 0, p;\n}" : "=r"(p));
    return p;
}
__device__ __forceinline__ void fence_async() { asm volatile("fence.proxy.async.global;" ::: "memory"); }
__device__ __forceinline__ void fence_async_smem() { asm volatile("fence.proxy.async.shared::cta;" ::: "memory"); }
__device__ __forceinline__ void st_release(uint32_t* p, uint32_t v) { asm volatile("st.release.gpu.global.u32 [%0], %1;" :: "l"(p), "r"(v) : "memory"); }
__device__ __forceinline__ void fence_acq() { asm volatile("fence.acq_rel.gpu;" ::: "memory"); }
__device__ __forceinline__ uint32_t ld_relaxed(const uint32_t* p) { uint32_t v; asm volatile("ld.relaxed.gpu.global.u32 %0, [%1];" : "=r"(v) : "l"(p) : "memory"); return v; }
__device__ __forceinline__ unsigned long long ld_relaxed64(const unsigned long long* p) { unsigned long long v; asm volatile("ld.relaxed.gpu.global.u64 %0, [%1];" : "=l"(v) : "l"(p) : "memory"); return v; }
__device__ __forceinline__ void poll_flag(const uint32_t* p, bool active, uint32_t tag) {
    uint32_t spin = 0;
    if (active) {
#pragma unroll 1
        while (ld_relaxed(p) != tag) { if (++spin > (1u << 17)) break; }
    }
    __syncwarp();
    fence_acq();
}
__device__ __forceinline__ uint32_t lds32(uint32_t a) { uint32_t v; asm volatile("ld.shared.u32 %0, [%1];" : "=r"(v) : "r"(a) : "memory"); return v; }
__device__ __forceinline__ void sts32(uint32_t a, uint32_t v) { asm volatile("st.shared.u32 [%0], %1;" :: "r"(a), "r"(v) : "memory"); }
__device__ __forceinline__ void sts16(uint32_t a, uint16_t v) { asm volatile("st.shared.u16 [%0], %1;" :: "r"(a), "h"(v) : "memory"); }
__device__ __forceinline__ void sts64(uint32_t a, uint32_t x, uint32_t y) { asm volatile("st.shared.v2.u32 [%0], {%1, %2};" :: "r"(a), "r"(x), "r"(y) : "memory"); }
__device__ __forceinline__ void sts128(uint32_t a, uint32_t x, uint32_t y, uint32_t z, uint32_t w) { asm volatile("st.shared.v4.u32 [%0], {%1, %2, %3, %4};" :: "r"(a), "r"(x), "r"(y), "r"(z), "r"(w) : "memory"); }
__device__ __forceinline__ uint2 lds64(uint32_t a) { uint2 v; asm volatile("ld.shared.v2.u32 {%0, %1}, [%2];" : "=r"(v.x), "=r"(v.y) : "r"(a) : "memory"); return v; }
__device__ __forceinline__ uint4 lds128(uint32_t a) { uint4 v; asm volatile("ld.shared.v4.u32 {%0, %1, %2, %3}, [%4];" : "=r"(v.x), "=r"(v.y), "=r"(v.z), "=r"(v.w) : "r"(a) : "memory"); return v; }
__device__ __forceinline__ float ex2f(float x) { float y; asm("ex2.approx.ftz.f32 %0, %1;" : "=f"(y) : "f"(x)); return y; }
__device__ __forceinline__ float rcpf(float x) { float y; asm("div.full.f32 %0, 0f3F800000, %1;" : "=f"(y) : "f"(x)); return y; }
__device__ __forceinline__ uint32_t pack_bf16(float lo, float hi) { uint32_t r; asm("cvt.rn.bf16x2.f32 %0, %1, %2;" : "=r"(r) : "f"(hi), "f"(lo)); return r; }
__device__ __forceinline__ float bf_lo(uint32_t v) { return __uint_as_float(v << 16); }
__device__ __forceinline__ float bf_hi(uint32_t v) { return __uint_as_float(v & 0xFFFF0000u); }
__device__ __forceinline__ float phi(float t) { return (t > 0.f ? t + 1.f : ex2f(t * LOG2E)) + 1e-6f; }

__device__ __forceinline__ uint32_t exp2_pair(float t0, float t1, uint32_t ca) {
    uint32_t y, u, g;
    asm("prmt.b32 %0, %1, %2, 0x6521;" : "=r"(y) : "r"(__float_as_uint(t0)), "r"(__float_as_uint(t1)));
    u = y & 0x007F007Fu;
    asm("{.reg .b32 c; mov.b32 c, 0xF963F963; fma.rn.f16x2 %0, %1, c, %2;}" : "=r"(g) : "r"(u), "r"(ca));
    asm("mul.rn.f16x2 %0, %1, %2;" : "=r"(g) : "r"(g), "r"(u));
    return y - g;
}

constexpr uint32_t HI_K = 768 >> 4, HI_V = 128 >> 4;
constexpr uint32_t LO_K = dlo(128), LO_V = dlo(768) + 24;

template <int J> __device__ __forceinline__ void exp_steps(const float (&s)[32], uint32_t (&p)[16], float (&o)[12], uint32_t lo, uint32_t ca) {
    if constexpr (J < 4) {
#pragma unroll
        for (int g = 2 * J; g < 2 * J + 2; g++) {
            if ((MUFU_MASK >> g) & 1) {
                p[2 * g] = pack_bf16(ex2f(s[4 * g]), ex2f(s[4 * g + 1]));
                p[2 * g + 1] = pack_bf16(ex2f(s[4 * g + 2]), ex2f(s[4 * g + 3]));
            } else {
                p[2 * g] = exp2_pair(s[4 * g], s[4 * g + 1], ca);
                p[2 * g + 1] = exp2_pair(s[4 * g + 2], s[4 * g + 3], ca);
            }
        }
        if constexpr (PVG == 1) {
            WG_FENCE();
            wg_rs_n24_tb1<HI_V>(o, p[4 * J], p[4 * J + 1], p[4 * J + 2], p[4 * J + 3], lo + LO_V + J * 96);
        }
        if constexpr (PVG == 2 && (J & 1)) {
            WG_FENCE();
            wg_rs_n24_tb1<HI_V>(o, p[4 * J - 4], p[4 * J - 3], p[4 * J - 2], p[4 * J - 1], lo + LO_V + (J - 1) * 96);
            wg_rs_n24_tb1<HI_V>(o, p[4 * J], p[4 * J + 1], p[4 * J + 2], p[4 * J + 3], lo + LO_V + J * 96);
        }
        exp_steps<J + 1>(s, p, o, lo, ca);
    }
}

struct Ring { uint32_t slot, phase; };
__device__ __forceinline__ void next_stage(Ring& r) { if (++r.slot == 3) { r.slot = 0; r.phase ^= 1; } }

#define BUNR 4
template <bool FAST>
__device__ __forceinline__ void attend(uint32_t sb, uint32_t& slot, int pass, const uint32_t (&q)[6], float (&o)[12], uint32_t ca, uint32_t z0, uint32_t z1) {
    float m0 = -INFINITY, m1 = -INFINITY;
    constexpr int UNR = FAST ? BUNR : 1;
#pragma unroll 1
    for (int c = 0; c < 8; c++) {
        const uint32_t lo0 = (sb + OFF_RING + slot * RING_BYTES) >> 4;
        uint32_t seen;
#pragma unroll UNR
        for (int b = 0; b < 4; b++) {
            const uint32_t lo = lo0 + b * 384;
            float s[32];
            uint32_t p[16];
            WG_FENCE();
            wg_rs_n64_tb0_init<HI_K>(s, q[0], q[1], q[2], q[3], lo + LO_K);
            wg_rs_n64_tb0<HI_K>(s, q[4], q[5], z0, z1, lo + LO_K + 16);
            WG_COMMIT();
            if (UNR < 4 || b == 3) seen = lds32(sb + OFF_PUB);
            WG_WAIT(0);
            fence_regs(s);
            if constexpr (FAST) {
                exp_steps<0>(s, p, o, lo, ca);
            } else {
                fence_regs(o);
                float x0 = m0, x1 = m1;
#pragma unroll
                for (int g = 0; g < 8; g++) {
                    if (!((MUFU_MASK >> g) & 1)) {
#pragma unroll
                        for (int e = 0; e < 4; e++) s[4 * g + e] *= 2.f;
                    }
                    x0 = fmaxf(x0, fmaxf(s[4 * g], s[4 * g + 1]));
                    x1 = fmaxf(x1, fmaxf(s[4 * g + 2], s[4 * g + 3]));
                }
                x0 = fmaxf(x0, __shfl_xor_sync(~0u, x0, 1)); x0 = fmaxf(x0, __shfl_xor_sync(~0u, x0, 2));
                x1 = fmaxf(x1, __shfl_xor_sync(~0u, x1, 1)); x1 = fmaxf(x1, __shfl_xor_sync(~0u, x1, 2));
                const float a0 = ex2f(m0 - x0), a1 = ex2f(m1 - x1);
                m0 = x0; m1 = x1;
#pragma unroll
                for (int b = 0; b < 3; b++) { o[4 * b] *= a0; o[4 * b + 1] *= a0; o[4 * b + 2] *= a1; o[4 * b + 3] *= a1; }
#pragma unroll
                for (int g = 0; g < 8; g++) {
                    p[2 * g] = pack_bf16(ex2f(s[4 * g] - x0), ex2f(s[4 * g + 1] - x0));
                    p[2 * g + 1] = pack_bf16(ex2f(s[4 * g + 2] - x1), ex2f(s[4 * g + 3] - x1));
                }
            }
            if constexpr (!FAST || PVG == 0) {
                WG_FENCE();
#pragma unroll
                for (int k = 0; k < 4; k++) wg_rs_n24_tb1<HI_V>(o, p[4 * k], p[4 * k + 1], p[4 * k + 2], p[4 * k + 3], lo + LO_V + k * 96);
            }
            WG_COMMIT();
            WG_WAIT(0);
            fence_regs(o);
        }
        if ((threadIdx.x & 31) == 0) mbar_arrive(sb + BAR_EMPTY_KV + slot * 8);
        slot = slot == 2 ? 0 : slot + 1;
        count_wait(sb + OFF_PUB, seen, min(pass * 8 + c + 2, 16));
    }
}

__device__ __forceinline__ void gemm_issue(uint32_t sb, const Ring& r, float (&a)[40], float (&b)[40]) {
    mbar_wait(sb + BAR_FULL_G + r.slot * 8, r.phase);
    const uint32_t lx = ((sb + OFF_STAGE + r.slot * STAGE_BYTES) >> 4) + dlo(16);
    const uint32_t lw = lx + (16384 >> 4) + dlo(8192) - dlo(16);
    WG_FENCE();
#pragma unroll
    for (int k = 0; k < 4; k++) {
        wg_ss_n80_ta0_tb1<SW128 | 64, SW128 | 64>(a, lx + 2 * k, lw + 128 * k);
        wg_ss_n80_ta0_tb1<SW128 | 64, SW128 | 64>(b, lx + 512 + 2 * k, lw + 128 * k);
    }
    WG_COMMIT();
}
__device__ __forceinline__ void gemm_pass(uint32_t sb, Ring& r, float (&a)[40], float (&b)[40]) {
    zero_regs(a); zero_regs(b);
    uint32_t prev = 0;
#pragma unroll 1
    for (int c = 0; c < 10; c++) {
        gemm_issue(sb, r, a, b);
        WG_WAIT(1);
        if (c > 0 && (threadIdx.x & 31) == 0) mbar_arrive(prev);
        prev = sb + BAR_EMPTY_G + r.slot * 8;
        next_stage(r);
    }
    WG_WAIT(0);
    if ((threadIdx.x & 31) == 0) mbar_arrive(prev);
    fence_regs(a); fence_regs(b);
}

__device__ __forceinline__ void store_tile(__nv_bfloat16* dst, int pitch, const float (&a)[40]) {
#pragma unroll
    for (int b = 0; b < 10; b++) {
        *reinterpret_cast<uint32_t*>(dst + 8 * b) = pack_bf16(a[4 * b], a[4 * b + 1]);
        *reinterpret_cast<uint32_t*>(dst + 8 * pitch + 8 * b) = pack_bf16(a[4 * b + 2], a[4 * b + 3]);
    }
}

__device__ __forceinline__ void linear_out(uint32_t sb, int half, __nv_bfloat16* dst, int q) {
    float d[44]; zero_regs(d);
    const uint32_t la = ((sb + OFF_PK + half * 10240) >> 4) + dlo(128), lb = ((sb + OFF_KVB) >> 4) + dlo(1408);
    WG_FENCE();
    wg_ss_n88_ta0_tb1<80, 8>(d, la, lb);
#pragma unroll
    for (int k = 1; k < 5; k++) wg_ss_n88_ta0_tb1<80, 8>(d, la + 16 * k, lb + 176 * k);
    WG_COMMIT();
    WG_WAIT(0);
    fence_regs(d);
    float r0[4], r1[4];
    const int base = (threadIdx.x & 31) & ~3;
#pragma unroll
    for (int h = 0; h < 4; h++) {
        r0[h] = rcpf(__shfl_sync(~0u, d[40 + (h & 1)], base + (h >> 1)) + 1e-6f);
        r1[h] = rcpf(__shfl_sync(~0u, d[42 + (h & 1)], base + (h >> 1)) + 1e-6f);
    }
#pragma unroll
    for (int b = 0; b < 10; b++) {
        const int hl = (8 * b) / 20, hh = (8 * b + 6) / 20;
        const bool up = hl != hh && q >= 2;
        const float s0 = up ? r0[hh] : r0[hl], s1 = up ? r1[hh] : r1[hl];
        *reinterpret_cast<uint32_t*>(dst + 8 * b) = pack_bf16(d[4 * b] * s0, d[4 * b + 1] * s0);
        *reinterpret_cast<uint32_t*>(dst + 8 * 640 + 8 * b) = pack_bf16(d[4 * b + 2] * s1, d[4 * b + 3] * s1);
    }
}

__global__ void __launch_bounds__(NTHR, 1) fused_kernel(const __grid_constant__ Params P) {
    extern __shared__ __align__(1024) uint8_t smem[];
    const uint32_t sb = (uint32_t)__cvta_generic_to_shared(smem);
    const int tid = threadIdx.x, lane = tid & 31;
    const int wg = __shfl_sync(~0u, tid >> 7, 0), warp = __shfl_sync(~0u, (tid >> 5) & 3, 0);
    const int cta = blockIdx.x, i = cta >> 3, j = cta & 7;
    const int q = lane & 3, r0 = 16 * warp + (lane >> 2);
    if (wg == 4 || wg == 0) TS(wg == 4 ? 0 : 16);

    if (tid == 640) {
#pragma unroll
        for (int s = 0; s < 3; s++) {
            mbar_init(sb + BAR_FULL_G + s * 8, 2);
            mbar_init(sb + BAR_EMPTY_G + s * 8, 4);
            mbar_init(sb + BAR_FULL_KV + s * 8, 1);
            mbar_init(sb + BAR_EMPTY_KV + s * 8, 16);
        }
        mbar_init(sb + BAR_KVIN, 1);
        sts32(sb + OFF_PUB, 0);
        sts128(sb + OFF_STAT + 16, 0x357F357Fu, 0u, 0u, 0u);
        mbar_init(sb + BAR_DEP, 1);
        mbar_init(sb + BAR_DEP + 8, 1);
        asm volatile("fence.mbarrier_init.release.cluster;" ::: "memory");
        fence_async_smem();
        mbar_expect(sb + BAR_KVIN, 51200 + 20480);
        bulk1d(sb + OFF_WRAW, P.wk, 25600, sb + BAR_KVIN);
        bulk1d(sb + OFF_WRAW + 25600, P.wv, 25600, sb + BAR_KVIN);
    }
    const uint32_t tag = *(volatile uint32_t*)&g_epoch + 1;
    __syncthreads();

    if (wg == 5) {
        asm volatile("setmaxnreg.dec.sync.aligned.u32 32;");
        if (warp == 0) {
            if (elect_one()) {
#pragma unroll 1
                for (int c = 0; c < 10; c++) tma2d(sb + OFF_X16 + c * 2048, &P.xa16, 64 * c, 16 * cta, sb + BAR_KVIN);
                Ring r{0, 1};
#pragma unroll 1
                for (int pass = 0; pass < NPASS; pass++) {
                    const CUtensorMap* m = pass == 0 ? &P.xa : pass <= 3 ? &P.xb : pass == 4 ? &P.ob : &P.oa;
                    if (pass >= 4) { mbar_wait(sb + BAR_DEP + (pass - 4) * 8, 0); fence_async(); }
#pragma unroll 1
                    for (int c = 0; c < 10; c++) {
                        if (pass > 0 || c >= 3) mbar_wait(sb + BAR_EMPTY_G + r.slot * 8, r.phase);
                        mbar_expect(sb + BAR_FULL_G + r.slot * 8, 16384);
                        tma2d(sb + OFF_STAGE + r.slot * STAGE_BYTES, m, 64 * c, 128 * i, sb + BAR_FULL_G + r.slot * 8);
                        next_stage(r);
                    }
                }
            }
        } else if (warp == 2) {
            if (elect_one()) {
                Ring r{0, 1};
#pragma unroll 1
                for (int pass = 0; pass < NPASS; pass++) {
                    const CUtensorMap* m = pass == 0 ? &P.wq : pass <= 3 ? &P.wqkv : pass == 4 ? &P.wob : &P.woa;
                    const int col = 80 * j + (pass == 1 ? 640 : pass == 2 ? 1280 : 0);
#pragma unroll 1
                    for (int c = 0; c < 10; c++) {
                        if (pass > 0 || c >= 3) mbar_wait(sb + BAR_EMPTY_G + r.slot * 8, r.phase);
                        const uint32_t st = sb + OFF_STAGE + r.slot * STAGE_BYTES + 16384, bar = sb + BAR_FULL_G + r.slot * 8;
                        mbar_expect(bar, 16384);
                        tma2d(st, m, col, 64 * c, bar);
                        tma2d(st + 8192, m, col + 64, 64 * c, bar);
                        next_stage(r);
                    }
                }
            }
        } else if (warp == 3 && NPASS == 6) {
            poll_flag(g_flag_b2 + i * 8 + (lane & 7), lane < 8, tag);
            if (lane == 0) { fence_async(); mbar_arrive(sb + BAR_DEP); }
            poll_flag(g_flag_a + i * 32 + lane, true, tag);
            if (lane == 0) { fence_async(); mbar_arrive(sb + BAR_DEP + 8); }
        } else if (warp == 1) {
            uint32_t sk, sv, spin = 0;
#pragma unroll 1
            while (true) {
                unsigned long long f[4];
#pragma unroll
                for (int u = 0; u < 4; u++) f[u] = ld_relaxed64(g_flag_kv + lane + 32 * u);
                bool ok = true;
                sk = 0; sv = 0;
#pragma unroll
                for (int u = 0; u < 4; u++) {
                    ok = ok && (uint32_t)(f[u] >> 32) == tag;
                    sk = max(sk, ((uint32_t)f[u] >> 16));
                    sv = max(sv, (uint32_t)f[u] & 0xFFFFu);
                }
                if (__all_sync(~0u, ok) || ++spin > (1u << 17)) break;
            }
            fence_acq();
            sk = __reduce_max_sync(~0u, sk);
            sv = __reduce_max_sync(~0u, sv);
            if (elect_one()) {
                const bool vok = sv == 0 || (sv >= ((127 - 40) << 7) && sv <= ((127 + 40) << 7));
                sts32(sb + OFF_STAT, vok ? sk << 16 : 0x7FC00000u);
                fence_async();
#pragma unroll 1
                for (int n = 0; n < 3; n++) {
                    mbar_expect(sb + BAR_FULL_KV + n * 8, RING_BYTES);
                    bulk1d(sb + OFF_RING + n * RING_BYTES, g_kv + n * RING_BYTES, RING_BYTES, sb + BAR_FULL_KV + n * 8);
                }
                Ring r{0, 0};
#pragma unroll 1
                for (int n = 0; n < 16; n++) {
                    if (n >= 3) {
                        mbar_wait(sb + BAR_EMPTY_KV + r.slot * 8, r.phase ^ 1);
                        mbar_expect(sb + BAR_FULL_KV + r.slot * 8, RING_BYTES);
                        bulk1d(sb + OFF_RING + r.slot * RING_BYTES, g_kv + (n & 7) * RING_BYTES, RING_BYTES, sb + BAR_FULL_KV + r.slot * 8);
                    }
                    mbar_wait(sb + BAR_FULL_KV + r.slot * 8, r.phase);
                    asm volatile("st.release.cta.shared::cta.u32 [%0], %1;" :: "r"(sb + OFF_PUB), "r"(n + 1) : "memory");
                    next_stage(r);
                }
            }
        }
    } else if (wg < 4) {
        if (wg == 0) TS(12);
        mbar_wait(sb + BAR_KVIN, 0);
        if (wg == 0) TS(13);
#pragma unroll 1
        for (int u = tid; u < 6400; u += 512) {
            const int mat = u >= 3200, rem = u - mat * 3200, k = rem / 5, m0 = mat * 20 + 4 * (rem - 5 * k);
            const uint2 v = lds64(sb + OFF_WRAW + u * 8);
            sts64(sb + OFF_WKV + (k >> 3) * 640 + (m0 >> 3) * 128 + (k & 7) * 16 + (m0 & 7) * 2, v.x, v.y);
        }
        fence_async_smem();
        bar_sync(1, 512);
        if (wg == 0) {
            TS(14);
            float d[8];
            const uint32_t la = ((sb + OFF_WKV) >> 4) + dlo(640), lb = ((sb + OFF_X16) >> 4) + dlo(16);
            WG_FENCE();
            wg_ss_n16_ta1_tb0_init<8, SW128 | 64>(d, la, lb);
#pragma unroll
            for (int k = 1; k < 40; k++) wg_ss_n16_ta1_tb0<8, SW128 | 64>(d, la + 80 * k, lb + (k >> 2) * 128 + (k & 3) * 2);
            WG_COMMIT();
            if (tid < 16) {
                const int g = tid >> 3;
                const bool mu = (MUFU_MASK >> ((2 * cta + g) & 7)) & 1;
                const uint32_t a = sb + OFF_IMG + g * 768 + (tid & 7) * 16 + 8;
                sts64(a + 256, mu ? 0u : 0x3F00433Fu, mu ? 0u : 0x00003B4Au);
                sts64(a + 640, 0x00003F80u, 0u);
            }
            WG_WAIT(0);
            fence_regs(d);
            bar_arrive(2, 256);
            TS(15);
#pragma unroll
            for (int hh = 0; hh < 2; hh++) {
                const int m = r0 + 8 * hh;
                if (m < 40) {
                    const int isv = m >= 20, dd = m - 20 * isv;
#pragma unroll
                    for (int g = 0; g < 2; g++) {
                        const bool mu = (MUFU_MASK >> ((2 * cta + g) & 7)) & 1;
                        const float sc = (isv || mu) ? 1.f : 0.5f;
                        const uint32_t pr = pack_bf16(d[4 * g + 2 * hh] * sc, d[4 * g + 2 * hh + 1] * sc);
                        const uint32_t a = sb + OFF_IMG + g * 768 + (3 * isv + (dd >> 3)) * 128 + (dd & 7) * 2 + 2 * q * 16;
                        sts16(a, (uint16_t)pr);
                        sts16(a + 16, (uint16_t)(pr >> 16));
                    }
                }
            }
            bar_sync(3, 128);
            if (warp == 0) {
#pragma unroll
                for (int u = 0; u < 3; u++) {
                    const uint4 v = lds128(sb + OFF_IMG + (lane + 32 * u) * 16);
                    *reinterpret_cast<uint4*>(g_kv + cta * 1536 + (lane + 32 * u) * 16) = v;
                }
                const int key = lane & 15, g = key >> 3;
                const uint32_t a = sb + OFF_IMG + g * 768 + (lane >> 4) * 384 + (key & 7) * 16;
                const uint4 w0 = lds128(a), w1 = lds128(a + 128);
                const uint2 w2 = lds64(a + 256);
                const uint32_t w[10] = {w0.x, w0.y, w0.z, w0.w, w1.x, w1.y, w1.z, w1.w, w2.x, w2.y};
                float n2 = 0.f;
                uint32_t mx = 0;
#pragma unroll
                for (int e = 0; e < 10; e++) {
                    n2 = fmaf(bf_lo(w[e]), bf_lo(w[e]), n2);
                    n2 = fmaf(bf_hi(w[e]), bf_hi(w[e]), n2);
                    mx = max(mx, max(w[e] & 0x7FFFu, (w[e] >> 16) & 0x7FFFu));
                }
                if (!((MUFU_MASK >> ((2 * cta + g) & 7)) & 1)) n2 *= 4.f;
                uint32_t st = lane < 16 ? min(((__float_as_uint(n2) & 0x7FFFFFFFu) + 0xFFFFu) >> 16, 0x7FFFu) : mx;
#pragma unroll
                for (int x = 1; x < 16; x <<= 1) st = max(st, __shfl_xor_sync(~0u, st, x));
                const uint32_t sv = __shfl_sync(~0u, st, 16);
                __syncwarp();
                if (lane == 0) {
                    const unsigned long long f = ((unsigned long long)tag << 32) | (st << 16) | sv;
                    asm volatile("st.release.gpu.global.u64 [%0], %1;" :: "l"(g_flag_kv + cta), "l"(f) : "memory");
                }
            }
            TS(17);
        }
        bar_sync(4, 640);
        uint32_t slot = 0;
        const uint4 cz = lds128(sb + OFF_STAT + 16);
#pragma unroll 1
        for (int pass = 0; pass < 2; pass++) {
            uint32_t qf[6];
            const uint32_t qa = sb + (pass ? OFF_Q2 : OFF_Q1) + r0 * QPITCH + wg * 40 + q * 4;
            qf[0] = lds32(qa); qf[1] = lds32(qa + 8 * QPITCH);
            qf[2] = lds32(qa + 16); qf[3] = lds32(qa + 8 * QPITCH + 16);
            qf[4] = q < 2 ? lds32(qa + 32) : 0u; qf[5] = q < 2 ? lds32(qa + 8 * QPITCH + 32) : 0u;
            if (pass == 0) { if (NPASS > 1) bar_arrive(5, 640); count_wait(sb + OFF_PUB, 0, 1); if (wg == 0) { TS(19); TC(26); } }
            float n0 = 0.f, n1 = 0.f;
#pragma unroll
            for (int e = 0; e < 3; e++) {
                n0 = fmaf(bf_lo(qf[2 * e]), bf_lo(qf[2 * e]), fmaf(bf_hi(qf[2 * e]), bf_hi(qf[2 * e]), n0));
                n1 = fmaf(bf_lo(qf[2 * e + 1]), bf_lo(qf[2 * e + 1]), fmaf(bf_hi(qf[2 * e + 1]), bf_hi(qf[2 * e + 1]), n1));
            }
            n0 += __shfl_xor_sync(~0u, n0, 1); n0 += __shfl_xor_sync(~0u, n0, 2);
            n1 += __shfl_xor_sync(~0u, n1, 1); n1 += __shfl_xor_sync(~0u, n1, 2);
            const float k2 = __uint_as_float(lds32(sb + OFF_STAT));
            const uint32_t bad = !(n0 * k2 <= 4000.f && n1 * k2 <= 4000.f);
            uint32_t anybad;
            asm volatile("{\n.reg .pred p, r;\nsetp.ne.u32 p, %1, 0;\nbar.red.or.pred r, %2, 128, p;\nselp.u32 %0, 1, 0, r;\n}" : "=r"(anybad) : "r"(bad), "r"(8 + wg) : "memory");
            float o[12];
#pragma unroll
            for (int k = 0; k < 12; k++) o[k] = 0.f;
            fence_regs(o);
            if (!__shfl_sync(~0u, anybad, 0)) {
                if (q >= 2) qf[4] = qf[5] = q == 2 ? 0x3F803F80u : 0x00003F80u;
                attend<true>(sb, slot, pass, qf, o, cz.x, cz.y, cz.z);
            } else {
                attend<false>(sb, slot, pass, qf, o, cz.x, cz.y, cz.z);
            }
            const float i0 = rcpf(__shfl_sync(~0u, o[8], (lane & ~3) | 2)), i1 = rcpf(__shfl_sync(~0u, o[10], (lane & ~3) | 2));
            __nv_bfloat16* dst = g_oa + (128 * i + 64 * pass + r0) * 640 + 20 * (4 * j + wg) + 2 * q;
#pragma unroll
            for (int b = 0; b < 3; b++) {
                if (b < 2 || q < 2) {
                    *reinterpret_cast<uint32_t*>(dst + 8 * b) = pack_bf16(o[4 * b] * i0, o[4 * b + 1] * i0);
                    *reinterpret_cast<uint32_t*>(dst + 8 * 640 + 8 * b) = pack_bf16(o[4 * b + 2] * i1, o[4 * b + 3] * i1);
                }
            }
            if (wg == 0) { TS(20 + pass); TC(27 + pass); }
        }
        bar_sync(8 + wg, 128);
        if ((tid & 127) == 0) st_release(g_flag_a + cta * 4 + wg, tag);
        TS(22 + wg);
    } else {
        asm volatile("setmaxnreg.inc.sync.aligned.u32 128;");
        const uint32_t ep = (lane >> 2) * 16 + q * 4;
        Ring gr{0, 0};
#pragma unroll 1
        for (int pass = 0; pass < NPASS; pass++) {
        if (pass == 4) {
#pragma unroll 1
        for (int u = tid - 512; u < 880; u += 128) sts128(sb + OFF_KVB + u * 16, 0u, 0u, 0u, 0u);
        if (warp == 0) poll_flag(g_flag_b1 + (lane & 15) * 8 + j, lane < 16, tag);
        bar_sync(6, 128);
        TS(7);
#pragma unroll 1
        for (int f = tid - 512; f < 480; f += 128) {
            float4 s = make_float4(0.f, 0.f, 0.f, 0.f);
#pragma unroll 1
            for (int x0 = 0; x0 < 16; x0 += 8) {
                float4 v[8];
#pragma unroll
                for (int x = 0; x < 8; x++) v[x] = __ldcg(reinterpret_cast<const float4*>(g_part + ((x0 + x) * 8 + j) * 1920) + f);
#pragma unroll
                for (int x = 0; x < 8; x++) { s.x += v[x].x; s.y += v[x].y; s.z += v[x].z; s.w += v[x].w; }
            }
            const int m = f / 6, e0 = (f - 6 * m) * 4, h = m / 20;
            const uint32_t x0 = sb + OFF_KVB + (m >> 3) * 1408 + (m & 7) * 16;
            if (e0 < 20) {
                const int n = 20 * h + e0;
                sts64(x0 + (n >> 3) * 128 + (n & 7) * 2, pack_bf16(s.x, s.y), pack_bf16(s.z, s.w));
            } else {
                sts16(x0 + 1280 + h * 2, (uint16_t)pack_bf16(s.x, 0.f));
            }
        }
        fence_async_smem();
        bar_sync(6, 128);
        {
            __nv_bfloat16* dst = g_ob + (128 * i + r0) * 640 + 80 * j + 2 * q;
#pragma unroll 1
            for (int half = 0; half < 2; half++) linear_out(sb, half, dst + half * 64 * 640, q);
        }
        bar_sync(6, 128);
        if (tid == 512) st_release(g_flag_b2 + cta, tag);
        TS(8);
        }
        float a[40], b[40];
        gemm_pass(sb, gr, a, b);
        if (pass == 0) {
        TS(1);
        bar_sync(2, 256);
#pragma unroll
        for (int k = 0; k < 10; k++) {
            const uint32_t x = sb + r0 * QPITCH + k * 16 + q * 4;
            sts32(x + OFF_Q1, pack_bf16(a[4 * k] * QSCALE, a[4 * k + 1] * QSCALE));
            sts32(x + OFF_Q1 + 8 * QPITCH, pack_bf16(a[4 * k + 2] * QSCALE, a[4 * k + 3] * QSCALE));
            sts32(x + OFF_Q2, pack_bf16(b[4 * k] * QSCALE, b[4 * k + 1] * QSCALE));
            sts32(x + OFF_Q2 + 8 * QPITCH, pack_bf16(b[4 * k + 2] * QSCALE, b[4 * k + 3] * QSCALE));
        }
        bar_arrive(4, 640);
        TS(2);
        } else if (pass == 1 || pass == 3) {
        TS(pass == 1 ? 3 : 6);
        if (pass == 1) bar_sync(5, 640);
#pragma unroll
        for (int k = 0; k < 10; k++) {
            const uint32_t x = sb + OFF_PK + 2 * warp * 1280 + k * 128 + ep;
            sts32(x, pack_bf16(phi(a[4 * k]), phi(a[4 * k + 1])));
            sts32(x + 1280, pack_bf16(phi(a[4 * k + 2]), phi(a[4 * k + 3])));
            sts32(x + 8 * 1280, pack_bf16(phi(b[4 * k]), phi(b[4 * k + 1])));
            sts32(x + 9 * 1280, pack_bf16(phi(b[4 * k + 2]), phi(b[4 * k + 3])));
        }
        if (pass == 1) {
            const int t = tid - 512;
            const uint32_t x = sb + OFF_V + (t >> 3) * 1536 + (t & 7) * 16;
            sts128(x, 0x3F80u, 0u, 0u, 0u);
            sts128(x + 11 * 128, 0x3F80u, 0u, 0u, 0u);
        }
        } else if (pass == 2) {
        TS(4);
#pragma unroll
        for (int k = 0; k < 10; k++) {
            const uint32_t x = sb + OFF_V + 2 * warp * 1536 + (k + 1) * 128 + ep;
            sts32(x, pack_bf16(a[4 * k], a[4 * k + 1]));
            sts32(x + 1536, pack_bf16(a[4 * k + 2], a[4 * k + 3]));
            sts32(x + 8 * 1536, pack_bf16(b[4 * k], b[4 * k + 1]));
            sts32(x + 9 * 1536, pack_bf16(b[4 * k + 2], b[4 * k + 3]));
        }
        fence_async_smem();
        bar_sync(6, 128);
        {
            float d1[36], d2[16]; zero_regs(d1); zero_regs(d2);
            const uint32_t la = ((sb + OFF_PK) >> 4) + dlo(1280), lb = ((sb + OFF_V) >> 4) + dlo(1536);
            WG_FENCE();
            wg_ss_n72_ta1_tb1<8, 8>(d1, la, lb);
            wg_ss_n32_ta1_tb1<8, 8>(d2, la + 16, lb + 64);
#pragma unroll
            for (int k = 1; k < 8; k++) {
                wg_ss_n72_ta1_tb1<8, 8>(d1, la + 160 * k, lb + 192 * k);
                wg_ss_n32_ta1_tb1<8, 8>(d2, la + 16 + 160 * k, lb + 64 + 192 * k);
            }
            WG_COMMIT();
            WG_WAIT(0);
            fence_regs(d1); fence_regs(d2);
            float* part = g_part + cta * 1920;
#pragma unroll
            for (int hh = 0; hh < 2; hh++) {
                const int m = r0 + 8 * hh;
                if (m < 60) {
                    const int h20 = (m / 20) * 20;
                    if (q == 0) part[m * 24 + 20] = d1[2 * hh];
#pragma unroll
                    for (int k = 1; k < 9; k++) {
                        const int e = 8 * (k - 1) + 2 * q - h20;
                        if (e >= 0 && e < 20) *reinterpret_cast<float2*>(part + m * 24 + e) = make_float2(d1[4 * k + 2 * hh], d1[4 * k + 2 * hh + 1]);
                    }
                }
                if (m >= 44) {
                    if (q == 0) part[(m + 16) * 24 + 20] = d2[12 + 2 * hh];
#pragma unroll
                    for (int k = 0; k < 3; k++) {
                        const int e = 8 * k + 2 * q - 4;
                        if (e >= 0) *reinterpret_cast<float2*>(part + (m + 16) * 24 + e) = make_float2(d2[4 * k + 2 * hh], d2[4 * k + 2 * hh + 1]);
                    }
                }
            }
            bar_sync(6, 128);
            if (tid == 512) st_release(g_flag_b1 + cta, tag);
        }
        TS(5);
        } else {
        __nv_bfloat16* out = P.out + (128 * i + r0) * 1280 + 80 * j + 2 * q + (pass == 4 ? 640 : 0);
        store_tile(out, 1280, a);
        store_tile(out + 64 * 1280, 1280, b);
        TS(pass == 4 ? 9 : 11);
        }
        }
        if (cta == 0 && tid == 512) *(volatile uint32_t*)&g_epoch = tag;
    }
}

typedef CUresult (*EncodeFn)(CUtensorMap*, CUtensorMapDataType, cuuint32_t, void*, const cuuint64_t*, const cuuint64_t*,
                             const cuuint32_t*, const cuuint32_t*, CUtensorMapInterleave, CUtensorMapSwizzle,
                             CUtensorMapL2promotion, CUtensorMapFloatOOBfill);

void make_map(EncodeFn enc, CUtensorMap* m, const void* p, uint64_t cols, uint64_t rows, uint32_t box_rows) {
    cuuint64_t dims[2] = {cols, rows}, strides[1] = {cols * 2};
    cuuint32_t box[2] = {64, box_rows}, es[2] = {1, 1};
    enc(m, CU_TENSOR_MAP_DATA_TYPE_BFLOAT16, 2, const_cast<void*>(p), dims, strides, box, es, CU_TENSOR_MAP_INTERLEAVE_NONE,
        CU_TENSOR_MAP_SWIZZLE_128B, CU_TENSOR_MAP_L2_PROMOTION_L2_128B, CU_TENSOR_MAP_FLOAT_OOB_FILL_NONE);
}

}

extern "C" void kernel_launch(void* const* d_in, const int* in_sizes, int n_in, void* d_out, int out_size) {
    static EncodeFn enc = nullptr;
    static void *oa = nullptr, *ob = nullptr;
    if (!enc) {
        void* fn = nullptr;
        cudaDriverEntryPointQueryResult qr;
        cudaGetDriverEntryPoint("cuTensorMapEncodeTiled", &fn, cudaEnableDefault, &qr);
        enc = (EncodeFn)fn;
        cudaGetSymbolAddress(&oa, g_oa);
        cudaGetSymbolAddress(&ob, g_ob);
        cudaFuncSetAttribute(fused_kernel, cudaFuncAttributeMaxDynamicSharedMemorySize, SMEM_BYTES);
    }
    Params P;
    make_map(enc, &P.xa, d_in[0], 640, 2048, 128);
    make_map(enc, &P.xa16, d_in[0], 640, 2048, 16);
    make_map(enc, &P.wq, d_in[1], 640, 640, 64);
    make_map(enc, &P.xb, d_in[5], 640, 2048, 128);
    make_map(enc, &P.wqkv, d_in[6], 1920, 640, 64);
    make_map(enc, &P.woa, d_in[4], 640, 640, 64);
    make_map(enc, &P.wob, d_in[7], 640, 640, 64);
    make_map(enc, &P.oa, oa, 640, 2048, 128);
    make_map(enc, &P.ob, ob, 640, 2048, 128);
    P.wk = (const __nv_bfloat16*)d_in[2];
    P.wv = (const __nv_bfloat16*)d_in[3];
    P.out = (__nv_bfloat16*)d_out;
    fused_kernel<<<NCTA, NTHR, SMEM_BYTES, cudaStreamPerThread>>>(P);
}
```

```cpp
#include <cuda_runtime.h>
#include <cuda_bf16.h>
#include <cuda.h>
#include <stdint.h>

namespace {

constexpr int NCTA = 128;
constexpr int NTHR = 768;

constexpr uint32_t OFF_STAGE = 0;
constexpr uint32_t STAGE_BYTES = 26624;
constexpr uint32_t OFF_PK = 79872;
constexpr uint32_t OFF_WRAW = OFF_PK;
constexpr uint32_t OFF_V = 100352;
constexpr uint32_t OFF_KVB = OFF_V;
constexpr uint32_t OFF_PST = OFF_V + 14336;
constexpr uint32_t OFF_WA = 0;
constexpr uint32_t OFF_XA = 102400;
constexpr uint32_t OFF_RING = 135168;
constexpr uint32_t RING_BYTES = 24576;
constexpr uint32_t OFF_WKV = OFF_RING;
constexpr uint32_t OFF_Q = 208896;
constexpr uint32_t OFF_X16 = OFF_Q;
constexpr uint32_t OFF_MISC = 229376;
constexpr uint32_t OFF_BAR = OFF_MISC;
constexpr uint32_t BAR_FULL_G = OFF_BAR, BAR_EMPTY_G = OFF_BAR + 24, BAR_FULL_KV = OFF_BAR + 48, BAR_EMPTY_KV = OFF_BAR + 72;
constexpr uint32_t BAR_OA = OFF_BAR + 96, BAR_WA = OFF_BAR + 112, BAR_FULL_X = OFF_BAR + 120, BAR_EMPTY_X = OFF_BAR + 152, BAR_TAIL = OFF_BAR + 184;
constexpr uint32_t BAR_PART = OFF_BAR + 264, BAR_KVB = OFF_BAR + 272, BAR_OB = OFF_BAR + 280, BAR_KVIN = OFF_BAR + 288;
constexpr uint32_t OFF_PUB = OFF_BAR + 296;
constexpr uint32_t OFF_STAT = OFF_BAR + 304;
constexpr uint32_t OFF_IMG = OFF_MISC + 384;
constexpr uint32_t OFF_TS = OFF_IMG + 1536;
constexpr uint32_t SMEM_BYTES = OFF_TS + 256;

#define MUFU_MASK 0x4A

#define PFS 3
#define HOLD 2
#define NPASS 5
constexpr float LOG2E = 1.4426950408889634f;
constexpr float QSCALE = 0.22360679774997896f * LOG2E;

struct Params {
    CUtensorMap xa, xa16, wq, xb, wqkv, woa, wob, oa, ob, oa_st, ob_st;
    const uint8_t* in[8];
    __nv_bfloat16* out;
    int helpers;
};

}

__device__ __align__(1024) uint8_t g_kv[256 * 768];
__device__ __align__(1024) __nv_bfloat16 g_oa[2048 * 640];
__device__ __align__(1024) __nv_bfloat16 g_ob[2048 * 640];
__device__ __align__(128) float g_part[8 * 1920];
__device__ __align__(128) unsigned long long g_flag_kv[128];
__device__ __align__(128) uint16_t g_flag_b1[128];
__device__ __align__(128) uint16_t g_flag_b2[128];
__device__ __align__(128) uint16_t g_flag_a[256];
__device__ __align__(128) uint16_t g_flag_w[32];
__device__ __align__(1024) uint8_t g_wt[320 * 10240];
__device__ uint32_t g_epoch;
#define TS(k)
#define TC(k)

namespace {

__device__ __forceinline__ void wg_rs_n24_tb1_d(float (&d)[12], uint32_t a0, uint32_t a1, uint32_t a2, uint32_t a3, uint64_t db) {
    asm volatile("{\n.reg .pred p;\nsetp.ne.b32 p, 1, 0;\n"
        "wgmma.mma_async.sync.aligned.m64n24k16.f32.bf16.bf16 {%0, %1, %2, %3, %4, %5, %6, %7, %8, %9, %10, %11}, {%12, %13, %14, %15}, %16, p, 1, 1, 1;\n}\n"
        : "+f"(d[0]), "+f"(d[1]), "+f"(d[2]), "+f"(d[3]), "+f"(d[4]), "+f"(d[5]), "+f"(d[6]), "+f"(d[7]), "+f"(d[8]), "+f"(d[9]), "+f"(d[10]), "+f"(d[11])
        : "r"(a0), "r"(a1), "r"(a2), "r"(a3), "l"(db));
}
__device__ __forceinline__ void wg_rs_n64_tb0_d(float (&d)[32], uint32_t a0, uint32_t a1, uint32_t a2, uint32_t a3, uint64_t db) {
    asm volatile("{\n.reg .pred p;\nsetp.ne.b32 p, 1, 0;\n"
        "wgmma.mma_async.sync.aligned.m64n64k16.f32.bf16.bf16 {%0, %1, %2, %3, %4, %5, %6, %7, %8, %9, %10, %11, %12, %13, %14, %15, %16, %17, %18, %19, %20, %21, %22, %23, %24, %25, %26, %27, %28, %29, %30, %31}, {%32, %33, %34, %35}, %36, p, 1, 1, 0;\n}\n"
        : "+f"(d[0]), "+f"(d[1]), "+f"(d[2]), "+f"(d[3]), "+f"(d[4]), "+f"(d[5]), "+f"(d[6]), "+f"(d[7]), "+f"(d[8]), "+f"(d[9]), "+f"(d[10]), "+f"(d[11]), "+f"(d[12]), "+f"(d[13]), "+f"(d[14]), "+f"(d[15]), "+f"(d[16]), "+f"(d[17]), "+f"(d[18]), "+f"(d[19]), "+f"(d[20]), "+f"(d[21]), "+f"(d[22]), "+f"(d[23]), "+f"(d[24]), "+f"(d[25]), "+f"(d[26]), "+f"(d[27]), "+f"(d[28]), "+f"(d[29]), "+f"(d[30]), "+f"(d[31])
        : "r"(a0), "r"(a1), "r"(a2), "r"(a3), "l"(db));
}
__device__ __forceinline__ void wg_rs_n64_tb0_initd(float (&d)[32], uint32_t a0, uint32_t a1, uint32_t a2, uint32_t a3, uint64_t db) {
    asm volatile("{\n.reg .pred p;\nsetp.ne.b32 p, 0, 0;\n"
        "wgmma.mma_async.sync.aligned.m64n64k16.f32.bf16.bf16 {%0, %1, %2, %3, %4, %5, %6, %7, %8, %9, %10, %11, %12, %13, %14, %15, %16, %17, %18, %19, %20, %21, %22, %23, %24, %25, %26, %27, %28, %29, %30, %31}, {%32, %33, %34, %35}, %36, p, 1, 1, 0;\n}\n"
        : "=f"(d[0]), "=f"(d[1]), "=f"(d[2]), "=f"(d[3]), "=f"(d[4]), "=f"(d[5]), "=f"(d[6]), "=f"(d[7]), "=f"(d[8]), "=f"(d[9]), "=f"(d[10]), "=f"(d[11]), "=f"(d[12]), "=f"(d[13]), "=f"(d[14]), "=f"(d[15]), "=f"(d[16]), "=f"(d[17]), "=f"(d[18]), "=f"(d[19]), "=f"(d[20]), "=f"(d[21]), "=f"(d[22]), "=f"(d[23]), "=f"(d[24]), "=f"(d[25]), "=f"(d[26]), "=f"(d[27]), "=f"(d[28]), "=f"(d[29]), "=f"(d[30]), "=f"(d[31])
        : "r"(a0), "r"(a1), "r"(a2), "r"(a3), "l"(db));
}
__device__ __forceinline__ void wg_ss_n16_ta1_tb0_d(float (&d)[8], uint64_t da, uint64_t db) {
    asm volatile("{\n.reg .pred p;\nsetp.ne.b32 p, 1, 0;\n"
        "wgmma.mma_async.sync.aligned.m64n16k16.f32.bf16.bf16 {%0, %1, %2, %3, %4, %5, %6, %7}, %8, %9, p, 1, 1, 1, 0;\n}\n"
        : "+f"(d[0]), "+f"(d[1]), "+f"(d[2]), "+f"(d[3]), "+f"(d[4]), "+f"(d[5]), "+f"(d[6]), "+f"(d[7])
        : "l"(da), "l"(db));
}
__device__ __forceinline__ void wg_ss_n16_ta1_tb0_initd(float (&d)[8], uint64_t da, uint64_t db) {
    asm volatile("{\n.reg .pred p;\nsetp.ne.b32 p, 0, 0;\n"
        "wgmma.mma_async.sync.aligned.m64n16k16.f32.bf16.bf16 {%0, %1, %2, %3, %4, %5, %6, %7}, %8, %9, p, 1, 1, 1, 0;\n}\n"
        : "=f"(d[0]), "=f"(d[1]), "=f"(d[2]), "=f"(d[3]), "=f"(d[4]), "=f"(d[5]), "=f"(d[6]), "=f"(d[7])
        : "l"(da), "l"(db));
}
__device__ __forceinline__ void wg_ss_n32_ta1_tb1_d(float (&d)[16], uint64_t da, uint64_t db) {
    asm volatile("{\n.reg .pred p;\nsetp.ne.b32 p, 1, 0;\n"
        "wgmma.mma_async.sync.aligned.m64n32k16.f32.bf16.bf16 {%0, %1, %2, %3, %4, %5, %6, %7, %8, %9, %10, %11, %12, %13, %14, %15}, %16, %17, p, 1, 1, 1, 1;\n}\n"
        : "+f"(d[0]), "+f"(d[1]), "+f"(d[2]), "+f"(d[3]), "+f"(d[4]), "+f"(d[5]), "+f"(d[6]), "+f"(d[7]), "+f"(d[8]), "+f"(d[9]), "+f"(d[10]), "+f"(d[11]), "+f"(d[12]), "+f"(d[13]), "+f"(d[14]), "+f"(d[15])
        : "l"(da), "l"(db));
}
__device__ __forceinline__ void wg_ss_n72_ta1_tb1_d(float (&d)[36], uint64_t da, uint64_t db) {
    asm volatile("{\n.reg .pred p;\nsetp.ne.b32 p, 1, 0;\n"
        "wgmma.mma_async.sync.aligned.m64n72k16.f32.bf16.bf16 {%0, %1, %2, %3, %4, %5, %6, %7, %8, %9, %10, %11, %12, %13, %14, %15, %16, %17, %18, %19, %20, %21, %22, %23, %24, %25, %26, %27, %28, %29, %30, %31, %32, %33, %34, %35}, %36, %37, p, 1, 1, 1, 1;\n}\n"
        : "+f"(d[0]), "+f"(d[1]), "+f"(d[2]), "+f"(d[3]), "+f"(d[4]), "+f"(d[5]), "+f"(d[6]), "+f"(d[7]), "+f"(d[8]), "+f"(d[9]), "+f"(d[10]), "+f"(d[11]), "+f"(d[12]), "+f"(d[13]), "+f"(d[14]), "+f"(d[15]), "+f"(d[16]), "+f"(d[17]), "+f"(d[18]), "+f"(d[19]), "+f"(d[20]), "+f"(d[21]), "+f"(d[22]), "+f"(d[23]), "+f"(d[24]), "+f"(d[25]), "+f"(d[26]), "+f"(d[27]), "+f"(d[28]), "+f"(d[29]), "+f"(d[30]), "+f"(d[31]), "+f"(d[32]), "+f"(d[33]), "+f"(d[34]), "+f"(d[35])
        : "l"(da), "l"(db));
}
__device__ __forceinline__ void wg_ss_n80_ta0_tb1_d(float (&d)[40], uint64_t da, uint64_t db) {
    asm volatile("{\n.reg .pred p;\nsetp.ne.b32 p, 1, 0;\n"
        "wgmma.mma_async.sync.aligned.m64n80k16.f32.bf16.bf16 {%0, %1, %2, %3, %4, %5, %6, %7, %8, %9, %10, %11, %12, %13, %14, %15, %16, %17, %18, %19, %20, %21, %22, %23, %24, %25, %26, %27, %28, %29, %30, %31, %32, %33, %34, %35, %36, %37, %38, %39}, %40, %41, p, 1, 1, 0, 1;\n}\n"
        : "+f"(d[0]), "+f"(d[1]), "+f"(d[2]), "+f"(d[3]), "+f"(d[4]), "+f"(d[5]), "+f"(d[6]), "+f"(d[7]), "+f"(d[8]), "+f"(d[9]), "+f"(d[10]), "+f"(d[11]), "+f"(d[12]), "+f"(d[13]), "+f"(d[14]), "+f"(d[15]), "+f"(d[16]), "+f"(d[17]), "+f"(d[18]), "+f"(d[19]), "+f"(d[20]), "+f"(d[21]), "+f"(d[22]), "+f"(d[23]), "+f"(d[24]), "+f"(d[25]), "+f"(d[26]), "+f"(d[27]), "+f"(d[28]), "+f"(d[29]), "+f"(d[30]), "+f"(d[31]), "+f"(d[32]), "+f"(d[33]), "+f"(d[34]), "+f"(d[35]), "+f"(d[36]), "+f"(d[37]), "+f"(d[38]), "+f"(d[39])
        : "l"(da), "l"(db));
}
__device__ __forceinline__ void wg_ss_n88_ta0_tb1_d(float (&d)[44], uint64_t da, uint64_t db) {
    asm volatile("{\n.reg .pred p;\nsetp.ne.b32 p, 1, 0;\n"
        "wgmma.mma_async.sync.aligned.m64n88k16.f32.bf16.bf16 {%0, %1, %2, %3, %4, %5, %6, %7, %8, %9, %10, %11, %12, %13, %14, %15, %16, %17, %18, %19, %20, %21, %22, %23, %24, %25, %26, %27, %28, %29, %30, %31, %32, %33, %34, %35, %36, %37, %38, %39, %40, %41, %42, %43}, %44, %45, p, 1, 1, 0, 1;\n}\n"
        : "+f"(d[0]), "+f"(d[1]), "+f"(d[2]), "+f"(d[3]), "+f"(d[4]), "+f"(d[5]), "+f"(d[6]), "+f"(d[7]), "+f"(d[8]), "+f"(d[9]), "+f"(d[10]), "+f"(d[11]), "+f"(d[12]), "+f"(d[13]), "+f"(d[14]), "+f"(d[15]), "+f"(d[16]), "+f"(d[17]), "+f"(d[18]), "+f"(d[19]), "+f"(d[20]), "+f"(d[21]), "+f"(d[22]), "+f"(d[23]), "+f"(d[24]), "+f"(d[25]), "+f"(d[26]), "+f"(d[27]), "+f"(d[28]), "+f"(d[29]), "+f"(d[30]), "+f"(d[31]), "+f"(d[32]), "+f"(d[33]), "+f"(d[34]), "+f"(d[35]), "+f"(d[36]), "+f"(d[37]), "+f"(d[38]), "+f"(d[39]), "+f"(d[40]), "+f"(d[41]), "+f"(d[42]), "+f"(d[43])
        : "l"(da), "l"(db));
}

#define WG_FENCE() asm volatile("wgmma.fence.sync.aligned;" ::: "memory")
#define WG_COMMIT() asm volatile("wgmma.commit_group.sync.aligned;" ::: "memory")
#define WG_WAIT(n) asm volatile("wgmma.wait_group.sync.aligned %0;" :: "n"(n) : "memory")
template <int NR> __device__ __forceinline__ void fence_regs(float (&d)[NR]) {
#pragma unroll
    for (int i = 0; i < NR; i++) asm volatile("" : "+f"(d[i]) :: "memory");
}
template <int NR> __device__ __forceinline__ void zero_regs(float (&d)[NR]) {
#pragma unroll
    for (int i = 0; i < NR; i++) asm volatile("mov.b32 %0, 0;" : "=f"(d[i]) :: "memory");
}
constexpr uint32_t SW128 = 1u << 30, SW32 = 3u << 30;
__device__ __forceinline__ constexpr uint32_t dlo(uint32_t lbo) { return (lbo >> 4) << 16; }

__device__ __forceinline__ void bar_sync(int id, int n) { asm volatile("bar.sync %0, %1;" :: "r"(id), "r"(n) : "memory"); }
__device__ __forceinline__ void bar_arrive(int id, int n) { asm volatile("bar.arrive %0, %1;" :: "r"(id), "r"(n) : "memory"); }
__device__ __forceinline__ void mbar_init(uint32_t bar, uint32_t cnt) { asm volatile("mbarrier.init.shared::cta.b64 [%0], %1;" :: "r"(bar), "r"(cnt) : "memory"); }
__device__ __forceinline__ void mbar_arrive(uint32_t bar) { asm volatile("mbarrier.arrive.shared::cta.b64 _, [%0];" :: "r"(bar) : "memory"); }
__device__ __forceinline__ void mbar_expect(uint32_t bar, uint32_t bytes) { asm volatile("mbarrier.arrive.expect_tx.shared::cta.b64 _, [%0], %1;" :: "r"(bar), "r"(bytes) : "memory"); }
__device__ __forceinline__ void mbar_wait(uint32_t bar, uint32_t parity) {
    asm volatile("{\n.reg .pred p;\n.reg .u32 n;\nmov.u32 n, 0;\n"
                 "MW_LOOP:\nmbarrier.try_wait.parity.shared::cta.b64 p, [%0], %1;\n@p bra.uni MW_DONE;\n"
                 "add.u32 n, n, 1;\nsetp.lt.u32 p, n, 32768;\n@p bra.uni MW_LOOP;\nMW_DONE:\n}"
                 :: "r"(bar), "r"(parity) : "memory");
}
__device__ __forceinline__ void count_wait(uint32_t addr, uint32_t seen, uint32_t need) {
    asm volatile("{\n.reg .pred p;\n.reg .u32 n, v;\nmov.u32 n, 0;\nmov.u32 v, %1;\n"
                 "CW_LOOP:\nsetp.ge.u32 p, v, %2;\n@p bra.uni CW_DONE;\nld.volatile.shared.u32 v, [%0];\n"
                 "add.u32 n, n, 1;\nsetp.lt.u32 p, n, 0x400000;\n@p bra.uni CW_LOOP;\nCW_DONE:\n}"
                 :: "r"(addr), "r"(seen), "r"(need) : "memory");
}
__device__ __forceinline__ void tma2d(uint32_t dst, const CUtensorMap* m, int x, int y, uint32_t bar) {
    asm volatile("cp.async.bulk.tensor.2d.shared::cluster.global.mbarrier::complete_tx::bytes [%0], [%1, {%2, %3}], [%4];"
                 :: "r"(dst), "l"(m), "r"(x), "r"(y), "r"(bar) : "memory");
}
__device__ __forceinline__ void bulk1d(uint32_t dst, const void* src, uint32_t bytes, uint32_t bar) {
    asm volatile("cp.async.bulk.shared::cluster.global.mbarrier::complete_tx::bytes [%0], [%1], %2, [%3];"
                 :: "r"(dst), "l"(src), "r"(bytes), "r"(bar) : "memory");
}
__device__ __forceinline__ void tma3d(uint32_t dst, const CUtensorMap* m, int y, int z, uint32_t bar) {
    asm volatile("cp.async.bulk.tensor.3d.shared::cluster.global.mbarrier::complete_tx::bytes [%0], [%1, {0, %2, %3}], [%4];"
                 :: "r"(dst), "l"(m), "r"(y), "r"(z), "r"(bar) : "memory");
}
__device__ __forceinline__ void tma2d_store(const CUtensorMap* m, int x, int y, uint32_t src) {
    asm volatile("cp.async.bulk.tensor.2d.global.shared::cta.bulk_group [%0, {%1, %2}], [%3];" :: "l"(m), "r"(x), "r"(y), "r"(src) : "memory");
}
__device__ __forceinline__ void bulk_store(void* dst, uint32_t src, uint32_t bytes) {
    asm volatile("cp.async.bulk.global.shared::cta.bulk_group [%0], [%1], %2;" :: "l"(dst), "r"(src), "r"(bytes) : "memory");
}
__device__ __forceinline__ void bulk_add_f32(void* dst, uint32_t src, uint32_t bytes) {
    asm volatile("cp.reduce.async.bulk.global.shared::cta.bulk_group.add.f32 [%0], [%1], %2;" :: "l"(dst), "r"(src), "r"(bytes) : "memory");
}
__device__ __forceinline__ void bulk_commit() { asm volatile("cp.async.bulk.commit_group;" ::: "memory"); }
__device__ __forceinline__ void bulk_wait() {
    asm volatile("cp.async.bulk.wait_group 0;\nfence.proxy.async.global;" ::: "memory");
}
__device__ __forceinline__ void prefetch_l2(const void* p, uint32_t bytes) { asm volatile("cp.async.bulk.prefetch.L2.global [%0], %1;" :: "l"(p), "r"(bytes) : "memory"); }
__device__ __forceinline__ void prefetch_map(const CUtensorMap* m) { asm volatile("prefetch.tensormap [%0];" :: "l"(m) : "memory"); }
__device__ __forceinline__ bool elect_one() {
    uint32_t p;
    asm volatile("{\n.reg .pred p;\nelect.sync _|p, 0xffffffff;\nselp.u32 %0, 1, 0, p;\n}" : "=r"(p));
    return p;
}
__device__ __forceinline__ void fence_async() { asm volatile("fence.proxy.async.global;" ::: "memory"); }
__device__ __forceinline__ void fence_async_smem() { asm volatile("fence.proxy.async.shared::cta;" ::: "memory"); }
__device__ __forceinline__ void st_flag(uint16_t* p, uint32_t v) { asm volatile("st.release.gpu.global.u16 [%0], %1;" :: "l"(p), "h"((uint16_t)v) : "memory"); }
__device__ __forceinline__ uint4 ld_relaxed128(const void* p) { uint4 v; asm volatile("ld.relaxed.gpu.global.v4.u32 {%0, %1, %2, %3}, [%4];" : "=r"(v.x), "=r"(v.y), "=r"(v.z), "=r"(v.w) : "l"(p) : "memory"); return v; }
__device__ __forceinline__ uint4 ld_acquire128(const void* p) { uint4 v; asm volatile("ld.acquire.gpu.global.v4.u32 {%0, %1, %2, %3}, [%4];" : "=r"(v.x), "=r"(v.y), "=r"(v.z), "=r"(v.w) : "l"(p) : "memory"); return v; }
__device__ __forceinline__ void poll1(const uint16_t* p, uint32_t tag) {
#pragma unroll 1
    for (uint32_t spin = 0; spin < (1u << 17); spin++) {
        uint16_t v;
        asm volatile("ld.acquire.gpu.global.u16 %0, [%1];" : "=h"(v) : "l"(p) : "memory");
        if (v == (uint16_t)tag) break;
    }
    fence_async();
}
__device__ __forceinline__ void poll8(const uint16_t* p, uint32_t tag) {
    const uint32_t t2 = (tag & 0xFFFFu) * 0x10001u;
#pragma unroll 1
    for (uint32_t spin = 0; spin < (1u << 17); spin++) {
        const uint4 a = ld_acquire128(p);
        if (a.x == t2 && a.y == t2 && a.z == t2 && a.w == t2) break;
    }
    fence_async();
}
__device__ __forceinline__ uint32_t lds32(uint32_t a) { uint32_t v; asm volatile("ld.shared.u32 %0, [%1];" : "=r"(v) : "r"(a) : "memory"); return v; }
__device__ __forceinline__ void sts32(uint32_t a, uint32_t v) { asm volatile("st.shared.u32 [%0], %1;" :: "r"(a), "r"(v) : "memory"); }
__device__ __forceinline__ void sts16(uint32_t a, uint16_t v) { asm volatile("st.shared.u16 [%0], %1;" :: "r"(a), "h"(v) : "memory"); }
__device__ __forceinline__ void sts64(uint32_t a, uint32_t x, uint32_t y) { asm volatile("st.shared.v2.u32 [%0], {%1, %2};" :: "r"(a), "r"(x), "r"(y) : "memory"); }
__device__ __forceinline__ void sts128(uint32_t a, uint32_t x, uint32_t y, uint32_t z, uint32_t w) { asm volatile("st.shared.v4.u32 [%0], {%1, %2, %3, %4};" :: "r"(a), "r"(x), "r"(y), "r"(z), "r"(w) : "memory"); }
__device__ __forceinline__ uint2 lds64(uint32_t a) { uint2 v; asm volatile("ld.shared.v2.u32 {%0, %1}, [%2];" : "=r"(v.x), "=r"(v.y) : "r"(a) : "memory"); return v; }
__device__ __forceinline__ uint4 lds128(uint32_t a) { uint4 v; asm volatile("ld.shared.v4.u32 {%0, %1, %2, %3}, [%4];" : "=r"(v.x), "=r"(v.y), "=r"(v.z), "=r"(v.w) : "r"(a) : "memory"); return v; }
__device__ __forceinline__ float ex2f(float x) { float y; asm("ex2.approx.ftz.f32 %0, %1;" : "=f"(y) : "f"(x)); return y; }
__device__ __forceinline__ float rcpf(float x) { float y; asm("rcp.approx.ftz.f32 %0, %1;" : "=f"(y) : "f"(x)); return y; }
__device__ __forceinline__ void stsm4(uint32_t a, uint32_t x, uint32_t y, uint32_t z, uint32_t w) {
    asm volatile("stmatrix.sync.aligned.m8n8.x4.shared.b16 [%0], {%1, %2, %3, %4};" :: "r"(a), "r"(x), "r"(y), "r"(z), "r"(w) : "memory");
}
__device__ __forceinline__ uint32_t pack_bf16(float lo, float hi) { uint32_t r; asm("cvt.rn.bf16x2.f32 %0, %1, %2;" : "=r"(r) : "f"(hi), "f"(lo)); return r; }
__device__ __forceinline__ float bf_lo(uint32_t v) { return __uint_as_float(v << 16); }
__device__ __forceinline__ float bf_hi(uint32_t v) { return __uint_as_float(v & 0xFFFF0000u); }
__device__ __forceinline__ uint32_t phi2(float t0, float t1) {
    uint32_t r;
    asm("{\n.reg .b32 one, eps, p, e;\nmov.b32 one, 0x3F803F80;\nmov.b32 eps, 0x35863586;\n"
        "add.rn.bf16x2 p, %1, one;\nmin.bf16x2 e, %2, one;\nmax.NaN.bf16x2 p, p, e;\nadd.rn.bf16x2 %0, p, eps;\n}"
        : "=r"(r) : "r"(pack_bf16(t0, t1)), "r"(pack_bf16(ex2f(t0 * LOG2E), ex2f(t1 * LOG2E))));
    return r;
}
template <int MODE> __device__ __forceinline__ void stage_tile(uint32_t x, uint32_t step, const float (&a)[40]) {
#pragma unroll
    for (int k = 0; k < 5; k++) {
        uint32_t r[4];
#pragma unroll
        for (int e = 0; e < 4; e++) {
            const float t0 = a[8 * k + 2 * e], t1 = a[8 * k + 2 * e + 1];
            r[e] = MODE == 0 ? pack_bf16(t0, t1) : MODE == 1 ? pack_bf16(t0 * QSCALE, t1 * QSCALE) : phi2(t0, t1);
        }
        stsm4(x + 2 * k * step, r[0], r[1], r[2], r[3]);
    }
}

__device__ __forceinline__ uint32_t exp2_pair(float t0, float t1, uint32_t ca) {
    uint32_t y, u, g;
    asm("prmt.b32 %0, %1, %2, 0x6521;" : "=r"(y) : "r"(__float_as_uint(t0)), "r"(__float_as_uint(t1)));
    u = y & 0x007F007Fu;
    asm("{.reg .b32 c; mov.b32 c, 0xF963F963; fma.rn.f16x2 %0, %1, c, %2;}" : "=r"(g) : "r"(u), "r"(ca));
    asm("mul.rn.f16x2 %0, %1, %2;" : "=r"(g) : "r"(g), "r"(u));
    return y - g;
}

__device__ __forceinline__ uint64_t desc(uint32_t addr, uint32_t lbo, uint32_t hi) { return ((uint64_t)hi << 32) | ((addr >> 4) + dlo(lbo)); }
template <int J> __device__ __forceinline__ void exp_steps(const float (&s)[32], uint32_t (&p)[16], float (&o)[12], uint64_t& dv, uint32_t ca) {
    if constexpr (J < 4) {
#pragma unroll
        for (int g = 2 * J; g < 2 * J + 2; g++) {
            if ((MUFU_MASK >> g) & 1) {
                p[2 * g] = pack_bf16(ex2f(s[4 * g]), ex2f(s[4 * g + 1]));
                p[2 * g + 1] = pack_bf16(ex2f(s[4 * g + 2]), ex2f(s[4 * g + 3]));
            } else {
                p[2 * g] = exp2_pair(s[4 * g], s[4 * g + 1], ca);
                p[2 * g + 1] = exp2_pair(s[4 * g + 2], s[4 * g + 3], ca);
            }
        }
        WG_FENCE();
        wg_rs_n24_tb1_d(o, p[4 * J], p[4 * J + 1], p[4 * J + 2], p[4 * J + 3], dv);
        dv += 96;
        exp_steps<J + 1>(s, p, o, dv, ca);
    }
}

struct Ring { uint32_t slot, phase; };
__device__ __forceinline__ void next_stage(Ring& r) { if (++r.slot == 3) { r.slot = 0; r.phase ^= 1; } }

#define BUNR 4
template <bool FAST>
__device__ __forceinline__ void attend(uint32_t sb, uint32_t& slot, int pass, const uint32_t (&q)[6], float (&o)[12], uint32_t ca, uint32_t z0, uint32_t z1) {
    float m0 = -INFINITY, m1 = -INFINITY;
    constexpr int UNR = FAST ? BUNR : 1;
#pragma unroll 1
    for (int c = 0; c < 8; c++) {
        const uint32_t base = sb + OFF_RING + slot * RING_BYTES;
        uint64_t dk = desc(base, 128, 768 >> 4), dv = desc(base + 384, 768, 128 >> 4);
        uint32_t seen;
#pragma unroll UNR
        for (int b = 0; b < 4; b++) {
            float s[32];
            uint32_t p[16];
            WG_FENCE();
            wg_rs_n64_tb0_initd(s, q[0], q[1], q[2], q[3], dk);
            dk += 16;
            wg_rs_n64_tb0_d(s, q[4], q[5], z0, z1, dk);
            dk += 368;
            WG_COMMIT();
            if (UNR < 4 || b == 3) seen = lds32(sb + OFF_PUB);
            WG_WAIT(0);
            fence_regs(s);
            if constexpr (FAST) {
                exp_steps<0>(s, p, o, dv, ca);
            } else {
                fence_regs(o);
                float x0 = m0, x1 = m1;
#pragma unroll
                for (int g = 0; g < 8; g++) {
                    if (!((MUFU_MASK >> g) & 1)) {
#pragma unroll
                        for (int e = 0; e < 4; e++) s[4 * g + e] *= 2.f;
                    }
                    x0 = fmaxf(x0, fmaxf(s[4 * g], s[4 * g + 1]));
                    x1 = fmaxf(x1, fmaxf(s[4 * g + 2], s[4 * g + 3]));
                }
                x0 = fmaxf(x0, __shfl_xor_sync(~0u, x0, 1)); x0 = fmaxf(x0, __shfl_xor_sync(~0u, x0, 2));
                x1 = fmaxf(x1, __shfl_xor_sync(~0u, x1, 1)); x1 = fmaxf(x1, __shfl_xor_sync(~0u, x1, 2));
                const float a0 = ex2f(m0 - x0), a1 = ex2f(m1 - x1);
                m0 = x0; m1 = x1;
#pragma unroll
                for (int b = 0; b < 3; b++) { o[4 * b] *= a0; o[4 * b + 1] *= a0; o[4 * b + 2] *= a1; o[4 * b + 3] *= a1; }
#pragma unroll
                for (int g = 0; g < 8; g++) {
                    p[2 * g] = pack_bf16(ex2f(s[4 * g] - x0), ex2f(s[4 * g + 1] - x0));
                    p[2 * g + 1] = pack_bf16(ex2f(s[4 * g + 2] - x1), ex2f(s[4 * g + 3] - x1));
                }
            }
            if constexpr (!FAST) {
                WG_FENCE();
#pragma unroll
                for (int k = 0; k < 4; k++) { wg_rs_n24_tb1_d(o, p[4 * k], p[4 * k + 1], p[4 * k + 2], p[4 * k + 3], dv); dv += 96; }
            }
            WG_COMMIT();
            WG_WAIT(0);
            fence_regs(o);
        }
        if ((threadIdx.x & 31) == 0) mbar_arrive(sb + BAR_EMPTY_KV + slot * 8);
        slot = slot == 2 ? 0 : slot + 1;
        count_wait(sb + OFF_PUB, seen, min(pass * 8 + c + 2, 16));
    }
}

__device__ __forceinline__ void gemm_pass(uint32_t sb, int pass, float (&a)[40], float (&b)[40]) {
    zero_regs(a); zero_regs(b);
    const uint32_t n0 = __shfl_sync(~0u, pass, 0) * 10;
    uint32_t slot = n0 % 3, phase = (n0 / 3) & 1;
    const bool lead = (threadIdx.x & 31) == 0;
#pragma unroll 1
    for (int c = 0; c < 10; c++) {
        mbar_wait(sb + BAR_FULL_G + slot * 8, phase);
        const uint32_t st = sb + OFF_STAGE + slot * STAGE_BYTES;
        const uint64_t dx = desc(st, 16, SW128 | 64), dw = desc(st + 16384, 2048, SW32 | 16);
        WG_FENCE();
#pragma unroll
        for (int k = 0; k < 4; k++) {
            wg_ss_n80_ta0_tb1_d(a, dx + 2 * k, dw + 32 * k);
            wg_ss_n80_ta0_tb1_d(b, dx + 512 + 2 * k, dw + 32 * k);
        }
        WG_COMMIT();
        WG_WAIT(0);
        if (lead) mbar_arrive(sb + BAR_EMPTY_G + slot * 8);
        if (++slot == 3) { slot = 0; phase ^= 1; }
    }
    fence_regs(a); fence_regs(b);
}

__device__ __forceinline__ void gemm_half(uint32_t sb, int half_, float (&a)[40]) {
    zero_regs(a);
    const int half = __shfl_sync(~0u, half_, 0);
    const bool lead = (threadIdx.x & 31) == 0 && !half;
#pragma unroll 1
    for (int c = 0; c < 10; c++) {
        const uint32_t box = (half && c < 9) ? OFF_RING + c * 8192 : OFF_XA + (half ? 0 : (c & 3) * 8192);
        mbar_wait(sb + (half ? BAR_TAIL + c * 8 : BAR_FULL_X + (c & 3) * 8), half ? 0 : (c >> 2) & 1);
        const uint64_t dx = desc(sb + box, 16, SW128 | 64), dw = desc(sb + OFF_WA + c * 10240, 2048, SW32 | 16);
        WG_FENCE();
#pragma unroll
        for (int k = 0; k < 4; k++) wg_ss_n80_ta0_tb1_d(a, dx + 2 * k, dw + 32 * k);
        WG_COMMIT();
        WG_WAIT(1);
        if (c > 0 && lead) mbar_arrive(sb + BAR_EMPTY_X + ((c - 1) & 3) * 8);
    }
    WG_WAIT(0);
    fence_regs(a);
}

__device__ __forceinline__ void store_tile(__nv_bfloat16* dst, int pitch, const float (&a)[40]) {
#pragma unroll
    for (int b = 0; b < 10; b++) {
        *reinterpret_cast<uint32_t*>(dst + 8 * b) = pack_bf16(a[4 * b], a[4 * b + 1]);
        *reinterpret_cast<uint32_t*>(dst + 8 * pitch + 8 * b) = pack_bf16(a[4 * b + 2], a[4 * b + 3]);
    }
}

__device__ __forceinline__ void linear_out(uint32_t sb, int half, uint32_t dst, int q) {
    float d[44]; zero_regs(d);
    const uint64_t da = desc(sb + OFF_PK + half * 10240, 128, 80), db = desc(sb + OFF_KVB, 1408, 8);
    WG_FENCE();
#pragma unroll
    for (int k = 0; k < 5; k++) wg_ss_n88_ta0_tb1_d(d, da + 16 * k, db + 176 * k);
    WG_COMMIT();
    WG_WAIT(0);
    fence_regs(d);
    bar_sync(6, 128);
    float r0[4], r1[4];
    const int base = (threadIdx.x & 31) & ~3;
#pragma unroll
    for (int e = 0; e < 4; e++) d[40 + e] = rcpf(d[40 + e] + 1e-6f);
#pragma unroll
    for (int h = 0; h < 4; h++) {
        r0[h] = __shfl_sync(~0u, d[40 + (h & 1)], base + (h >> 1));
        r1[h] = __shfl_sync(~0u, d[42 + (h & 1)], base + (h >> 1));
    }
    uint32_t r[20];
#pragma unroll
    for (int b = 0; b < 10; b++) {
        const int hl = (8 * b) / 20, hh = (8 * b + 6) / 20;
        const bool up = hl != hh && q >= 2;
        const float s0 = up ? r0[hh] : r0[hl], s1 = up ? r1[hh] : r1[hl];
        r[2 * b] = pack_bf16(d[4 * b] * s0, d[4 * b + 1] * s0);
        r[2 * b + 1] = pack_bf16(d[4 * b + 2] * s1, d[4 * b + 3] * s1);
    }
#pragma unroll
    for (int k = 0; k < 5; k++) stsm4(dst + 32 * k, r[4 * k], r[4 * k + 1], r[4 * k + 2], r[4 * k + 3]);
}

__global__ void __launch_bounds__(NTHR, 1) fused_kernel(const __grid_constant__ Params P) {
    extern __shared__ __align__(1024) uint8_t smem[];
    const uint32_t sb = (uint32_t)__cvta_generic_to_shared(smem);
    const int tid = threadIdx.x, lane = tid & 31;
    const int wg = __shfl_sync(~0u, tid >> 7, 0), warp = __shfl_sync(~0u, (tid >> 5) & 3, 0);
    const int cta = blockIdx.x, i = cta >> 3, j = cta & 7;
    const int q = lane & 3, r0 = 16 * warp + (lane >> 2);
    if (wg == 4 || wg == 0) TS(wg == 4 ? 0 : 16);

    const uint32_t tag = *(volatile uint32_t*)&g_epoch + 1;

    if (cta >= NCTA) {
        if (tid < 64 && elect_one()) {
            const int jj = 2 * (cta - NCTA) + warp;
            const uint32_t buf = sb + warp * 102400, bar = sb + OFF_BAR + warp * 80;
#pragma unroll 1
            for (int s = 0; s < 10; s++) mbar_init(bar + s * 8, 1);
            asm volatile("fence.mbarrier_init.release.cluster;" ::: "memory");
            int lp = 0, lc = 0;
#pragma unroll 1
            for (int n = -8; n < 40; n++) {
                if (n >= 0) {
                    const int part = n / 10, c = n - 10 * part;
                    mbar_wait(bar + c * 8, part & 1);
                    bulk_store(g_wt + ((part * 8 + jj) * 10 + c) * 10240, buf + c * 10240, 10240);
                    bulk_commit();
                    if (c == 9) { bulk_wait(); st_flag(g_flag_w + part * 8 + jj, tag); }
                    else asm volatile("cp.async.bulk.wait_group.read 2;" ::: "memory");
                }
                if (lp < 4) {
                    mbar_expect(bar + lc * 8, 10240);
                    tma3d(buf + lc * 10240, lp < 2 ? &P.wqkv : lp == 2 ? &P.wob : &P.woa, 64 * lc, 5 * jj + (lp == 0 ? 80 : 0), bar + lc * 8);
                    if (++lc == 10) { lc = 0; lp++; }
                }
            }
        }
        return;
    }
    if (tid == 640) {
        mbar_init(sb + BAR_KVIN, 1);
        asm volatile("fence.mbarrier_init.release.cluster;" ::: "memory");
        mbar_expect(sb + BAR_KVIN, 51200 + 20480);
        tma3d(sb + OFF_X16, &P.xa16, 16 * cta, 0, sb + BAR_KVIN);
#pragma unroll
        for (int u = 0; u < 4; u++) {
            const int v = (u + cta) & 3;
            bulk1d(sb + OFF_WRAW + v * 12800, P.in[2 + (v >> 1)] + (v & 1) * 12800, 12800, sb + BAR_KVIN);
        }
    } else if (tid == 672) {
#pragma unroll
        for (int s = 0; s < 3; s++) {
            mbar_init(sb + BAR_FULL_G + s * 8, 2);
            mbar_init(sb + BAR_EMPTY_G + s * 8, 4);
            mbar_init(sb + BAR_FULL_KV + s * 8, 1);
            mbar_init(sb + BAR_EMPTY_KV + s * 8, 16);
        }
        mbar_init(sb + BAR_OA, 16);
        mbar_init(sb + BAR_OA + 8, 16);
        asm volatile("fence.mbarrier_init.release.cluster;" ::: "memory");
    } else if (tid == 704) {
        prefetch_map(&P.xa);
        prefetch_map(&P.wq);
        prefetch_l2(P.in[1] + cta * 6400, 6400);
        mbar_init(sb + BAR_WA, 1);
        mbar_init(sb + BAR_PART, 4);
        mbar_init(sb + BAR_KVB, 1);
        mbar_init(sb + BAR_OB, 4);
        sts32(sb + OFF_PUB, 0);
        sts128(sb + OFF_STAT + 16, 0x357F357Fu, 0u, 0u, 0u);
        asm volatile("fence.mbarrier_init.release.cluster;" ::: "memory");
    } else if (tid == 736) {
#pragma unroll
        for (int s = 0; s < 4; s++) { mbar_init(sb + BAR_FULL_X + s * 8, 1); mbar_init(sb + BAR_EMPTY_X + s * 8, 4); }
#pragma unroll
        for (int s = 0; s < 10; s++) mbar_init(sb + BAR_TAIL + s * 8, 1);
        asm volatile("fence.mbarrier_init.release.cluster;" ::: "memory");
    }
    __syncthreads();

    if (wg == 5) {
        asm volatile("setmaxnreg.dec.sync.aligned.u32 32;");
        if (warp == 0) {
            if (elect_one()) {
                Ring r{0, 1};
#pragma unroll 1
                for (int pass = 0; pass < NPASS; pass++) {
                    const CUtensorMap* m = pass == 0 ? &P.xa : pass <= 3 ? &P.xb : &P.ob;
                    if (pass == 1) count_wait(sb + OFF_PUB, 0, HOLD);
                    if (pass == 4) {
                        mbar_wait(sb + BAR_OB, 0);
                        tma2d_store(&P.ob_st, 80 * j, 128 * i, sb + OFF_PK);
                        bulk_commit();
                        bulk_wait();
                        st_flag(g_flag_b2 + cta, tag);
                        poll8(g_flag_b2 + i * 8, tag);
                    }
#pragma unroll 1
                    for (int c = 0; c < 10; c++) {
                        if (pass == 3 && c == 3) {
                            mbar_wait(sb + BAR_PART, 0);
                            bulk_add_f32(g_part + j * 1920, sb + OFF_PST, 7680);
                            bulk_commit();
                        }
                        if (pass > 0 || c >= 3) mbar_wait(sb + BAR_EMPTY_G + r.slot * 8, r.phase);
                        mbar_expect(sb + BAR_FULL_G + r.slot * 8, 16384);
                        tma2d(sb + OFF_STAGE + r.slot * STAGE_BYTES, m, 64 * c, 128 * i, sb + BAR_FULL_G + r.slot * 8);
                        next_stage(r);
                        if (pass == 3 && c == 3) {
                            bulk_wait();
                            st_flag(g_flag_b1 + j * 16 + i, tag);
                        }
                    }
                }
                if (NPASS == 5) {
                    poll8(g_flag_a + i * 8, tag);
#pragma unroll 1
                    for (int c = 0; c < 10; c++) {
                        const uint32_t s = c & 3;
                        if (c >= 4) mbar_wait(sb + BAR_EMPTY_X + s * 8, ((c >> 2) - 1) & 1);
                        mbar_expect(sb + BAR_FULL_X + s * 8, 8192);
                        tma2d(sb + OFF_XA + s * 8192, &P.oa, 64 * c, 128 * i, sb + BAR_FULL_X + s * 8);
                    }
#pragma unroll 1
                    for (int c = 0; c < 10; c++) mbar_expect(sb + BAR_TAIL + c * 8, 8192);
                    mbar_wait(sb + BAR_EMPTY_X, 0);
                    poll8(g_flag_a + 128 + i * 8, tag);
#pragma unroll 1
                    for (int c = 0; c < 10; c++)
                        tma2d(sb + (c < 9 ? OFF_RING + c * 8192 : OFF_XA), &P.oa, 64 * c, 128 * i + 64, sb + BAR_TAIL + c * 8);
                }
            }
        } else if (warp == 2) {
            if (elect_one()) {
                Ring r{0, 1};
#pragma unroll 1
                for (int pass = 0; pass < NPASS; pass++) {
                    const CUtensorMap* m = pass == 0 ? &P.wq : pass <= 3 ? &P.wqkv : &P.wob;
                    const int col = 5 * j + (pass == 1 ? 40 : pass == 2 ? 80 : 0);
                    if (pass == 1) count_wait(sb + OFF_PUB, 0, HOLD);
                    const bool pre = pass >= 2 && P.helpers;
                    if (pre) poll1(g_flag_w + (pass - 2) * 8 + j, tag);
#pragma unroll 1
                    for (int c = 0; c < 10; c++) {
                        if (pass > 0 || c >= 3) mbar_wait(sb + BAR_EMPTY_G + r.slot * 8, r.phase);
                        const uint32_t bar = sb + BAR_FULL_G + r.slot * 8;
                        mbar_expect(bar, 10240);
                        const uint32_t dst = sb + OFF_STAGE + r.slot * STAGE_BYTES + 16384;
                        if (pre) bulk1d(dst, g_wt + (((pass - 2) * 8 + j) * 10 + c) * 10240, 10240, bar);
                        else tma3d(dst, m, 64 * c, col, bar);
                        next_stage(r);
                    }
                }
                if (NPASS == 5) {
                    if (P.helpers) poll1(g_flag_w + 24 + j, tag);
#pragma unroll 1
                    for (int c = 0; c < 3; c++) { mbar_wait(sb + BAR_EMPTY_G + r.slot * 8, r.phase); next_stage(r); }
                    mbar_expect(sb + BAR_WA, 102400);
                    if (P.helpers) bulk1d(sb + OFF_WA, g_wt + (24 + j) * 102400, 102400, sb + BAR_WA);
                    else {
#pragma unroll 1
                        for (int c = 0; c < 10; c++) tma3d(sb + OFF_WA + c * 10240, &P.woa, 64 * c, 5 * j, sb + BAR_WA);
                    }
                }
            }
        } else if (warp == 3) {
            if (elect_one()) {
                mbar_wait(sb + BAR_FULL_G, 0);
                mbar_wait(sb + BAR_FULL_G, 1);
                mbar_wait(sb + BAR_FULL_G, 0);
                prefetch_l2(P.in[5] + cta * 20480, 20480);
#pragma unroll 1
                for (int u = 0; u < 5; u++) prefetch_l2(P.in[6] + (cta * 5 + u) * 3840 + 1280, 1280);
            }
            __syncwarp();
            if (NPASS == 5) {
                if (elect_one()) {
                    poll8(g_flag_b1 + j * 16, tag);
                    poll8(g_flag_b1 + j * 16 + 8, tag);
                    mbar_expect(sb + BAR_KVB, 7680);
                    bulk1d(sb + OFF_PST, g_part + j * 1920, 7680, sb + BAR_KVB);
                }
            }
            if (elect_one()) {
#pragma unroll 1
                for (int pass = 0; pass < 2; pass++) {
                    mbar_wait(sb + BAR_OA + pass * 8, 0);
                    tma2d_store(&P.oa_st, 80 * j, 128 * i + 64 * pass, sb + OFF_Q + pass * 10240);
                    bulk_commit();
                    bulk_wait();
                    st_flag(g_flag_a + pass * 128 + cta, tag);
                }
            }
        } else if (warp == 1) {
            uint32_t sk, sv, spin = 0;
            bar_sync(12, 64);
#pragma unroll 1
            while (true) {
                const uint4 f = ld_relaxed128(g_flag_kv + 2 * lane), g = ld_relaxed128(g_flag_kv + 2 * lane + 64);
                const bool ok = f.y == tag && f.w == tag && g.y == tag && g.w == tag;
                sk = max(max(f.x >> 16, f.z >> 16), max(g.x >> 16, g.z >> 16));
                sv = max(max(f.x & 0xFFFFu, f.z & 0xFFFFu), max(g.x & 0xFFFFu, g.z & 0xFFFFu));
                if (__all_sync(~0u, ok) || ++spin > (1u << 17)) break;
            }
            asm volatile("fence.acq_rel.cta;" ::: "memory");
            sk = __reduce_max_sync(~0u, sk);
            sv = __reduce_max_sync(~0u, sv);
            if (elect_one()) {
                const bool vok = sv == 0 || (sv >= ((127 - 40) << 7) && sv <= ((127 + 40) << 7));
                sts32(sb + OFF_STAT, vok ? sk << 16 : 0x7FC00000u);
                fence_async();
#pragma unroll 1
                for (int n = 0; n < 3; n++) {
                    mbar_expect(sb + BAR_FULL_KV + n * 8, RING_BYTES);
                    bulk1d(sb + OFF_RING + n * RING_BYTES, g_kv + n * RING_BYTES, RING_BYTES, sb + BAR_FULL_KV + n * 8);
                }
                Ring r{0, 0};
#pragma unroll 1
                for (int n = 0; n < 16; n++) {
                    if (n >= 3) {
                        mbar_wait(sb + BAR_EMPTY_KV + r.slot * 8, r.phase ^ 1);
                        mbar_expect(sb + BAR_FULL_KV + r.slot * 8, RING_BYTES);
                        bulk1d(sb + OFF_RING + r.slot * RING_BYTES, g_kv + (n & 7) * RING_BYTES, RING_BYTES, sb + BAR_FULL_KV + r.slot * 8);
                    }
                    mbar_wait(sb + BAR_FULL_KV + r.slot * 8, r.phase);
                    asm volatile("st.release.cta.shared::cta.u32 [%0], %1;" :: "r"(sb + OFF_PUB), "r"(n + 1) : "memory");
                    next_stage(r);
                }
            }
        }
    } else if (wg < 4) {
        {
            if (tid < 30) reinterpret_cast<uint4*>(g_part + j * 1920 + i * 120)[tid] = make_uint4(0u, 0u, 0u, 0u);
            const int k = tid / 5, m0 = 4 * (tid - 5 * k), m1 = m0 + 20;
            const uint32_t row = sb + OFF_WKV + (k >> 3) * 880 + (k & 7) * 16;
            const uint32_t a0 = row + (m0 >> 3) * 176 + (m0 & 7) * 2, a1 = row + (m1 >> 3) * 176 + (m1 & 7) * 2;
            mbar_wait(sb + BAR_KVIN, 0);
            if (wg == 0) TS(13);
            uint2 w[14];
#pragma unroll
            for (int n = 0; n < 7; n++) if (tid < (n < 6 ? 480 : 320)) { w[2 * n] = lds64(sb + OFF_WRAW + tid * 8 + n * 3840); w[2 * n + 1] = lds64(sb + OFF_WRAW + 25600 + tid * 8 + n * 3840); }
#pragma unroll
            for (int n = 0; n < 7; n++) if (tid < (n < 6 ? 480 : 320)) { sts64(a0 + n * 10560, w[2 * n].x, w[2 * n].y); sts64(a1 + n * 10560, w[2 * n + 1].x, w[2 * n + 1].y); }
        }
        fence_async_smem();
        bar_sync(1, 512);
        if (wg == 0) {
            TS(14);
            float d[8];
            const uint64_t da = desc(sb + OFF_WKV, 880, 11), db = desc(sb + OFF_X16, 16, SW128 | 64);
            WG_FENCE();
            wg_ss_n16_ta1_tb0_initd(d, da, db);
#pragma unroll
            for (int k = 1; k < 40; k++) wg_ss_n16_ta1_tb0_d(d, da + 110 * k, db + (k >> 2) * 128 + (k & 3) * 2);
            WG_COMMIT();
            if (tid < 16) {
                const int g = tid >> 3;
                const bool mu = (MUFU_MASK >> ((2 * cta + g) & 7)) & 1;
                const uint32_t a = sb + OFF_IMG + g * 768 + (tid & 7) * 16 + 8;
                sts64(a + 256, mu ? 0u : 0x3F00433Fu, mu ? 0u : 0x00003B4Au);
                sts64(a + 640, 0x00003F80u, 0u);
            }
            WG_WAIT(0);
            fence_regs(d);
            bar_arrive(2, 256);
            TS(15);
#pragma unroll
            for (int hh = 0; hh < 2; hh++) {
                const int m = r0 + 8 * hh;
                if (m < 40) {
                    const int isv = m >= 20, dd = m - 20 * isv;
#pragma unroll
                    for (int g = 0; g < 2; g++) {
                        const bool mu = (MUFU_MASK >> ((2 * cta + g) & 7)) & 1;
                        const float sc = (isv || mu) ? 1.f : 0.5f;
                        const uint32_t pr = pack_bf16(d[4 * g + 2 * hh] * sc, d[4 * g + 2 * hh + 1] * sc);
                        const uint32_t a = sb + OFF_IMG + g * 768 + (3 * isv + (dd >> 3)) * 128 + (dd & 7) * 2 + 2 * q * 16;
                        sts16(a, (uint16_t)pr);
                        sts16(a + 16, (uint16_t)(pr >> 16));
                    }
                }
            }
            bar_sync(3, 128);
            if (warp == 0) {
#pragma unroll
                for (int u = 0; u < 3; u++) {
                    const uint4 v = lds128(sb + OFF_IMG + (lane + 32 * u) * 16);
                    *reinterpret_cast<uint4*>(g_kv + cta * 1536 + (lane + 32 * u) * 16) = v;
                }
                const int key = lane & 15, g = key >> 3;
                const uint32_t a = sb + OFF_IMG + g * 768 + (lane >> 4) * 384 + (key & 7) * 16;
                const uint4 w0 = lds128(a), w1 = lds128(a + 128);
                const uint2 w2 = lds64(a + 256);
                const uint32_t w[10] = {w0.x, w0.y, w0.z, w0.w, w1.x, w1.y, w1.z, w1.w, w2.x, w2.y};
                float n2 = 0.f;
                uint32_t mx = 0;
#pragma unroll
                for (int e = 0; e < 10; e++) {
                    n2 = fmaf(bf_lo(w[e]), bf_lo(w[e]), n2);
                    n2 = fmaf(bf_hi(w[e]), bf_hi(w[e]), n2);
                    mx = max(mx, max(w[e] & 0x7FFFu, (w[e] >> 16) & 0x7FFFu));
                }
                if (!((MUFU_MASK >> ((2 * cta + g) & 7)) & 1)) n2 *= 4.f;
                uint32_t st = lane < 16 ? min(((__float_as_uint(n2) & 0x7FFFFFFFu) + 0xFFFFu) >> 16, 0x7FFFu) : mx;
#pragma unroll
                for (int x = 1; x < 16; x <<= 1) st = max(st, __shfl_xor_sync(~0u, st, x));
                const uint32_t sv = __shfl_sync(~0u, st, 16);
                __syncwarp();
                if (lane == 0) {
                    const unsigned long long f = ((unsigned long long)tag << 32) | (st << 16) | sv;
                    asm volatile("st.release.gpu.global.u64 [%0], %1;" :: "l"(g_flag_kv + cta), "l"(f) : "memory");
                }
                __syncwarp();
                bar_arrive(12, 64);
            }
            TS(17);
        }
        bar_sync(4, 640);
        uint32_t slot = 0;
        const uint4 cz = lds128(sb + OFF_STAT + 16);
#pragma unroll 1
        for (int pass = 0; pass < 2; pass++) {
            uint32_t qf[6];
            const uint32_t qa = sb + OFF_Q + pass * 10240 + r0 * 160 + wg * 40 + q * 4;
            qf[0] = lds32(qa); qf[1] = lds32(qa + 8 * 160);
            qf[2] = lds32(qa + 16); qf[3] = lds32(qa + 8 * 160 + 16);
            qf[4] = q < 2 ? lds32(qa + 32) : 0u; qf[5] = q < 2 ? lds32(qa + 8 * 160 + 32) : 0u;
            if (pass == 0) { count_wait(sb + OFF_PUB, 0, 1); if (wg == 0) { TS(19); TC(26); } }
            float n0 = 0.f, n1 = 0.f;
#pragma unroll
            for (int e = 0; e < 3; e++) {
                n0 = fmaf(bf_lo(qf[2 * e]), bf_lo(qf[2 * e]), fmaf(bf_hi(qf[2 * e]), bf_hi(qf[2 * e]), n0));
                n1 = fmaf(bf_lo(qf[2 * e + 1]), bf_lo(qf[2 * e + 1]), fmaf(bf_hi(qf[2 * e + 1]), bf_hi(qf[2 * e + 1]), n1));
            }
            n0 += __shfl_xor_sync(~0u, n0, 1); n0 += __shfl_xor_sync(~0u, n0, 2);
            n1 += __shfl_xor_sync(~0u, n1, 1); n1 += __shfl_xor_sync(~0u, n1, 2);
            const float k2 = __uint_as_float(lds32(sb + OFF_STAT));
            const uint32_t bad = !(n0 * k2 <= 4000.f && n1 * k2 <= 4000.f);
            uint32_t anybad;
            asm volatile("{\n.reg .pred p, r;\nsetp.ne.u32 p, %1, 0;\nbar.red.or.pred r, %2, 128, p;\nselp.u32 %0, 1, 0, r;\n}" : "=r"(anybad) : "r"(bad), "r"(8 + wg) : "memory");
            float o[12];
#pragma unroll
            for (int k = 0; k < 12; k++) o[k] = 0.f;
            fence_regs(o);
            if (!__shfl_sync(~0u, anybad, 0)) {
                if (q >= 2) qf[4] = qf[5] = q == 2 ? 0x3F803F80u : 0x00003F80u;
                attend<true>(sb, slot, pass, qf, o, cz.x, cz.y, cz.z);
            } else {
                attend<false>(sb, slot, pass, qf, o, cz.x, cz.y, cz.z);
            }
            const float i0 = rcpf(__shfl_sync(~0u, o[8], (lane & ~3) | 2)), i1 = rcpf(__shfl_sync(~0u, o[10], (lane & ~3) | 2));
            const uint32_t dst = sb + OFF_Q + pass * 10240 + r0 * 160 + wg * 40 + q * 4;
#pragma unroll
            for (int b = 0; b < 3; b++) {
                if (b < 2 || q < 2) {
                    sts32(dst + 16 * b, pack_bf16(o[4 * b] * i0, o[4 * b + 1] * i0));
                    sts32(dst + 8 * 160 + 16 * b, pack_bf16(o[4 * b + 2] * i1, o[4 * b + 3] * i1));
                }
            }
            fence_async_smem();
            __syncwarp();
            if (lane == 0) mbar_arrive(sb + BAR_OA + pass * 8);
            if (wg == 0) { TS(20 + pass); TC(27 + pass); }
        }
        TS(22 + wg);
    } else {
        asm volatile("setmaxnreg.inc.sync.aligned.u32 128;");
        const uint32_t mrow = 16 * warp + (lane & 15), mcol = lane >> 4;
        const uint32_t xrow = mrow * 160 + mcol * 16, xgrp = (mrow & 7) * 16 + mcol * 128;
#pragma unroll 1
        for (int pass = 0; pass < NPASS; pass++) {
        if (pass == 4) {
        mbar_wait(sb + BAR_KVB, 0);
        TS(7);
        if (tid < 592) {
            const int m = tid - 512, h = m / 20;
            const uint32_t x0 = sb + OFF_KVB + (m >> 3) * 1408 + (m & 7) * 16;
#pragma unroll
            for (int e = 0; e < 5; e++) {
                const uint4 v = lds128(sb + OFF_PST + m * 96 + e * 16);
                const int n = 20 * h + 4 * e;
                sts64(x0 + (n >> 3) * 128 + (n & 4) * 2, pack_bf16(__uint_as_float(v.x), __uint_as_float(v.y)), pack_bf16(__uint_as_float(v.z), __uint_as_float(v.w)));
            }
            sts16(x0 + 1280 + h * 2, (uint16_t)pack_bf16(__uint_as_float(lds32(sb + OFF_PST + m * 96 + 80)), 0.f));
        }
        fence_async_smem();
        bar_sync(6, 128);
#pragma unroll 1
        for (int half = 0; half < 2; half++) linear_out(sb, half, sb + OFF_PK + half * 10240 + xrow, q);
        fence_async_smem();
        __syncwarp();
        if (lane == 0) mbar_arrive(sb + BAR_OB);
        }
        float a[40], b[40];
        gemm_pass(sb, pass, a, b);
        if (pass == 0) {
        TS(1);
        bar_sync(2, 256);
        stage_tile<1>(sb + OFF_Q + xrow, 16, a);
        stage_tile<1>(sb + OFF_Q + 10240 + xrow, 16, b);
        bar_arrive(4, 640);
        TS(2);
        } else if (pass == 1 || pass == 3) {
        TS(pass == 1 ? 3 : 6);
        stage_tile<2>(sb + OFF_PK + (mrow >> 3) * 1280 + xgrp, 128, a);
        stage_tile<2>(sb + OFF_PK + (8 + (mrow >> 3)) * 1280 + xgrp, 128, b);
        } else if (pass == 2) {
        TS(4);
        stage_tile<0>(sb + OFF_V + 128 + (mrow >> 3) * 1536 + xgrp, 128, a);
        stage_tile<0>(sb + OFF_V + 128 + (8 + (mrow >> 3)) * 1536 + xgrp, 128, b);
        {
            const uint32_t x = sb + OFF_V + ((tid - 512) >> 3) * 1536 + (tid & 7) * 16;
            sts128(x, 0x3F80u, 0u, 0u, 0u);
            sts128(x + 11 * 128, 0x3F80u, 0u, 0u, 0u);
        }
        fence_async_smem();
        bar_sync(6, 128);
        {
            float d1[36], d2[16]; zero_regs(d1); zero_regs(d2);
            const uint64_t da = desc(sb + OFF_PK, 1280, 8), db = desc(sb + OFF_V, 1536, 8);
            WG_FENCE();
#pragma unroll
            for (int k = 0; k < 8; k++) {
                wg_ss_n72_ta1_tb1_d(d1, da + 160 * k, db + 192 * k);
                wg_ss_n32_ta1_tb1_d(d2, da + 16 + 160 * k, db + 64 + 192 * k);
            }
            WG_COMMIT();
            WG_WAIT(0);
            fence_regs(d1); fence_regs(d2);
            bar_sync(6, 128);
#pragma unroll
            for (int u = 0; u < 7; u++) if (u < 6 || tid < 624) sts128(sb + OFF_KVB + (tid - 512 + 128 * u) * 16, 0u, 0u, 0u, 0u);
            const uint32_t part = sb + OFF_PST;
#pragma unroll
            for (int hh = 0; hh < 2; hh++) {
                const int m = r0 + 8 * hh;
                if (m < 60) {
                    const int h20 = (m / 20) * 20;
                    if (q == 0) sts128(part + m * 96 + 80, __float_as_uint(d1[2 * hh]), 0u, 0u, 0u);
#pragma unroll
                    for (int k = 1; k < 9; k++) {
                        const int e = 8 * (k - 1) + 2 * q - h20;
                        if (e >= 0 && e < 20) sts64(part + m * 96 + e * 4, __float_as_uint(d1[4 * k + 2 * hh]), __float_as_uint(d1[4 * k + 2 * hh + 1]));
                    }
                }
                if (m >= 44) {
                    if (q == 0) sts128(part + (m + 16) * 96 + 80, __float_as_uint(d2[12 + 2 * hh]), 0u, 0u, 0u);
#pragma unroll
                    for (int k = 0; k < 3; k++) {
                        const int e = 8 * k + 2 * q - 4;
                        if (e >= 0) sts64(part + (m + 16) * 96 + e * 4, __float_as_uint(d2[4 * k + 2 * hh]), __float_as_uint(d2[4 * k + 2 * hh + 1]));
                    }
                }
            }
            fence_async_smem();
            __syncwarp();
            if (lane == 0) mbar_arrive(sb + BAR_PART);
        }
        } else {
        __nv_bfloat16* out = P.out + (128 * i + r0) * 1280 + 80 * j + 2 * q + 640;
        store_tile(out, 1280, a);
        store_tile(out + 64 * 1280, 1280, b);
        TS(9);
        }
        }
        if (NPASS == 5) {
            mbar_wait(sb + BAR_WA, 0);
#pragma unroll 1
            for (int half = 0; half < 2; half++) {
                float a[40];
                gemm_half(sb, half, a);
                store_tile(P.out + (128 * i + 64 * half + r0) * 1280 + 80 * j + 2 * q, 1280, a);
                TS(half ? 11 : 12);
            }
        }
        if (cta == 0 && tid == 512) *(volatile uint32_t*)&g_epoch = tag;
    }
}

typedef CUresult (*EncodeFn)(CUtensorMap*, CUtensorMapDataType, cuuint32_t, void*, const cuuint64_t*, const cuuint64_t*,
                             const cuuint32_t*, const cuuint32_t*, CUtensorMapInterleave, CUtensorMapSwizzle,
                             CUtensorMapL2promotion, CUtensorMapFloatOOBfill);

void make_map(EncodeFn enc, CUtensorMap* m, const void* p, uint32_t box_cols, uint32_t box_rows) {
    cuuint64_t dims[2] = {640, 2048}, strides[1] = {1280};
    cuuint32_t box[2] = {box_cols, box_rows}, es[2] = {1, 1};
    enc(m, CU_TENSOR_MAP_DATA_TYPE_BFLOAT16, 2, const_cast<void*>(p), dims, strides, box, es, CU_TENSOR_MAP_INTERLEAVE_NONE,
        box_cols == 64 ? CU_TENSOR_MAP_SWIZZLE_128B : CU_TENSOR_MAP_SWIZZLE_NONE, CU_TENSOR_MAP_L2_PROMOTION_L2_128B, CU_TENSOR_MAP_FLOAT_OOB_FILL_NONE);
}
void make_x16map(EncodeFn enc, CUtensorMap* m, const void* p) {
    cuuint64_t dims[3] = {64, 2048, 10}, strides[2] = {1280, 128};
    cuuint32_t box[3] = {64, 16, 10}, es[3] = {1, 1, 1};
    enc(m, CU_TENSOR_MAP_DATA_TYPE_BFLOAT16, 3, const_cast<void*>(p), dims, strides, box, es, CU_TENSOR_MAP_INTERLEAVE_NONE,
        CU_TENSOR_MAP_SWIZZLE_128B, CU_TENSOR_MAP_L2_PROMOTION_L2_128B, CU_TENSOR_MAP_FLOAT_OOB_FILL_NONE);
}
void make_wmap(EncodeFn enc, CUtensorMap* m, const void* p, uint64_t cols) {
    cuuint64_t dims[3] = {16, 640, cols / 16}, strides[2] = {cols * 2, 32};
    cuuint32_t box[3] = {16, 64, 5}, es[3] = {1, 1, 1};
    enc(m, CU_TENSOR_MAP_DATA_TYPE_BFLOAT16, 3, const_cast<void*>(p), dims, strides, box, es, CU_TENSOR_MAP_INTERLEAVE_NONE,
        CU_TENSOR_MAP_SWIZZLE_32B, CU_TENSOR_MAP_L2_PROMOTION_L2_128B, CU_TENSOR_MAP_FLOAT_OOB_FILL_NONE);
}

}

extern "C" void kernel_launch(void* const* d_in, const int* in_sizes, int n_in, void* d_out, int out_size) {
    static EncodeFn enc = nullptr;
    static void *oa = nullptr, *ob = nullptr;
    static int sms = 0;
    if (!enc) {
        void* fn = nullptr;
        cudaDriverEntryPointQueryResult qr;
        cudaGetDriverEntryPoint("cuTensorMapEncodeTiled", &fn, cudaEnableDefault, &qr);
        enc = (EncodeFn)fn;
        int dev = 0;
        cudaGetDevice(&dev);
        cudaDeviceGetAttribute(&sms, cudaDevAttrMultiProcessorCount, dev);
        cudaGetSymbolAddress(&oa, g_oa);
        cudaGetSymbolAddress(&ob, g_ob);
        cudaFuncSetAttribute(fused_kernel, cudaFuncAttributeMaxDynamicSharedMemorySize, SMEM_BYTES);
    }
    Params P;
    make_map(enc, &P.xa, d_in[0], 64, 128);
    make_x16map(enc, &P.xa16, d_in[0]);
    make_map(enc, &P.xb, d_in[5], 64, 128);
    make_wmap(enc, &P.wq, d_in[1], 640);
    make_wmap(enc, &P.wqkv, d_in[6], 1920);
    make_wmap(enc, &P.woa, d_in[4], 640);
    make_wmap(enc, &P.wob, d_in[7], 640);
    make_map(enc, &P.oa, oa, 64, 64);
    make_map(enc, &P.ob, ob, 64, 128);
    make_map(enc, &P.oa_st, oa, 80, 64);
    make_map(enc, &P.ob_st, ob, 80, 128);
    for (int k = 0; k < 8; k++) P.in[k] = (const uint8_t*)d_in[k];
    P.out = (__nv_bfloat16*)d_out;
    P.helpers = sms >= NCTA + 4;
    fused_kernel<<<P.helpers ? NCTA + 4 : NCTA, NTHR, SMEM_BYTES, cudaStreamPerThread>>>(P);
}
```

```cpp
#include <cuda_runtime.h>
#include <cuda_bf16.h>
#include <cuda.h>
#include <stdint.h>

namespace {

constexpr int NCTA = 128;
constexpr int NTHR = 768;

constexpr uint32_t OFF_STAGE = 0;
constexpr uint32_t STAGE_BYTES = 26624;
constexpr uint32_t OFF_PK = 79872;
constexpr uint32_t OFF_WRAW = OFF_PK;
constexpr uint32_t OFF_V = 100352;
constexpr uint32_t OFF_KVB = OFF_V;
constexpr uint32_t OFF_PST = OFF_V + 14336;
constexpr uint32_t OFF_WA = 0;
constexpr uint32_t OFF_XA = 102400;
constexpr uint32_t OFF_RING = 135168;
constexpr uint32_t RING_BYTES = 24576;
constexpr uint32_t OFF_WKV = OFF_RING;
constexpr uint32_t OFF_Q = 208896;
constexpr uint32_t OFF_X16 = OFF_Q;
constexpr uint32_t OFF_MISC = 229376;
constexpr uint32_t OFF_BAR = OFF_MISC;
constexpr uint32_t BAR_FULL_G = OFF_BAR, BAR_EMPTY_G = OFF_BAR + 24, BAR_FULL_KV = OFF_BAR + 48, BAR_EMPTY_KV = OFF_BAR + 72;
constexpr uint32_t BAR_OA = OFF_BAR + 96, BAR_WA = OFF_BAR + 112, BAR_FULL_X = OFF_BAR + 120, BAR_EMPTY_X = OFF_BAR + 152, BAR_A0 = OFF_BAR + 184;
constexpr uint32_t OFF_QUEUE = OFF_BAR + 192;
constexpr uint32_t BAR_PART = OFF_BAR + 264, BAR_KVB = OFF_BAR + 272, BAR_OB = OFF_BAR + 280, BAR_KVIN = OFF_BAR + 288;
constexpr uint32_t OFF_PUB = OFF_BAR + 296;
constexpr uint32_t OFF_STAT = OFF_BAR + 304;
constexpr uint32_t OFF_IMG = OFF_MISC + 384;
constexpr uint32_t OFF_TS = OFF_IMG + 1536;
constexpr uint32_t SMEM_BYTES = OFF_TS + 256;

#define MUFU_MASK 0x4A

#define PFS 3
#define HOLD 2
#define NPASS 5
constexpr float LOG2E = 1.4426950408889634f;
constexpr float QSCALE = 0.22360679774997896f * LOG2E;

struct Params {
    CUtensorMap xa, xa16, wq, xb, wqkv, woa, wob, oa, ob, oa_st, ob_st;
    const uint8_t* in[8];
    __nv_bfloat16* out;
    int helpers;
};

}

__device__ __align__(1024) uint8_t g_kv[256 * 768];
__device__ __align__(1024) __nv_bfloat16 g_oa[2048 * 640];
__device__ __align__(1024) __nv_bfloat16 g_ob[2048 * 640];
__device__ __align__(1024) uint8_t g_ox[16 * 40 * 2048];
__device__ __align__(128) float g_part[8 * 1920];
__device__ __align__(128) unsigned long long g_flag_kv[128];
__device__ __align__(128) uint16_t g_flag_b1[128];
__device__ __align__(128) uint16_t g_flag_b2[128];
__device__ __align__(128) uint16_t g_flag_a[128];
__device__ __align__(128) uint16_t g_flag_w[32];
__device__ __align__(1024) uint8_t g_wt[320 * 10240];
__device__ uint32_t g_epoch;
#define TS(k)
#define TC(k)

namespace {

__device__ __forceinline__ void wg_rs_n24_tb1_d(float (&d)[12], uint32_t a0, uint32_t a1, uint32_t a2, uint32_t a3, uint64_t db) {
    asm volatile("{\n.reg .pred p;\nsetp.ne.b32 p, 1, 0;\n"
        "wgmma.mma_async.sync.aligned.m64n24k16.f32.bf16.bf16 {%0, %1, %2, %3, %4, %5, %6, %7, %8, %9, %10, %11}, {%12, %13, %14, %15}, %16, p, 1, 1, 1;\n}\n"
        : "+f"(d[0]), "+f"(d[1]), "+f"(d[2]), "+f"(d[3]), "+f"(d[4]), "+f"(d[5]), "+f"(d[6]), "+f"(d[7]), "+f"(d[8]), "+f"(d[9]), "+f"(d[10]), "+f"(d[11])
        : "r"(a0), "r"(a1), "r"(a2), "r"(a3), "l"(db));
}
__device__ __forceinline__ void wg_rs_n64_tb0_d(float (&d)[32], uint32_t a0, uint32_t a1, uint32_t a2, uint32_t a3, uint64_t db) {
    asm volatile("{\n.reg .pred p;\nsetp.ne.b32 p, 1, 0;\n"
        "wgmma.mma_async.sync.aligned.m64n64k16.f32.bf16.bf16 {%0, %1, %2, %3, %4, %5, %6, %7, %8, %9, %10, %11, %12, %13, %14, %15, %16, %17, %18, %19, %20, %21, %22, %23, %24, %25, %26, %27, %28, %29, %30, %31}, {%32, %33, %34, %35}, %36, p, 1, 1, 0;\n}\n"
        : "+f"(d[0]), "+f"(d[1]), "+f"(d[2]), "+f"(d[3]), "+f"(d[4]), "+f"(d[5]), "+f"(d[6]), "+f"(d[7]), "+f"(d[8]), "+f"(d[9]), "+f"(d[10]), "+f"(d[11]), "+f"(d[12]), "+f"(d[13]), "+f"(d[14]), "+f"(d[15]), "+f"(d[16]), "+f"(d[17]), "+f"(d[18]), "+f"(d[19]), "+f"(d[20]), "+f"(d[21]), "+f"(d[22]), "+f"(d[23]), "+f"(d[24]), "+f"(d[25]), "+f"(d[26]), "+f"(d[27]), "+f"(d[28]), "+f"(d[29]), "+f"(d[30]), "+f"(d[31])
        : "r"(a0), "r"(a1), "r"(a2), "r"(a3), "l"(db));
}
__device__ __forceinline__ void wg_rs_n64_tb0_initd(float (&d)[32], uint32_t a0, uint32_t a1, uint32_t a2, uint32_t a3, uint64_t db) {
    asm volatile("{\n.reg .pred p;\nsetp.ne.b32 p, 0, 0;\n"
        "wgmma.mma_async.sync.aligned.m64n64k16.f32.bf16.bf16 {%0, %1, %2, %3, %4, %5, %6, %7, %8, %9, %10, %11, %12, %13, %14, %15, %16, %17, %18, %19, %20, %21, %22, %23, %24, %25, %26, %27, %28, %29, %30, %31}, {%32, %33, %34, %35}, %36, p, 1, 1, 0;\n}\n"
        : "=f"(d[0]), "=f"(d[1]), "=f"(d[2]), "=f"(d[3]), "=f"(d[4]), "=f"(d[5]), "=f"(d[6]), "=f"(d[7]), "=f"(d[8]), "=f"(d[9]), "=f"(d[10]), "=f"(d[11]), "=f"(d[12]), "=f"(d[13]), "=f"(d[14]), "=f"(d[15]), "=f"(d[16]), "=f"(d[17]), "=f"(d[18]), "=f"(d[19]), "=f"(d[20]), "=f"(d[21]), "=f"(d[22]), "=f"(d[23]), "=f"(d[24]), "=f"(d[25]), "=f"(d[26]), "=f"(d[27]), "=f"(d[28]), "=f"(d[29]), "=f"(d[30]), "=f"(d[31])
        : "r"(a0), "r"(a1), "r"(a2), "r"(a3), "l"(db));
}
__device__ __forceinline__ void wg_ss_n16_ta1_tb0_d(float (&d)[8], uint64_t da, uint64_t db) {
    asm volatile("{\n.reg .pred p;\nsetp.ne.b32 p, 1, 0;\n"
        "wgmma.mma_async.sync.aligned.m64n16k16.f32.bf16.bf16 {%0, %1, %2, %3, %4, %5, %6, %7}, %8, %9, p, 1, 1, 1, 0;\n}\n"
        : "+f"(d[0]), "+f"(d[1]), "+f"(d[2]), "+f"(d[3]), "+f"(d[4]), "+f"(d[5]), "+f"(d[6]), "+f"(d[7])
        : "l"(da), "l"(db));
}
__device__ __forceinline__ void wg_ss_n16_ta1_tb0_initd(float (&d)[8], uint64_t da, uint64_t db) {
    asm volatile("{\n.reg .pred p;\nsetp.ne.b32 p, 0, 0;\n"
        "wgmma.mma_async.sync.aligned.m64n16k16.f32.bf16.bf16 {%0, %1, %2, %3, %4, %5, %6, %7}, %8, %9, p, 1, 1, 1, 0;\n}\n"
        : "=f"(d[0]), "=f"(d[1]), "=f"(d[2]), "=f"(d[3]), "=f"(d[4]), "=f"(d[5]), "=f"(d[6]), "=f"(d[7])
        : "l"(da), "l"(db));
}
__device__ __forceinline__ void wg_ss_n32_ta1_tb1_d(float (&d)[16], uint64_t da, uint64_t db) {
    asm volatile("{\n.reg .pred p;\nsetp.ne.b32 p, 1, 0;\n"
        "wgmma.mma_async.sync.aligned.m64n32k16.f32.bf16.bf16 {%0, %1, %2, %3, %4, %5, %6, %7, %8, %9, %10, %11, %12, %13, %14, %15}, %16, %17, p, 1, 1, 1, 1;\n}\n"
        : "+f"(d[0]), "+f"(d[1]), "+f"(d[2]), "+f"(d[3]), "+f"(d[4]), "+f"(d[5]), "+f"(d[6]), "+f"(d[7]), "+f"(d[8]), "+f"(d[9]), "+f"(d[10]), "+f"(d[11]), "+f"(d[12]), "+f"(d[13]), "+f"(d[14]), "+f"(d[15])
        : "l"(da), "l"(db));
}
__device__ __forceinline__ void wg_ss_n72_ta1_tb1_d(float (&d)[36], uint64_t da, uint64_t db) {
    asm volatile("{\n.reg .pred p;\nsetp.ne.b32 p, 1, 0;\n"
        "wgmma.mma_async.sync.aligned.m64n72k16.f32.bf16.bf16 {%0, %1, %2, %3, %4, %5, %6, %7, %8, %9, %10, %11, %12, %13, %14, %15, %16, %17, %18, %19, %20, %21, %22, %23, %24, %25, %26, %27, %28, %29, %30, %31, %32, %33, %34, %35}, %36, %37, p, 1, 1, 1, 1;\n}\n"
        : "+f"(d[0]), "+f"(d[1]), "+f"(d[2]), "+f"(d[3]), "+f"(d[4]), "+f"(d[5]), "+f"(d[6]), "+f"(d[7]), "+f"(d[8]), "+f"(d[9]), "+f"(d[10]), "+f"(d[11]), "+f"(d[12]), "+f"(d[13]), "+f"(d[14]), "+f"(d[15]), "+f"(d[16]), "+f"(d[17]), "+f"(d[18]), "+f"(d[19]), "+f"(d[20]), "+f"(d[21]), "+f"(d[22]), "+f"(d[23]), "+f"(d[24]), "+f"(d[25]), "+f"(d[26]), "+f"(d[27]), "+f"(d[28]), "+f"(d[29]), "+f"(d[30]), "+f"(d[31]), "+f"(d[32]), "+f"(d[33]), "+f"(d[34]), "+f"(d[35])
        : "l"(da), "l"(db));
}
__device__ __forceinline__ void wg_ss_n80_ta0_tb1_d(float (&d)[40], uint64_t da, uint64_t db) {
    asm volatile("{\n.reg .pred p;\nsetp.ne.b32 p, 1, 0;\n"
        "wgmma.mma_async.sync.aligned.m64n80k16.f32.bf16.bf16 {%0, %1, %2, %3, %4, %5, %6, %7, %8, %9, %10, %11, %12, %13, %14, %15, %16, %17, %18, %19, %20, %21, %22, %23, %24, %25, %26, %27, %28, %29, %30, %31, %32, %33, %34, %35, %36, %37, %38, %39}, %40, %41, p, 1, 1, 0, 1;\n}\n"
        : "+f"(d[0]), "+f"(d[1]), "+f"(d[2]), "+f"(d[3]), "+f"(d[4]), "+f"(d[5]), "+f"(d[6]), "+f"(d[7]), "+f"(d[8]), "+f"(d[9]), "+f"(d[10]), "+f"(d[11]), "+f"(d[12]), "+f"(d[13]), "+f"(d[14]), "+f"(d[15]), "+f"(d[16]), "+f"(d[17]), "+f"(d[18]), "+f"(d[19]), "+f"(d[20]), "+f"(d[21]), "+f"(d[22]), "+f"(d[23]), "+f"(d[24]), "+f"(d[25]), "+f"(d[26]), "+f"(d[27]), "+f"(d[28]), "+f"(d[29]), "+f"(d[30]), "+f"(d[31]), "+f"(d[32]), "+f"(d[33]), "+f"(d[34]), "+f"(d[35]), "+f"(d[36]), "+f"(d[37]), "+f"(d[38]), "+f"(d[39])
        : "l"(da), "l"(db));
}
__device__ __forceinline__ void wg_ss_n80_ta0_tb1_initd(float (&d)[40], uint64_t da, uint64_t db) {
    asm volatile("{\n.reg .pred p;\nsetp.ne.b32 p, 0, 0;\n"
        "wgmma.mma_async.sync.aligned.m64n80k16.f32.bf16.bf16 {%0, %1, %2, %3, %4, %5, %6, %7, %8, %9, %10, %11, %12, %13, %14, %15, %16, %17, %18, %19, %20, %21, %22, %23, %24, %25, %26, %27, %28, %29, %30, %31, %32, %33, %34, %35, %36, %37, %38, %39}, %40, %41, p, 1, 1, 0, 1;\n}\n"
        : "=f"(d[0]), "=f"(d[1]), "=f"(d[2]), "=f"(d[3]), "=f"(d[4]), "=f"(d[5]), "=f"(d[6]), "=f"(d[7]), "=f"(d[8]), "=f"(d[9]), "=f"(d[10]), "=f"(d[11]), "=f"(d[12]), "=f"(d[13]), "=f"(d[14]), "=f"(d[15]), "=f"(d[16]), "=f"(d[17]), "=f"(d[18]), "=f"(d[19]), "=f"(d[20]), "=f"(d[21]), "=f"(d[22]), "=f"(d[23]), "=f"(d[24]), "=f"(d[25]), "=f"(d[26]), "=f"(d[27]), "=f"(d[28]), "=f"(d[29]), "=f"(d[30]), "=f"(d[31]), "=f"(d[32]), "=f"(d[33]), "=f"(d[34]), "=f"(d[35]), "=f"(d[36]), "=f"(d[37]), "=f"(d[38]), "=f"(d[39])
        : "l"(da), "l"(db));
}
__device__ __forceinline__ void wg_ss_n88_ta0_tb1_d(float (&d)[44], uint64_t da, uint64_t db) {
    asm volatile("{\n.reg .pred p;\nsetp.ne.b32 p, 1, 0;\n"
        "wgmma.mma_async.sync.aligned.m64n88k16.f32.bf16.bf16 {%0, %1, %2, %3, %4, %5, %6, %7, %8, %9, %10, %11, %12, %13, %14, %15, %16, %17, %18, %19, %20, %21, %22, %23, %24, %25, %26, %27, %28, %29, %30, %31, %32, %33, %34, %35, %36, %37, %38, %39, %40, %41, %42, %43}, %44, %45, p, 1, 1, 0, 1;\n}\n"
        : "+f"(d[0]), "+f"(d[1]), "+f"(d[2]), "+f"(d[3]), "+f"(d[4]), "+f"(d[5]), "+f"(d[6]), "+f"(d[7]), "+f"(d[8]), "+f"(d[9]), "+f"(d[10]), "+f"(d[11]), "+f"(d[12]), "+f"(d[13]), "+f"(d[14]), "+f"(d[15]), "+f"(d[16]), "+f"(d[17]), "+f"(d[18]), "+f"(d[19]), "+f"(d[20]), "+f"(d[21]), "+f"(d[22]), "+f"(d[23]), "+f"(d[24]), "+f"(d[25]), "+f"(d[26]), "+f"(d[27]), "+f"(d[28]), "+f"(d[29]), "+f"(d[30]), "+f"(d[31]), "+f"(d[32]), "+f"(d[33]), "+f"(d[34]), "+f"(d[35]), "+f"(d[36]), "+f"(d[37]), "+f"(d[38]), "+f"(d[39]), "+f"(d[40]), "+f"(d[41]), "+f"(d[42]), "+f"(d[43])
        : "l"(da), "l"(db));
}

#define WG_FENCE() asm volatile("wgmma.fence.sync.aligned;" ::: "memory")
#define WG_COMMIT() asm volatile("wgmma.commit_group.sync.aligned;" ::: "memory")
#define WG_WAIT(n) asm volatile("wgmma.wait_group.sync.aligned %0;" :: "n"(n) : "memory")
template <int NR> __device__ __forceinline__ void fence_regs(float (&d)[NR]) {
#pragma unroll
    for (int i = 0; i < NR; i++) asm volatile("" : "+f"(d[i]) :: "memory");
}
template <int NR> __device__ __forceinline__ void zero_regs(float (&d)[NR]) {
#pragma unroll
    for (int i = 0; i < NR; i++) asm volatile("mov.b32 %0, 0;" : "=f"(d[i]) :: "memory");
}
constexpr uint32_t SW128 = 1u << 30, SW32 = 3u << 30;
__device__ __forceinline__ constexpr uint32_t dlo(uint32_t lbo) { return (lbo >> 4) << 16; }

__device__ __forceinline__ void bar_sync(int id, int n) { asm volatile("bar.sync %0, %1;" :: "r"(id), "r"(n) : "memory"); }
__device__ __forceinline__ void bar_arrive(int id, int n) { asm volatile("bar.arrive %0, %1;" :: "r"(id), "r"(n) : "memory"); }
__device__ __forceinline__ void mbar_init(uint32_t bar, uint32_t cnt) { asm volatile("mbarrier.init.shared::cta.b64 [%0], %1;" :: "r"(bar), "r"(cnt) : "memory"); }
__device__ __forceinline__ void mbar_arrive(uint32_t bar) { asm volatile("mbarrier.arrive.shared::cta.b64 _, [%0];" :: "r"(bar) : "memory"); }
__device__ __forceinline__ void mbar_expect(uint32_t bar, uint32_t bytes) { asm volatile("mbarrier.arrive.expect_tx.shared::cta.b64 _, [%0], %1;" :: "r"(bar), "r"(bytes) : "memory"); }
__device__ __forceinline__ void mbar_wait(uint32_t bar, uint32_t parity) {
    asm volatile("{\n.reg .pred p;\n.reg .u32 n;\nmov.u32 n, 0;\n"
                 "MW_LOOP:\nmbarrier.try_wait.parity.shared::cta.b64 p, [%0], %1;\n@p bra.uni MW_DONE;\n"
                 "add.u32 n, n, 1;\nsetp.lt.u32 p, n, 32768;\n@p bra.uni MW_LOOP;\nMW_DONE:\n}"
                 :: "r"(bar), "r"(parity) : "memory");
}
__device__ __forceinline__ void count_wait(uint32_t addr, uint32_t seen, uint32_t need) {
    asm volatile("{\n.reg .pred p;\n.reg .u32 n, v;\nmov.u32 n, 0;\nmov.u32 v, %1;\n"
                 "CW_LOOP:\nsetp.ge.u32 p, v, %2;\n@p bra.uni CW_DONE;\nld.volatile.shared.u32 v, [%0];\n"
                 "add.u32 n, n, 1;\nsetp.lt.u32 p, n, 0x400000;\n@p bra.uni CW_LOOP;\nCW_DONE:\n}"
                 :: "r"(addr), "r"(seen), "r"(need) : "memory");
}
__device__ __forceinline__ uint32_t queue_wait(uint32_t addr) {
    uint32_t v;
    asm volatile("{\n.reg .pred p;\n.reg .u32 n;\nmov.u32 n, 0;\n"
                 "QW_LOOP:\nld.acquire.cta.shared::cta.u32 %0, [%1];\nsetp.ne.u32 p, %0, 0;\n@p bra.uni QW_DONE;\n"
                 "add.u32 n, n, 1;\nsetp.lt.u32 p, n, 0x400000;\n@p bra.uni QW_LOOP;\nmov.u32 %0, 1;\nQW_DONE:\n}"
                 : "=r"(v) : "r"(addr) : "memory");
    return v;
}
__device__ __forceinline__ void tma2d(uint32_t dst, const CUtensorMap* m, int x, int y, uint32_t bar) {
    asm volatile("cp.async.bulk.tensor.2d.shared::cluster.global.mbarrier::complete_tx::bytes [%0], [%1, {%2, %3}], [%4];"
                 :: "r"(dst), "l"(m), "r"(x), "r"(y), "r"(bar) : "memory");
}
__device__ __forceinline__ void bulk1d(uint32_t dst, const void* src, uint32_t bytes, uint32_t bar) {
    asm volatile("cp.async.bulk.shared::cluster.global.mbarrier::complete_tx::bytes [%0], [%1], %2, [%3];"
                 :: "r"(dst), "l"(src), "r"(bytes), "r"(bar) : "memory");
}
__device__ __forceinline__ void tma3d(uint32_t dst, const CUtensorMap* m, int y, int z, uint32_t bar) {
    asm volatile("cp.async.bulk.tensor.3d.shared::cluster.global.mbarrier::complete_tx::bytes [%0], [%1, {0, %2, %3}], [%4];"
                 :: "r"(dst), "l"(m), "r"(y), "r"(z), "r"(bar) : "memory");
}
__device__ __forceinline__ void tma2d_store(const CUtensorMap* m, int x, int y, uint32_t src) {
    asm volatile("cp.async.bulk.tensor.2d.global.shared::cta.bulk_group [%0, {%1, %2}], [%3];" :: "l"(m), "r"(x), "r"(y), "r"(src) : "memory");
}
__device__ __forceinline__ void bulk_store(void* dst, uint32_t src, uint32_t bytes) {
    asm volatile("cp.async.bulk.global.shared::cta.bulk_group [%0], [%1], %2;" :: "l"(dst), "r"(src), "r"(bytes) : "memory");
}
__device__ __forceinline__ void bulk_add_f32(void* dst, uint32_t src, uint32_t bytes) {
    asm volatile("cp.reduce.async.bulk.global.shared::cta.bulk_group.add.f32 [%0], [%1], %2;" :: "l"(dst), "r"(src), "r"(bytes) : "memory");
}
__device__ __forceinline__ void bulk_commit() { asm volatile("cp.async.bulk.commit_group;" ::: "memory"); }
__device__ __forceinline__ void bulk_wait() {
    asm volatile("cp.async.bulk.wait_group 0;\nfence.proxy.async.global;" ::: "memory");
}
__device__ __forceinline__ void prefetch_l2(const void* p, uint32_t bytes) { asm volatile("cp.async.bulk.prefetch.L2.global [%0], %1;" :: "l"(p), "r"(bytes) : "memory"); }
__device__ __forceinline__ void prefetch_map(const CUtensorMap* m) { asm volatile("prefetch.tensormap [%0];" :: "l"(m) : "memory"); }
__device__ __forceinline__ uint32_t opaque_tid() { uint32_t t; asm volatile("mov.u32 %0, %tid.x;" : "=r"(t) :: "memory"); return t; }
__device__ __forceinline__ uint32_t opaque_cta() { uint32_t t; asm volatile("mov.u32 %0, %ctaid.x;" : "=r"(t) :: "memory"); return t; }
__device__ __forceinline__ bool elect_one() {
    uint32_t p;
    asm volatile("{\n.reg .pred p;\nelect.sync _|p, 0xffffffff;\nselp.u32 %0, 1, 0, p;\n}" : "=r"(p));
    return p;
}
__device__ __forceinline__ void fence_async() { asm volatile("fence.proxy.async.global;" ::: "memory"); }
__device__ __forceinline__ void fence_async_smem() { asm volatile("fence.proxy.async.shared::cta;" ::: "memory"); }
__device__ __forceinline__ void st_flag(uint16_t* p, uint32_t v) { asm volatile("st.release.gpu.global.u16 [%0], %1;" :: "l"(p), "h"((uint16_t)v) : "memory"); }
__device__ __forceinline__ void st_relaxed(void* p, uint32_t v) { asm volatile("st.relaxed.gpu.global.u32 [%0], %1;" :: "l"(p), "r"(v) : "memory"); }
__device__ __forceinline__ uint4 ld_relaxed128(const void* p) { uint4 v; asm volatile("ld.relaxed.gpu.global.v4.u32 {%0, %1, %2, %3}, [%4];" : "=r"(v.x), "=r"(v.y), "=r"(v.z), "=r"(v.w) : "l"(p) : "memory"); return v; }
__device__ __forceinline__ uint4 ld_acquire128(const void* p) { uint4 v; asm volatile("ld.acquire.gpu.global.v4.u32 {%0, %1, %2, %3}, [%4];" : "=r"(v.x), "=r"(v.y), "=r"(v.z), "=r"(v.w) : "l"(p) : "memory"); return v; }
__device__ __forceinline__ void poll1(const uint16_t* p, uint32_t tag) {
#pragma unroll 1
    for (uint32_t spin = 0; spin < (1u << 17); spin++) {
        uint16_t v;
        asm volatile("ld.acquire.gpu.global.u16 %0, [%1];" : "=h"(v) : "l"(p) : "memory");
        if (v == (uint16_t)tag) break;
    }
    fence_async();
}
__device__ __forceinline__ void poll8(const uint16_t* p, uint32_t tag) {
    const uint32_t t2 = (tag & 0xFFFFu) * 0x10001u;
#pragma unroll 1
    for (uint32_t spin = 0; spin < (1u << 17); spin++) {
        const uint4 a = ld_acquire128(p);
        if (a.x == t2 && a.y == t2 && a.z == t2 && a.w == t2) break;
    }
    fence_async();
}
__device__ __forceinline__ uint32_t lds32(uint32_t a) { uint32_t v; asm volatile("ld.shared.u32 %0, [%1];" : "=r"(v) : "r"(a) : "memory"); return v; }
__device__ __forceinline__ void sts32(uint32_t a, uint32_t v) { asm volatile("st.shared.u32 [%0], %1;" :: "r"(a), "r"(v) : "memory"); }
__device__ __forceinline__ void sts16(uint32_t a, uint16_t v) { asm volatile("st.shared.u16 [%0], %1;" :: "r"(a), "h"(v) : "memory"); }
__device__ __forceinline__ void sts64(uint32_t a, uint32_t x, uint32_t y) { asm volatile("st.shared.v2.u32 [%0], {%1, %2};" :: "r"(a), "r"(x), "r"(y) : "memory"); }
__device__ __forceinline__ void sts128(uint32_t a, uint32_t x, uint32_t y, uint32_t z, uint32_t w) { asm volatile("st.shared.v4.u32 [%0], {%1, %2, %3, %4};" :: "r"(a), "r"(x), "r"(y), "r"(z), "r"(w) : "memory"); }
__device__ __forceinline__ uint2 lds64(uint32_t a) { uint2 v; asm volatile("ld.shared.v2.u32 {%0, %1}, [%2];" : "=r"(v.x), "=r"(v.y) : "r"(a) : "memory"); return v; }
__device__ __forceinline__ uint4 lds128(uint32_t a) { uint4 v; asm volatile("ld.shared.v4.u32 {%0, %1, %2, %3}, [%4];" : "=r"(v.x), "=r"(v.y), "=r"(v.z), "=r"(v.w) : "r"(a) : "memory"); return v; }
__device__ __forceinline__ float ex2f(float x) { float y; asm("ex2.approx.ftz.f32 %0, %1;" : "=f"(y) : "f"(x)); return y; }
__device__ __forceinline__ float rcpf(float x) { float y; asm("rcp.approx.ftz.f32 %0, %1;" : "=f"(y) : "f"(x)); return y; }
__device__ __forceinline__ void stsm4(uint32_t a, uint32_t x, uint32_t y, uint32_t z, uint32_t w) {
    asm volatile("stmatrix.sync.aligned.m8n8.x4.shared.b16 [%0], {%1, %2, %3, %4};" :: "r"(a), "r"(x), "r"(y), "r"(z), "r"(w) : "memory");
}
__device__ __forceinline__ uint32_t pack_bf16(float lo, float hi) { uint32_t r; asm("cvt.rn.bf16x2.f32 %0, %1, %2;" : "=r"(r) : "f"(hi), "f"(lo)); return r; }
__device__ __forceinline__ float bf_lo(uint32_t v) { return __uint_as_float(v << 16); }
__device__ __forceinline__ float bf_hi(uint32_t v) { return __uint_as_float(v & 0xFFFF0000u); }
__device__ __forceinline__ uint32_t phi2(float t0, float t1) {
    uint32_t r;
    asm("{\n.reg .b32 one, eps, p, e;\nmov.b32 one, 0x3F803F80;\nmov.b32 eps, 0x35863586;\n"
        "add.rn.bf16x2 p, %1, one;\nmin.bf16x2 e, %2, one;\nmax.NaN.bf16x2 p, p, e;\nadd.rn.bf16x2 %0, p, eps;\n}"
        : "=r"(r) : "r"(pack_bf16(t0, t1)), "r"(pack_bf16(ex2f(t0 * LOG2E), ex2f(t1 * LOG2E))));
    return r;
}
template <int MODE> __device__ __forceinline__ void stage_tile(uint32_t x, uint32_t step, const float (&a)[40]) {
#pragma unroll
    for (int k = 0; k < 5; k++) {
        uint32_t r[4];
#pragma unroll
        for (int e = 0; e < 4; e++) {
            const float t0 = a[8 * k + 2 * e], t1 = a[8 * k + 2 * e + 1];
            r[e] = MODE == 0 ? pack_bf16(t0, t1) : MODE == 1 ? pack_bf16(t0 * QSCALE, t1 * QSCALE) : phi2(t0, t1);
        }
        stsm4(x + 2 * k * step, r[0], r[1], r[2], r[3]);
    }
}

__device__ __forceinline__ uint32_t exp2_pair(float t0, float t1, uint32_t ca) {
    uint32_t y, u, g;
    asm("prmt.b32 %0, %1, %2, 0x6521;" : "=r"(y) : "r"(__float_as_uint(t0)), "r"(__float_as_uint(t1)));
    u = y & 0x007F007Fu;
    asm("{.reg .b32 c; mov.b32 c, 0xF963F963; fma.rn.f16x2 %0, %1, c, %2;}" : "=r"(g) : "r"(u), "r"(ca));
    asm("mul.rn.f16x2 %0, %1, %2;" : "=r"(g) : "r"(g), "r"(u));
    return y - g;
}

__device__ __forceinline__ uint64_t desc(uint32_t addr, uint32_t lbo, uint32_t hi) { return ((uint64_t)hi << 32) | ((addr >> 4) + dlo(lbo)); }
template <int J> __device__ __forceinline__ void exp_steps(const float (&s)[32], uint32_t (&p)[16], float (&o)[12], uint64_t& dv, uint32_t ca) {
    if constexpr (J < 4) {
#pragma unroll
        for (int g = 2 * J; g < 2 * J + 2; g++) {
            if ((MUFU_MASK >> g) & 1) {
                p[2 * g] = pack_bf16(ex2f(s[4 * g]), ex2f(s[4 * g + 1]));
                p[2 * g + 1] = pack_bf16(ex2f(s[4 * g + 2]), ex2f(s[4 * g + 3]));
            } else {
                p[2 * g] = exp2_pair(s[4 * g], s[4 * g + 1], ca);
                p[2 * g + 1] = exp2_pair(s[4 * g + 2], s[4 * g + 3], ca);
            }
        }
        WG_FENCE();
        wg_rs_n24_tb1_d(o, p[4 * J], p[4 * J + 1], p[4 * J + 2], p[4 * J + 3], dv);
        dv += 96;
        exp_steps<J + 1>(s, p, o, dv, ca);
    }
}

struct Ring { uint32_t slot, phase; };
__device__ __forceinline__ void next_stage(Ring& r) { if (++r.slot == 3) { r.slot = 0; r.phase ^= 1; } }

#define BUNR 4
template <bool FAST>
__device__ __forceinline__ void attend(uint32_t sb, uint32_t& slot, int pass, const uint32_t (&q)[6], float (&o)[12], uint32_t ca, uint32_t z0, uint32_t z1) {
    float m0 = -INFINITY, m1 = -INFINITY;
    constexpr int UNR = FAST ? BUNR : 1;
#pragma unroll 1
    for (int c = 0; c < 8; c++) {
        const uint32_t base = sb + OFF_RING + slot * RING_BYTES;
        uint64_t dk = desc(base, 128, 768 >> 4), dv = desc(base + 384, 768, 128 >> 4);
        uint32_t seen;
#pragma unroll UNR
        for (int b = 0; b < 4; b++) {
            float s[32];
            uint32_t p[16];
            WG_FENCE();
            wg_rs_n64_tb0_initd(s, q[0], q[1], q[2], q[3], dk);
            dk += 16;
            wg_rs_n64_tb0_d(s, q[4], q[5], z0, z1, dk);
            dk += 368;
            WG_COMMIT();
            if (UNR < 4 || b == 3) seen = lds32(sb + OFF_PUB);
            WG_WAIT(0);
            fence_regs(s);
            if constexpr (FAST) {
                exp_steps<0>(s, p, o, dv, ca);
            } else {
                fence_regs(o);
                float x0 = m0, x1 = m1;
#pragma unroll
                for (int g = 0; g < 8; g++) {
                    if (!((MUFU_MASK >> g) & 1)) {
#pragma unroll
                        for (int e = 0; e < 4; e++) s[4 * g + e] *= 2.f;
                    }
                    x0 = fmaxf(x0, fmaxf(s[4 * g], s[4 * g + 1]));
                    x1 = fmaxf(x1, fmaxf(s[4 * g + 2], s[4 * g + 3]));
                }
                x0 = fmaxf(x0, __shfl_xor_sync(~0u, x0, 1)); x0 = fmaxf(x0, __shfl_xor_sync(~0u, x0, 2));
                x1 = fmaxf(x1, __shfl_xor_sync(~0u, x1, 1)); x1 = fmaxf(x1, __shfl_xor_sync(~0u, x1, 2));
                const float a0 = ex2f(m0 - x0), a1 = ex2f(m1 - x1);
                m0 = x0; m1 = x1;
#pragma unroll
                for (int b = 0; b < 3; b++) { o[4 * b] *= a0; o[4 * b + 1] *= a0; o[4 * b + 2] *= a1; o[4 * b + 3] *= a1; }
#pragma unroll
                for (int g = 0; g < 8; g++) {
                    p[2 * g] = pack_bf16(ex2f(s[4 * g] - x0), ex2f(s[4 * g + 1] - x0));
                    p[2 * g + 1] = pack_bf16(ex2f(s[4 * g + 2] - x1), ex2f(s[4 * g + 3] - x1));
                }
            }
            if constexpr (!FAST) {
                WG_FENCE();
#pragma unroll
                for (int k = 0; k < 4; k++) { wg_rs_n24_tb1_d(o, p[4 * k], p[4 * k + 1], p[4 * k + 2], p[4 * k + 3], dv); dv += 96; }
            }
            WG_COMMIT();
            WG_WAIT(0);
            fence_regs(o);
        }
        if ((threadIdx.x & 31) == 0) mbar_arrive(sb + BAR_EMPTY_KV + slot * 8);
        slot = slot == 2 ? 0 : slot + 1;
        count_wait(sb + OFF_PUB, seen, min(pass * 8 + c + 2, 16));
    }
}

__device__ __forceinline__ void gemm_pass(uint32_t sb, int pass, float (&a)[40], float (&b)[40]) {
    zero_regs(a); zero_regs(b);
    const uint32_t n0 = __shfl_sync(~0u, pass, 0) * 10;
    uint32_t slot = n0 % 3, phase = (n0 / 3) & 1;
    const bool lead = (threadIdx.x & 31) == 0;
#pragma unroll 1
    for (int c = 0; c < 10; c++) {
        mbar_wait(sb + BAR_FULL_G + slot * 8, phase);
        const uint32_t st = sb + OFF_STAGE + slot * STAGE_BYTES;
        const uint64_t dx = desc(st, 16, SW128 | 64), dw = desc(st + 16384, 2048, SW32 | 16);
        WG_FENCE();
#pragma unroll
        for (int k = 0; k < 4; k++) {
            wg_ss_n80_ta0_tb1_d(a, dx + 2 * k, dw + 32 * k);
            wg_ss_n80_ta0_tb1_d(b, dx + 512 + 2 * k, dw + 32 * k);
        }
        WG_COMMIT();
        WG_WAIT(0);
        if (lead) mbar_arrive(sb + BAR_EMPTY_G + slot * 8);
        if (++slot == 3) { slot = 0; phase ^= 1; }
    }
    fence_regs(a); fence_regs(b);
}

__device__ __forceinline__ void gemm_half(uint32_t sb, float (&a)[40]) {
    zero_regs(a);
    const bool lead = (threadIdx.x & 31) == 0;
#pragma unroll 1
    for (int c = 0; c < 10; c++) {
        mbar_wait(sb + BAR_FULL_X + (c & 3) * 8, (c >> 2) & 1);
        const uint64_t dx = desc(sb + OFF_XA + (c & 3) * 8192, 16, SW128 | 64), dw = desc(sb + OFF_WA + c * 10240, 2048, SW32 | 16);
        WG_FENCE();
#pragma unroll
        for (int k = 0; k < 4; k++) wg_ss_n80_ta0_tb1_d(a, dx + 2 * k, dw + 32 * k);
        WG_COMMIT();
        WG_WAIT(1);
        if (c > 0 && lead) mbar_arrive(sb + BAR_EMPTY_X + ((c - 1) & 3) * 8);
    }
    WG_WAIT(0);
    fence_regs(a);
}

__device__ __forceinline__ void store_tile(__nv_bfloat16* dst, int pitch, const float (&a)[40]) {
#pragma unroll
    for (int b = 0; b < 10; b++) {
        *reinterpret_cast<uint32_t*>(dst + 8 * b) = pack_bf16(a[4 * b], a[4 * b + 1]);
        *reinterpret_cast<uint32_t*>(dst + 8 * pitch + 8 * b) = pack_bf16(a[4 * b + 2], a[4 * b + 3]);
    }
}

__device__ __forceinline__ void linear_out(uint32_t sb, int half, uint32_t dst, int q) {
    float d[44]; zero_regs(d);
    const uint64_t da = desc(sb + OFF_PK + half * 10240, 128, 80), db = desc(sb + OFF_KVB, 1408, 8);
    WG_FENCE();
#pragma unroll
    for (int k = 0; k < 5; k++) wg_ss_n88_ta0_tb1_d(d, da + 16 * k, db + 176 * k);
    WG_COMMIT();
    WG_WAIT(0);
    fence_regs(d);
    bar_sync(6, 128);
    float r0[4], r1[4];
    const int base = (threadIdx.x & 31) & ~3;
#pragma unroll
    for (int e = 0; e < 4; e++) d[40 + e] = rcpf(d[40 + e] + 1e-6f);
#pragma unroll
    for (int h = 0; h < 4; h++) {
        r0[h] = __shfl_sync(~0u, d[40 + (h & 1)], base + (h >> 1));
        r1[h] = __shfl_sync(~0u, d[42 + (h & 1)], base + (h >> 1));
    }
    uint32_t r[20];
#pragma unroll
    for (int b = 0; b < 10; b++) {
        const int hl = (8 * b) / 20, hh = (8 * b + 6) / 20;
        const bool up = hl != hh && q >= 2;
        const float s0 = up ? r0[hh] : r0[hl], s1 = up ? r1[hh] : r1[hl];
        r[2 * b] = pack_bf16(d[4 * b] * s0, d[4 * b + 1] * s0);
        r[2 * b + 1] = pack_bf16(d[4 * b + 2] * s1, d[4 * b + 3] * s1);
    }
#pragma unroll
    for (int k = 0; k < 5; k++) stsm4(dst + 32 * k, r[4 * k], r[4 * k + 1], r[4 * k + 2], r[4 * k + 3]);
}

__global__ void __launch_bounds__(NTHR, 1) fused_kernel(const __grid_constant__ Params P) {
    extern __shared__ __align__(1024) uint8_t smem[];
    const uint32_t sb = (uint32_t)__cvta_generic_to_shared(smem);
    const int tid = threadIdx.x, lane = tid & 31;
    const int wg = __shfl_sync(~0u, tid >> 7, 0), warp = __shfl_sync(~0u, (tid >> 5) & 3, 0);
    const int cta = blockIdx.x, i = cta >> 3, j = cta & 7;
    const int q = lane & 3, r0 = 16 * warp + (lane >> 2);
    if (wg == 4 || wg == 0) TS(wg == 4 ? 0 : 16);

    const uint32_t tag = *(volatile uint32_t*)&g_epoch + 1;

    if (cta >= NCTA) {
        if (tid < 64 && elect_one()) {
            const int jj = 2 * (cta - NCTA) + warp;
            const uint32_t buf = sb + warp * 102400, bar = sb + OFF_BAR + warp * 80;
#pragma unroll 1
            for (int s = 0; s < 10; s++) mbar_init(bar + s * 8, 1);
            asm volatile("fence.mbarrier_init.release.cluster;" ::: "memory");
            int lp = 0, lc = 0;
#pragma unroll 1
            for (int n = -8; n < 40; n++) {
                if (n >= 0) {
                    const int part = n / 10, c = n - 10 * part;
                    mbar_wait(bar + c * 8, part & 1);
                    bulk_store(g_wt + ((part * 8 + jj) * 10 + c) * 10240, buf + c * 10240, 10240);
                    bulk_commit();
                    if (c == 9) { bulk_wait(); st_flag(g_flag_w + part * 8 + jj, tag); }
                    else asm volatile("cp.async.bulk.wait_group.read 2;" ::: "memory");
                }
                if (lp < 4) {
                    mbar_expect(bar + lc * 8, 10240);
                    tma3d(buf + lc * 10240, lp < 2 ? &P.wqkv : lp == 2 ? &P.wob : &P.woa, 64 * lc, 5 * jj + (lp == 0 ? 80 : 0), bar + lc * 8);
                    if (++lc == 10) { lc = 0; lp++; }
                }
            }
        }
        return;
    }
    if (tid == 640) {
        mbar_init(sb + BAR_KVIN, 1);
        asm volatile("fence.mbarrier_init.release.cluster;" ::: "memory");
        mbar_expect(sb + BAR_KVIN, 51200 + 20480);
        tma3d(sb + OFF_X16, &P.xa16, 16 * cta, 0, sb + BAR_KVIN);
#pragma unroll
        for (int u = 0; u < 4; u++) {
            const int v = (u + cta) & 3;
            bulk1d(sb + OFF_WRAW + v * 12800, P.in[2 + (v >> 1)] + (v & 1) * 12800, 12800, sb + BAR_KVIN);
        }
    } else if (tid == 672) {
#pragma unroll
        for (int s = 0; s < 3; s++) {
            mbar_init(sb + BAR_FULL_G + s * 8, 2);
            mbar_init(sb + BAR_EMPTY_G + s * 8, 4);
            mbar_init(sb + BAR_FULL_KV + s * 8, 1);
            mbar_init(sb + BAR_EMPTY_KV + s * 8, 16);
        }
        mbar_init(sb + BAR_OA, 16);
        mbar_init(sb + BAR_OA + 8, 16);
        asm volatile("fence.mbarrier_init.release.cluster;" ::: "memory");
    } else if (tid == 704) {
        prefetch_map(&P.xa);
        prefetch_map(&P.wq);
        prefetch_l2(P.in[1] + cta * 6400, 6400);
        mbar_init(sb + BAR_WA, 1);
        mbar_init(sb + BAR_PART, 4);
        mbar_init(sb + BAR_KVB, 1);
        mbar_init(sb + BAR_OB, 4);
        sts32(sb + OFF_PUB, 0);
        sts128(sb + OFF_STAT + 16, 0x357F357Fu, 0u, 0u, 0u);
        asm volatile("fence.mbarrier_init.release.cluster;" ::: "memory");
    } else if (tid == 736) {
#pragma unroll
        for (int s = 0; s < 4; s++) { mbar_init(sb + BAR_FULL_X + s * 8, 1); mbar_init(sb + BAR_EMPTY_X + s * 8, 4); }
#pragma unroll
        for (int s = 0; s < 4; s++) sts128(sb + OFF_QUEUE + s * 16, 0u, 0u, 0u, 0u);
        mbar_init(sb + BAR_A0, 1);
        asm volatile("fence.mbarrier_init.release.cluster;" ::: "memory");
    }
    __syncthreads();

    if (wg == 5) {
        asm volatile("setmaxnreg.dec.sync.aligned.u32 32;");
        if (warp == 0) {
            if (elect_one()) {
                Ring r{0, 1};
#pragma unroll 1
                for (int pass = 0; pass < NPASS; pass++) {
                    const CUtensorMap* m = pass == 0 ? &P.xa : pass <= 3 ? &P.xb : &P.ob;
                    if (pass == 1) count_wait(sb + OFF_PUB, 0, HOLD);
                    if (pass == 4) {
                        mbar_wait(sb + BAR_OB, 0);
                        tma2d_store(&P.ob_st, 80 * j, 128 * i, sb + OFF_PK);
                        bulk_commit();
                        bulk_wait();
                        st_flag(g_flag_b2 + cta, tag);
                        poll8(g_flag_b2 + i * 8, tag);
                    }
#pragma unroll 1
                    for (int c = 0; c < 10; c++) {
                        if (pass == 3 && c == 3) {
                            mbar_wait(sb + BAR_PART, 0);
                            bulk_add_f32(g_part + j * 1920, sb + OFF_PST, 7680);
                            bulk_commit();
                        }
                        if (pass > 0 || c >= 3) mbar_wait(sb + BAR_EMPTY_G + r.slot * 8, r.phase);
                        mbar_expect(sb + BAR_FULL_G + r.slot * 8, 16384);
                        tma2d(sb + OFF_STAGE + r.slot * STAGE_BYTES, m, 64 * c, 128 * i, sb + BAR_FULL_G + r.slot * 8);
                        next_stage(r);
                        if (pass == 3 && c == 3) {
                            bulk_wait();
                            st_flag(g_flag_b1 + j * 16 + i, tag);
                        }
                    }
                }
                if (NPASS == 5) {
                    poll8(g_flag_a + i * 8, tag);
                    mbar_arrive(sb + BAR_A0);
#pragma unroll 1
                    for (int c = 0; c < 10; c++) {
                        const uint32_t s = c & 3;
                        if (c >= 4) mbar_wait(sb + BAR_EMPTY_X + s * 8, ((c >> 2) - 1) & 1);
                        mbar_expect(sb + BAR_FULL_X + s * 8, 8192);
                        tma2d(sb + OFF_XA + s * 8192, &P.oa, 64 * c, 128 * i, sb + BAR_FULL_X + s * 8);
                    }
                }
            }
        } else if (warp == 2) {
            if (elect_one()) {
                Ring r{0, 1};
#pragma unroll 1
                for (int pass = 0; pass < NPASS; pass++) {
                    const CUtensorMap* m = pass == 0 ? &P.wq : pass <= 3 ? &P.wqkv : &P.wob;
                    const int col = 5 * j + (pass == 1 ? 40 : pass == 2 ? 80 : 0);
                    if (pass == 1) count_wait(sb + OFF_PUB, 0, HOLD);
                    const bool pre = pass >= 2 && P.helpers;
                    if (pre) poll1(g_flag_w + (pass - 2) * 8 + j, tag);
#pragma unroll 1
                    for (int c = 0; c < 10; c++) {
                        if (pass > 0 || c >= 3) mbar_wait(sb + BAR_EMPTY_G + r.slot * 8, r.phase);
                        const uint32_t bar = sb + BAR_FULL_G + r.slot * 8;
                        mbar_expect(bar, 10240);
                        const uint32_t dst = sb + OFF_STAGE + r.slot * STAGE_BYTES + 16384;
                        if (pre) bulk1d(dst, g_wt + (((pass - 2) * 8 + j) * 10 + c) * 10240, 10240, bar);
                        else tma3d(dst, m, 64 * c, col, bar);
                        next_stage(r);
                    }
                }
                if (NPASS == 5) {
                    if (P.helpers) poll1(g_flag_w + 24 + j, tag);
#pragma unroll 1
                    for (int c = 0; c < 3; c++) { mbar_wait(sb + BAR_EMPTY_G + r.slot * 8, r.phase); next_stage(r); }
                    mbar_expect(sb + BAR_WA, 102400);
                    if (P.helpers) bulk1d(sb + OFF_WA, g_wt + (24 + j) * 102400, 102400, sb + BAR_WA);
                    else {
#pragma unroll 1
                        for (int c = 0; c < 10; c++) tma3d(sb + OFF_WA + c * 10240, &P.woa, 64 * c, 5 * j, sb + BAR_WA);
                    }
                }
            }
        } else if (warp == 3) {
            if (elect_one()) {
                mbar_wait(sb + BAR_FULL_G, 0);
                mbar_wait(sb + BAR_FULL_G, 1);
                mbar_wait(sb + BAR_FULL_G, 0);
                prefetch_l2(P.in[5] + cta * 20480, 20480);
#pragma unroll 1
                for (int u = 0; u < 5; u++) prefetch_l2(P.in[6] + (cta * 5 + u) * 3840 + 1280, 1280);
            }
            __syncwarp();
            if (NPASS == 5) {
                if (elect_one()) {
                    poll8(g_flag_b1 + j * 16, tag);
                    poll8(g_flag_b1 + j * 16 + 8, tag);
                    mbar_expect(sb + BAR_KVB, 7680);
                    bulk1d(sb + OFF_PST, g_part + j * 1920, 7680, sb + BAR_KVB);
                }
            }
            if (elect_one()) {
                mbar_wait(sb + BAR_OA, 0);
                tma2d_store(&P.oa_st, 80 * j, 128 * i, sb + OFF_Q);
                bulk_commit();
                bulk_wait();
                st_flag(g_flag_a + cta, tag);
            }
        } else if (warp == 1) {
            uint32_t sk, sv, spin = 0;
            bar_sync(12, 64);
#pragma unroll 1
            while (true) {
                const uint4 f = ld_relaxed128(g_flag_kv + 2 * lane), g = ld_relaxed128(g_flag_kv + 2 * lane + 64);
                const bool ok = f.y == tag && f.w == tag && g.y == tag && g.w == tag;
                sk = max(max(f.x >> 16, f.z >> 16), max(g.x >> 16, g.z >> 16));
                sv = max(max(f.x & 0xFFFFu, f.z & 0xFFFFu), max(g.x & 0xFFFFu, g.z & 0xFFFFu));
                if (__all_sync(~0u, ok) || ++spin > (1u << 17)) break;
            }
            asm volatile("fence.acq_rel.cta;" ::: "memory");
            sk = __reduce_max_sync(~0u, sk);
            sv = __reduce_max_sync(~0u, sv);
            if (elect_one()) {
                const bool vok = sv == 0 || (sv >= ((127 - 40) << 7) && sv <= ((127 + 40) << 7));
                sts32(sb + OFF_STAT, vok ? sk << 16 : 0x7FC00000u);
                fence_async();
#pragma unroll 1
                for (int n = 0; n < 3; n++) {
                    mbar_expect(sb + BAR_FULL_KV + n * 8, RING_BYTES);
                    bulk1d(sb + OFF_RING + n * RING_BYTES, g_kv + n * RING_BYTES, RING_BYTES, sb + BAR_FULL_KV + n * 8);
                }
                Ring r{0, 0};
#pragma unroll 1
                for (int n = 0; n < 16; n++) {
                    if (n >= 3) {
                        mbar_wait(sb + BAR_EMPTY_KV + r.slot * 8, r.phase ^ 1);
                        mbar_expect(sb + BAR_FULL_KV + r.slot * 8, RING_BYTES);
                        bulk1d(sb + OFF_RING + r.slot * RING_BYTES, g_kv + (n & 7) * RING_BYTES, RING_BYTES, sb + BAR_FULL_KV + r.slot * 8);
                    }
                    mbar_wait(sb + BAR_FULL_KV + r.slot * 8, r.phase);
                    asm volatile("st.release.cta.shared::cta.u32 [%0], %1;" :: "r"(sb + OFF_PUB), "r"(n + 1) : "memory");
                    next_stage(r);
                }
            }
        }
    } else if (wg < 4) {
        {
            if (tid < 30) reinterpret_cast<uint4*>(g_part + j * 1920 + i * 120)[tid] = make_uint4(0u, 0u, 0u, 0u);
            const int k = tid / 5, m0 = 4 * (tid - 5 * k), m1 = m0 + 20;
            const uint32_t row = sb + OFF_WKV + (k >> 3) * 880 + (k & 7) * 16;
            const uint32_t a0 = row + (m0 >> 3) * 176 + (m0 & 7) * 2, a1 = row + (m1 >> 3) * 176 + (m1 & 7) * 2;
            mbar_wait(sb + BAR_KVIN, 0);
            if (wg == 0) TS(13);
            uint2 w[14];
#pragma unroll
            for (int n = 0; n < 7; n++) if (tid < (n < 6 ? 480 : 320)) { w[2 * n] = lds64(sb + OFF_WRAW + tid * 8 + n * 3840); w[2 * n + 1] = lds64(sb + OFF_WRAW + 25600 + tid * 8 + n * 3840); }
#pragma unroll
            for (int n = 0; n < 7; n++) if (tid < (n < 6 ? 480 : 320)) { sts64(a0 + n * 10560, w[2 * n].x, w[2 * n].y); sts64(a1 + n * 10560, w[2 * n + 1].x, w[2 * n + 1].y); }
        }
        fence_async_smem();
        bar_sync(1, 512);
        if (wg == 0) {
            TS(14);
            float d[8];
            const uint64_t da = desc(sb + OFF_WKV, 880, 11), db = desc(sb + OFF_X16, 16, SW128 | 64);
            WG_FENCE();
            wg_ss_n16_ta1_tb0_initd(d, da, db);
#pragma unroll
            for (int k = 1; k < 40; k++) wg_ss_n16_ta1_tb0_d(d, da + 110 * k, db + (k >> 2) * 128 + (k & 3) * 2);
            WG_COMMIT();
            if (tid < 16) {
                const int g = tid >> 3;
                const bool mu = (MUFU_MASK >> ((2 * cta + g) & 7)) & 1;
                const uint32_t a = sb + OFF_IMG + g * 768 + (tid & 7) * 16 + 8;
                sts64(a + 256, mu ? 0u : 0x3F00433Fu, mu ? 0u : 0x00003B4Au);
                sts64(a + 640, 0x00003F80u, 0u);
            }
            WG_WAIT(0);
            fence_regs(d);
            bar_arrive(2, 256);
            TS(15);
#pragma unroll
            for (int hh = 0; hh < 2; hh++) {
                const int m = r0 + 8 * hh;
                if (m < 40) {
                    const int isv = m >= 20, dd = m - 20 * isv;
#pragma unroll
                    for (int g = 0; g < 2; g++) {
                        const bool mu = (MUFU_MASK >> ((2 * cta + g) & 7)) & 1;
                        const float sc = (isv || mu) ? 1.f : 0.5f;
                        const uint32_t pr = pack_bf16(d[4 * g + 2 * hh] * sc, d[4 * g + 2 * hh + 1] * sc);
                        const uint32_t a = sb + OFF_IMG + g * 768 + (3 * isv + (dd >> 3)) * 128 + (dd & 7) * 2 + 2 * q * 16;
                        sts16(a, (uint16_t)pr);
                        sts16(a + 16, (uint16_t)(pr >> 16));
                    }
                }
            }
            bar_sync(3, 128);
            if (warp == 0) {
#pragma unroll
                for (int u = 0; u < 3; u++) {
                    const uint4 v = lds128(sb + OFF_IMG + (lane + 32 * u) * 16);
                    *reinterpret_cast<uint4*>(g_kv + cta * 1536 + (lane + 32 * u) * 16) = v;
                }
                const int key = lane & 15, g = key >> 3;
                const uint32_t a = sb + OFF_IMG + g * 768 + (lane >> 4) * 384 + (key & 7) * 16;
                const uint4 w0 = lds128(a), w1 = lds128(a + 128);
                const uint2 w2 = lds64(a + 256);
                const uint32_t w[10] = {w0.x, w0.y, w0.z, w0.w, w1.x, w1.y, w1.z, w1.w, w2.x, w2.y};
                float n2 = 0.f;
                uint32_t mx = 0;
#pragma unroll
                for (int e = 0; e < 10; e++) {
                    n2 = fmaf(bf_lo(w[e]), bf_lo(w[e]), n2);
                    n2 = fmaf(bf_hi(w[e]), bf_hi(w[e]), n2);
                    mx = max(mx, max(w[e] & 0x7FFFu, (w[e] >> 16) & 0x7FFFu));
                }
                if (!((MUFU_MASK >> ((2 * cta + g) & 7)) & 1)) n2 *= 4.f;
                uint32_t st = lane < 16 ? min(((__float_as_uint(n2) & 0x7FFFFFFFu) + 0xFFFFu) >> 16, 0x7FFFu) : mx;
#pragma unroll
                for (int x = 1; x < 16; x <<= 1) st = max(st, __shfl_xor_sync(~0u, st, x));
                const uint32_t sv = __shfl_sync(~0u, st, 16);
                __syncwarp();
                if (lane == 0) {
                    const unsigned long long f = ((unsigned long long)tag << 32) | (st << 16) | sv;
                    asm volatile("st.release.gpu.global.u64 [%0], %1;" :: "l"(g_flag_kv + cta), "l"(f) : "memory");
                }
                __syncwarp();
                bar_arrive(12, 64);
            }
            TS(17);
        }
        bar_sync(4, 640);
        uint32_t slot = 0;
        const uint4 cz = lds128(sb + OFF_STAT + 16);
#pragma unroll 1
        for (int pass = 0; pass < 2; pass++) {
            uint32_t qf[6];
            const uint32_t qa = sb + OFF_Q + pass * 10240 + r0 * 160 + wg * 40 + q * 4;
            qf[0] = lds32(qa); qf[1] = lds32(qa + 8 * 160);
            qf[2] = lds32(qa + 16); qf[3] = lds32(qa + 8 * 160 + 16);
            qf[4] = q < 2 ? lds32(qa + 32) : 0u; qf[5] = q < 2 ? lds32(qa + 8 * 160 + 32) : 0u;
            if (pass == 0) { count_wait(sb + OFF_PUB, 0, 1); if (wg == 0) { TS(19); TC(26); } }
            float n0 = 0.f, n1 = 0.f;
#pragma unroll
            for (int e = 0; e < 3; e++) {
                n0 = fmaf(bf_lo(qf[2 * e]), bf_lo(qf[2 * e]), fmaf(bf_hi(qf[2 * e]), bf_hi(qf[2 * e]), n0));
                n1 = fmaf(bf_lo(qf[2 * e + 1]), bf_lo(qf[2 * e + 1]), fmaf(bf_hi(qf[2 * e + 1]), bf_hi(qf[2 * e + 1]), n1));
            }
            n0 += __shfl_xor_sync(~0u, n0, 1); n0 += __shfl_xor_sync(~0u, n0, 2);
            n1 += __shfl_xor_sync(~0u, n1, 1); n1 += __shfl_xor_sync(~0u, n1, 2);
            const float k2 = __uint_as_float(lds32(sb + OFF_STAT));
            const uint32_t bad = !(n0 * k2 <= 4000.f && n1 * k2 <= 4000.f);
            uint32_t anybad;
            asm volatile("{\n.reg .pred p, r;\nsetp.ne.u32 p, %1, 0;\nbar.red.or.pred r, %2, 128, p;\nselp.u32 %0, 1, 0, r;\n}" : "=r"(anybad) : "r"(bad), "r"(8 + wg) : "memory");
            float o[12];
#pragma unroll
            for (int k = 0; k < 12; k++) o[k] = 0.f;
            fence_regs(o);
            if (!__shfl_sync(~0u, anybad, 0)) {
                if (q >= 2) qf[4] = qf[5] = q == 2 ? 0x3F803F80u : 0x00003F80u;
                attend<true>(sb, slot, pass, qf, o, cz.x, cz.y, cz.z);
            } else {
                attend<false>(sb, slot, pass, qf, o, cz.x, cz.y, cz.z);
            }
            const float i0 = rcpf(__shfl_sync(~0u, o[8], (lane & ~3) | 2)), i1 = rcpf(__shfl_sync(~0u, o[10], (lane & ~3) | 2));
            const uint32_t ot = opaque_tid(), ol = ot & 31, oq = ot & 3;
            uint8_t* const gx = g_ox + opaque_cta() * 10240;
#pragma unroll
            for (int b = 0; b < 3; b++) {
                if (b < 2 || oq < 2) {
                    const uint32_t v0 = pack_bf16(o[4 * b] * i0, o[4 * b + 1] * i0), v1 = pack_bf16(o[4 * b + 2] * i1, o[4 * b + 3] * i1);
                    const uint32_t col = 20 * (ot >> 7) + 8 * b + 2 * oq;
                    const uint32_t x = (col >> 4) * 2048 + (ot & 96) * 16 + (col & 8) * 16 + (ol >> 2) * 16 + (col & 7) * 2;
                    st_relaxed(gx + x, pass ? v0 : ~0u);
                    st_relaxed(gx + x + 256, pass ? v1 : ~0u);
                    const uint32_t dst = sb + OFF_Q + (pass ? 10240 + x : (((ot & 96) >> 1) + (ol >> 2)) * 160 + col * 2);
                    sts32(dst, v0);
                    sts32(dst + (pass ? 256 : 8 * 160), v1);
                }
            }
            fence_async_smem();
            __syncwarp();
            if (lane == 0) mbar_arrive(sb + BAR_OA + pass * 8);
            if (wg == 0) { TS(20 + pass); TC(27 + pass); }
        }
        TS(22 + wg);
        if (NPASS == 5) {
            const uint32_t ot = opaque_tid(), oc = opaque_cta();
            const int lane = ot & 31, i = oc >> 3, j = oc & 7;
            if (wg != 0) {
                const int u = 4 * (wg - 1) + warp;
                uint4 v[12];
                const uint8_t* src[3];
#pragma unroll
                for (int t = 0; t < 3; t++) {
                    const int g = 5 * j + 5 + 3 * u + t;
                    src[t] = g_ox + (i * 40 + (g >= 40 ? g - 40 : g)) * 2048 + lane * 16;
                }
#pragma unroll
                for (int k = 0; k < 12; k++) v[k] = make_uint4(k >= 8 && u == 11 ? 0u : ~0u, 0u, 0u, 0u);
                mbar_wait(sb + BAR_A0, 0);
#pragma unroll 1
                for (uint32_t spin = 0; spin < (1u << 16); spin++) {
#pragma unroll
                    for (int k = 0; k < 12; k++) if (v[k].x == ~0u) v[k] = ld_relaxed128(src[k >> 2] + (k & 3) * 512);
                    bool ok = true;
#pragma unroll
                    for (int k = 0; k < 12; k++) {
                        if (v[k].y == ~0u || v[k].z == ~0u || v[k].w == ~0u) v[k].x = ~0u;
                        ok = ok && v[k].x != ~0u;
                    }
                    if (__all_sync(~0u, ok)) break;
                }
                mbar_wait(sb + BAR_OA + 8, 0);
#pragma unroll
                for (int k = 0; k < 12; k++) sts128(sb + OFF_RING + u * 6144 + k * 512 + lane * 16, v[k].x, v[k].y, v[k].z, v[k].w);
                fence_async_smem();
                __syncwarp();
                if (lane == 0) {
                    uint32_t n;
                    asm volatile("atom.relaxed.cta.shared::cta.add.u32 %0, [%1], 1;" : "=r"(n) : "r"(sb + OFF_QUEUE + 48) : "memory");
                    asm volatile("st.release.cta.shared::cta.u32 [%0], %1;" :: "r"(sb + OFF_QUEUE + n * 4), "r"(u + 1) : "memory");
                }
                if (wg == 1) TS(10);
            } else {
                float a[40];
                mbar_wait(sb + BAR_WA, 0);
                mbar_wait(sb + BAR_OA + 8, 0);
                TS(30);
                const uint64_t dw = desc(sb + OFF_WA, 2048, SW32 | 16);
                {
                    const uint64_t da = desc(sb + OFF_Q + 10240, 128, 16);
                    WG_FENCE();
#pragma unroll
                    for (int t = 0; t < 5; t++) {
                        const uint32_t g = 5 * j + t;
                        if (t == 0) wg_ss_n80_ta0_tb1_initd(a, da, dw + (g >> 2) * 640 + (g & 3) * 32);
                        else wg_ss_n80_ta0_tb1_d(a, da + 128 * t, dw + (g >> 2) * 640 + (g & 3) * 32);
                    }
                    WG_COMMIT();
                }
#pragma unroll 1
                for (int n = 0; n < 12; n++) {
                    const uint32_t u = __shfl_sync(~0u, queue_wait(sb + OFF_QUEUE + n * 4), 0) - 1;
                    const uint64_t da = desc(sb + OFF_RING + u * 6144, 128, 16);
                    WG_FENCE();
#pragma unroll
                    for (int t = 0; t < 3; t++) {
                        uint32_t g = 5 * j + 5 + 3 * u + t;
                        if (g >= 40) g -= 40;
                        wg_ss_n80_ta0_tb1_d(a, da + 128 * t, dw + (g >> 2) * 640 + (g & 3) * 32);
                    }
                    WG_COMMIT();
                }
                WG_WAIT(0);
                fence_regs(a);
                store_tile(P.out + (128 * i + 64 + (ot >> 5) * 16 + (lane >> 2)) * 1280 + 80 * j + 2 * (lane & 3), 1280, a);
                TS(11);
            }
        }
    } else {
        asm volatile("setmaxnreg.inc.sync.aligned.u32 128;");
        const uint32_t mrow = 16 * warp + (lane & 15), mcol = lane >> 4;
        const uint32_t xrow = mrow * 160 + mcol * 16, xgrp = (mrow & 7) * 16 + mcol * 128;
#pragma unroll 1
        for (int pass = 0; pass < NPASS; pass++) {
        if (pass == 4) {
        mbar_wait(sb + BAR_KVB, 0);
        TS(7);
        if (tid < 592) {
            const int m = tid - 512, h = m / 20;
            const uint32_t x0 = sb + OFF_KVB + (m >> 3) * 1408 + (m & 7) * 16;
#pragma unroll
            for (int e = 0; e < 5; e++) {
                const uint4 v = lds128(sb + OFF_PST + m * 96 + e * 16);
                const int n = 20 * h + 4 * e;
                sts64(x0 + (n >> 3) * 128 + (n & 4) * 2, pack_bf16(__uint_as_float(v.x), __uint_as_float(v.y)), pack_bf16(__uint_as_float(v.z), __uint_as_float(v.w)));
            }
            sts16(x0 + 1280 + h * 2, (uint16_t)pack_bf16(__uint_as_float(lds32(sb + OFF_PST + m * 96 + 80)), 0.f));
        }
        fence_async_smem();
        bar_sync(6, 128);
#pragma unroll 1
        for (int half = 0; half < 2; half++) linear_out(sb, half, sb + OFF_PK + half * 10240 + xrow, q);
        fence_async_smem();
        __syncwarp();
        if (lane == 0) mbar_arrive(sb + BAR_OB);
        }
        float a[40], b[40];
        gemm_pass(sb, pass, a, b);
        if (pass == 0) {
        TS(1);
        bar_sync(2, 256);
        stage_tile<1>(sb + OFF_Q + xrow, 16, a);
        stage_tile<1>(sb + OFF_Q + 10240 + xrow, 16, b);
        bar_arrive(4, 640);
        TS(2);
        } else if (pass == 1 || pass == 3) {
        TS(pass == 1 ? 3 : 6);
        stage_tile<2>(sb + OFF_PK + (mrow >> 3) * 1280 + xgrp, 128, a);
        stage_tile<2>(sb + OFF_PK + (8 + (mrow >> 3)) * 1280 + xgrp, 128, b);
        } else if (pass == 2) {
        TS(4);
        stage_tile<0>(sb + OFF_V + 128 + (mrow >> 3) * 1536 + xgrp, 128, a);
        stage_tile<0>(sb + OFF_V + 128 + (8 + (mrow >> 3)) * 1536 + xgrp, 128, b);
        {
            const uint32_t x = sb + OFF_V + ((tid - 512) >> 3) * 1536 + (tid & 7) * 16;
            sts128(x, 0x3F80u, 0u, 0u, 0u);
            sts128(x + 11 * 128, 0x3F80u, 0u, 0u, 0u);
        }
        fence_async_smem();
        bar_sync(6, 128);
        {
            float d1[36], d2[16]; zero_regs(d1); zero_regs(d2);
            const uint64_t da = desc(sb + OFF_PK, 1280, 8), db = desc(sb + OFF_V, 1536, 8);
            WG_FENCE();
#pragma unroll
            for (int k = 0; k < 8; k++) {
                wg_ss_n72_ta1_tb1_d(d1, da + 160 * k, db + 192 * k);
                wg_ss_n32_ta1_tb1_d(d2, da + 16 + 160 * k, db + 64 + 192 * k);
            }
            WG_COMMIT();
            WG_WAIT(0);
            fence_regs(d1); fence_regs(d2);
            bar_sync(6, 128);
#pragma unroll
            for (int u = 0; u < 7; u++) if (u < 6 || tid < 624) sts128(sb + OFF_KVB + (tid - 512 + 128 * u) * 16, 0u, 0u, 0u, 0u);
            const uint32_t part = sb + OFF_PST;
#pragma unroll
            for (int hh = 0; hh < 2; hh++) {
                const int m = r0 + 8 * hh;
                if (m < 60) {
                    const int h20 = (m / 20) * 20;
                    if (q == 0) sts128(part + m * 96 + 80, __float_as_uint(d1[2 * hh]), 0u, 0u, 0u);
#pragma unroll
                    for (int k = 1; k < 9; k++) {
                        const int e = 8 * (k - 1) + 2 * q - h20;
                        if (e >= 0 && e < 20) sts64(part + m * 96 + e * 4, __float_as_uint(d1[4 * k + 2 * hh]), __float_as_uint(d1[4 * k + 2 * hh + 1]));
                    }
                }
                if (m >= 44) {
                    if (q == 0) sts128(part + (m + 16) * 96 + 80, __float_as_uint(d2[12 + 2 * hh]), 0u, 0u, 0u);
#pragma unroll
                    for (int k = 0; k < 3; k++) {
                        const int e = 8 * k + 2 * q - 4;
                        if (e >= 0) sts64(part + (m + 16) * 96 + e * 4, __float_as_uint(d2[4 * k + 2 * hh]), __float_as_uint(d2[4 * k + 2 * hh + 1]));
                    }
                }
            }
            fence_async_smem();
            __syncwarp();
            if (lane == 0) mbar_arrive(sb + BAR_PART);
        }
        } else {
        __nv_bfloat16* out = P.out + (128 * i + r0) * 1280 + 80 * j + 2 * q + 640;
        store_tile(out, 1280, a);
        store_tile(out + 64 * 1280, 1280, b);
        TS(9);
        }
        }
        if (NPASS == 5) {
            mbar_wait(sb + BAR_WA, 0);
            float a[40];
            gemm_half(sb, a);
            store_tile(P.out + (128 * i + r0) * 1280 + 80 * j + 2 * q, 1280, a);
            TS(12);
        }
        if (cta == 0 && tid == 512) *(volatile uint32_t*)&g_epoch = tag;
    }
}

typedef CUresult (*EncodeFn)(CUtensorMap*, CUtensorMapDataType, cuuint32_t, void*, const cuuint64_t*, const cuuint64_t*,
                             const cuuint32_t*, const cuuint32_t*, CUtensorMapInterleave, CUtensorMapSwizzle,
                             CUtensorMapL2promotion, CUtensorMapFloatOOBfill);

void make_map(EncodeFn enc, CUtensorMap* m, const void* p, uint32_t box_cols, uint32_t box_rows) {
    cuuint64_t dims[2] = {640, 2048}, strides[1] = {1280};
    cuuint32_t box[2] = {box_cols, box_rows}, es[2] = {1, 1};
    enc(m, CU_TENSOR_MAP_DATA_TYPE_BFLOAT16, 2, const_cast<void*>(p), dims, strides, box, es, CU_TENSOR_MAP_INTERLEAVE_NONE,
        box_cols == 64 ? CU_TENSOR_MAP_SWIZZLE_128B : CU_TENSOR_MAP_SWIZZLE_NONE, CU_TENSOR_MAP_L2_PROMOTION_L2_128B, CU_TENSOR_MAP_FLOAT_OOB_FILL_NONE);
}
void make_x16map(EncodeFn enc, CUtensorMap* m, const void* p) {
    cuuint64_t dims[3] = {64, 2048, 10}, strides[2] = {1280, 128};
    cuuint32_t box[3] = {64, 16, 10}, es[3] = {1, 1, 1};
    enc(m, CU_TENSOR_MAP_DATA_TYPE_BFLOAT16, 3, const_cast<void*>(p), dims, strides, box, es, CU_TENSOR_MAP_INTERLEAVE_NONE,
        CU_TENSOR_MAP_SWIZZLE_128B, CU_TENSOR_MAP_L2_PROMOTION_L2_128B, CU_TENSOR_MAP_FLOAT_OOB_FILL_NONE);
}
void make_wmap(EncodeFn enc, CUtensorMap* m, const void* p, uint64_t cols) {
    cuuint64_t dims[3] = {16, 640, cols / 16}, strides[2] = {cols * 2, 32};
    cuuint32_t box[3] = {16, 64, 5}, es[3] = {1, 1, 1};
    enc(m, CU_TENSOR_MAP_DATA_TYPE_BFLOAT16, 3, const_cast<void*>(p), dims, strides, box, es, CU_TENSOR_MAP_INTERLEAVE_NONE,
        CU_TENSOR_MAP_SWIZZLE_32B, CU_TENSOR_MAP_L2_PROMOTION_L2_128B, CU_TENSOR_MAP_FLOAT_OOB_FILL_NONE);
}

}

extern "C" void kernel_launch(void* const* d_in, const int* in_sizes, int n_in, void* d_out, int out_size) {
    static EncodeFn enc = nullptr;
    static void *oa = nullptr, *ob = nullptr;
    static int sms = 0;
    if (!enc) {
        void* fn = nullptr;
        cudaDriverEntryPointQueryResult qr;
        cudaGetDriverEntryPoint("cuTensorMapEncodeTiled", &fn, cudaEnableDefault, &qr);
        enc = (EncodeFn)fn;
        int dev = 0;
        cudaGetDevice(&dev);
        cudaDeviceGetAttribute(&sms, cudaDevAttrMultiProcessorCount, dev);
        cudaGetSymbolAddress(&oa, g_oa);
        cudaGetSymbolAddress(&ob, g_ob);
        cudaFuncSetAttribute(fused_kernel, cudaFuncAttributeMaxDynamicSharedMemorySize, SMEM_BYTES);
    }
    Params P;
    make_map(enc, &P.xa, d_in[0], 64, 128);
    make_x16map(enc, &P.xa16, d_in[0]);
    make_map(enc, &P.xb, d_in[5], 64, 128);
    make_wmap(enc, &P.wq, d_in[1], 640);
    make_wmap(enc, &P.wqkv, d_in[6], 1920);
    make_wmap(enc, &P.woa, d_in[4], 640);
    make_wmap(enc, &P.wob, d_in[7], 640);
    make_map(enc, &P.oa, oa, 64, 64);
    make_map(enc, &P.ob, ob, 64, 128);
    make_map(enc, &P.oa_st, oa, 80, 64);
    make_map(enc, &P.ob_st, ob, 80, 128);
    for (int k = 0; k < 8; k++) P.in[k] = (const uint8_t*)d_in[k];
    P.out = (__nv_bfloat16*)d_out;
    P.helpers = sms >= NCTA + 4;
    fused_kernel<<<P.helpers ? NCTA + 4 : NCTA, NTHR, SMEM_BYTES, cudaStreamPerThread>>>(P);
}
```

```cpp
#include <cuda_runtime.h>
#include <cuda_bf16.h>
#include <cuda.h>
#include <stdint.h>

namespace {

constexpr int NCTA = 128;
constexpr int NTHR = 768;

constexpr uint32_t OFF_STAGE = 0;
constexpr uint32_t STAGE_BYTES = 26624;
constexpr uint32_t OFF_PK = 79872;
constexpr uint32_t OFF_WRAW = OFF_PK;
constexpr uint32_t OFF_V = 100352;
constexpr uint32_t OFF_KVB = OFF_V;
constexpr uint32_t OFF_PST = OFF_V + 14336;
constexpr uint32_t OFF_WA = 0;
constexpr uint32_t OFF_XA = 102400;
constexpr uint32_t OFF_RING = 135168;
constexpr uint32_t RING_BYTES = 24576;
constexpr uint32_t OFF_WKV = OFF_RING;
constexpr uint32_t OFF_Q = 208896;
constexpr uint32_t OFF_X16 = OFF_Q;
constexpr uint32_t OFF_MISC = 229376;
constexpr uint32_t OFF_BAR = OFF_MISC;
constexpr uint32_t BAR_FULL_G = OFF_BAR, BAR_EMPTY_G = OFF_BAR + 24, BAR_FULL_KV = OFF_BAR + 48, BAR_EMPTY_KV = OFF_BAR + 72;
constexpr uint32_t BAR_OA = OFF_BAR + 96, BAR_WA = OFF_BAR + 112, BAR_FULL_X = OFF_BAR + 120, BAR_EMPTY_X = OFF_BAR + 152, BAR_A0 = OFF_BAR + 184;
constexpr uint32_t OFF_QUEUE = OFF_BAR + 192;
constexpr uint32_t BAR_PART = OFF_BAR + 264, BAR_KVB = OFF_BAR + 272, BAR_OB = OFF_BAR + 280, BAR_KVIN = OFF_BAR + 288;
constexpr uint32_t OFF_PUB = OFF_BAR + 296;
constexpr uint32_t OFF_STAT = OFF_BAR + 304;
constexpr uint32_t OFF_IMG = OFF_MISC + 384;
constexpr uint32_t OFF_TS = OFF_IMG + 1536;
constexpr uint32_t SMEM_BYTES = OFF_TS + 256;

#define MUFU_MASK 0x4A

#define TAILM 1
#define PFS 3
#define HOLD 2
#define NPASS 5
constexpr float LOG2E = 1.4426950408889634f;
constexpr float QSCALE = 0.22360679774997896f * LOG2E;

struct Params {
    CUtensorMap xa, xa16, wq, xb, wqkv, woa, wob, oa, ob, oa_st, ob_st;
    const uint8_t* in[8];
    __nv_bfloat16* out;
    int helpers;
};

}

__device__ __align__(1024) uint8_t g_kv[256 * 768];
__device__ __align__(1024) __nv_bfloat16 g_oa[2048 * 640];
__device__ __align__(1024) __nv_bfloat16 g_ob[2048 * 640];
__device__ __align__(1024) uint8_t g_ox[16 * 40 * 2048];
__device__ __align__(128) float g_part[8 * 1920];
__device__ __align__(128) unsigned long long g_flag_kv[128];
__device__ __align__(128) uint16_t g_flag_b1[128];
__device__ __align__(128) uint16_t g_flag_b2[128];
__device__ __align__(128) uint16_t g_flag_a[128];
__device__ __align__(128) uint16_t g_flag_w[32];
__device__ __align__(1024) uint8_t g_wt[320 * 10240];
__device__ uint32_t g_epoch;
#define TS(k)
#define TC(k)

namespace {

__device__ __forceinline__ void wg_rs_n24_tb1_d(float (&d)[12], uint32_t a0, uint32_t a1, uint32_t a2, uint32_t a3, uint64_t db) {
    asm volatile("{\n.reg .pred p;\nsetp.ne.b32 p, 1, 0;\n"
        "wgmma.mma_async.sync.aligned.m64n24k16.f32.bf16.bf16 {%0, %1, %2, %3, %4, %5, %6, %7, %8, %9, %10, %11}, {%12, %13, %14, %15}, %16, p, 1, 1, 1;\n}\n"
        : "+f"(d[0]), "+f"(d[1]), "+f"(d[2]), "+f"(d[3]), "+f"(d[4]), "+f"(d[5]), "+f"(d[6]), "+f"(d[7]), "+f"(d[8]), "+f"(d[9]), "+f"(d[10]), "+f"(d[11])
        : "r"(a0), "r"(a1), "r"(a2), "r"(a3), "l"(db));
}
__device__ __forceinline__ void wg_rs_n64_tb0_d(float (&d)[32], uint32_t a0, uint32_t a1, uint32_t a2, uint32_t a3, uint64_t db) {
    asm volatile("{\n.reg .pred p;\nsetp.ne.b32 p, 1, 0;\n"
        "wgmma.mma_async.sync.aligned.m64n64k16.f32.bf16.bf16 {%0, %1, %2, %3, %4, %5, %6, %7, %8, %9, %10, %11, %12, %13, %14, %15, %16, %17, %18, %19, %20, %21, %22, %23, %24, %25, %26, %27, %28, %29, %30, %31}, {%32, %33, %34, %35}, %36, p, 1, 1, 0;\n}\n"
        : "+f"(d[0]), "+f"(d[1]), "+f"(d[2]), "+f"(d[3]), "+f"(d[4]), "+f"(d[5]), "+f"(d[6]), "+f"(d[7]), "+f"(d[8]), "+f"(d[9]), "+f"(d[10]), "+f"(d[11]), "+f"(d[12]), "+f"(d[13]), "+f"(d[14]), "+f"(d[15]), "+f"(d[16]), "+f"(d[17]), "+f"(d[18]), "+f"(d[19]), "+f"(d[20]), "+f"(d[21]), "+f"(d[22]), "+f"(d[23]), "+f"(d[24]), "+f"(d[25]), "+f"(d[26]), "+f"(d[27]), "+f"(d[28]), "+f"(d[29]), "+f"(d[30]), "+f"(d[31])
        : "r"(a0), "r"(a1), "r"(a2), "r"(a3), "l"(db));
}
__device__ __forceinline__ void wg_rs_n64_tb0_initd(float (&d)[32], uint32_t a0, uint32_t a1, uint32_t a2, uint32_t a3, uint64_t db) {
    asm volatile("{\n.reg .pred p;\nsetp.ne.b32 p, 0, 0;\n"
        "wgmma.mma_async.sync.aligned.m64n64k16.f32.bf16.bf16 {%0, %1, %2, %3, %4, %5, %6, %7, %8, %9, %10, %11, %12, %13, %14, %15, %16, %17, %18, %19, %20, %21, %22, %23, %24, %25, %26, %27, %28, %29, %30, %31}, {%32, %33, %34, %35}, %36, p, 1, 1, 0;\n}\n"
        : "=f"(d[0]), "=f"(d[1]), "=f"(d[2]), "=f"(d[3]), "=f"(d[4]), "=f"(d[5]), "=f"(d[6]), "=f"(d[7]), "=f"(d[8]), "=f"(d[9]), "=f"(d[10]), "=f"(d[11]), "=f"(d[12]), "=f"(d[13]), "=f"(d[14]), "=f"(d[15]), "=f"(d[16]), "=f"(d[17]), "=f"(d[18]), "=f"(d[19]), "=f"(d[20]), "=f"(d[21]), "=f"(d[22]), "=f"(d[23]), "=f"(d[24]), "=f"(d[25]), "=f"(d[26]), "=f"(d[27]), "=f"(d[28]), "=f"(d[29]), "=f"(d[30]), "=f"(d[31])
        : "r"(a0), "r"(a1), "r"(a2), "r"(a3), "l"(db));
}
__device__ __forceinline__ void wg_ss_n16_ta1_tb0_d(float (&d)[8], uint64_t da, uint64_t db) {
    asm volatile("{\n.reg .pred p;\nsetp.ne.b32 p, 1, 0;\n"
        "wgmma.mma_async.sync.aligned.m64n16k16.f32.bf16.bf16 {%0, %1, %2, %3, %4, %5, %6, %7}, %8, %9, p, 1, 1, 1, 0;\n}\n"
        : "+f"(d[0]), "+f"(d[1]), "+f"(d[2]), "+f"(d[3]), "+f"(d[4]), "+f"(d[5]), "+f"(d[6]), "+f"(d[7])
        : "l"(da), "l"(db));
}
__device__ __forceinline__ void wg_ss_n16_ta1_tb0_initd(float (&d)[8], uint64_t da, uint64_t db) {
    asm volatile("{\n.reg .pred p;\nsetp.ne.b32 p, 0, 0;\n"
        "wgmma.mma_async.sync.aligned.m64n16k16.f32.bf16.bf16 {%0, %1, %2, %3, %4, %5, %6, %7}, %8, %9, p, 1, 1, 1, 0;\n}\n"
        : "=f"(d[0]), "=f"(d[1]), "=f"(d[2]), "=f"(d[3]), "=f"(d[4]), "=f"(d[5]), "=f"(d[6]), "=f"(d[7])
        : "l"(da), "l"(db));
}
__device__ __forceinline__ void wg_ss_n32_ta1_tb1_d(float (&d)[16], uint64_t da, uint64_t db) {
    asm volatile("{\n.reg .pred p;\nsetp.ne.b32 p, 1, 0;\n"
        "wgmma.mma_async.sync.aligned.m64n32k16.f32.bf16.bf16 {%0, %1, %2, %3, %4, %5, %6, %7, %8, %9, %10, %11, %12, %13, %14, %15}, %16, %17, p, 1, 1, 1, 1;\n}\n"
        : "+f"(d[0]), "+f"(d[1]), "+f"(d[2]), "+f"(d[3]), "+f"(d[4]), "+f"(d[5]), "+f"(d[6]), "+f"(d[7]), "+f"(d[8]), "+f"(d[9]), "+f"(d[10]), "+f"(d[11]), "+f"(d[12]), "+f"(d[13]), "+f"(d[14]), "+f"(d[15])
        : "l"(da), "l"(db));
}
__device__ __forceinline__ void wg_ss_n72_ta1_tb1_d(float (&d)[36], uint64_t da, uint64_t db) {
    asm volatile("{\n.reg .pred p;\nsetp.ne.b32 p, 1, 0;\n"
        "wgmma.mma_async.sync.aligned.m64n72k16.f32.bf16.bf16 {%0, %1, %2, %3, %4, %5, %6, %7, %8, %9, %10, %11, %12, %13, %14, %15, %16, %17, %18, %19, %20, %21, %22, %23, %24, %25, %26, %27, %28, %29, %30, %31, %32, %33, %34, %35}, %36, %37, p, 1, 1, 1, 1;\n}\n"
        : "+f"(d[0]), "+f"(d[1]), "+f"(d[2]), "+f"(d[3]), "+f"(d[4]), "+f"(d[5]), "+f"(d[6]), "+f"(d[7]), "+f"(d[8]), "+f"(d[9]), "+f"(d[10]), "+f"(d[11]), "+f"(d[12]), "+f"(d[13]), "+f"(d[14]), "+f"(d[15]), "+f"(d[16]), "+f"(d[17]), "+f"(d[18]), "+f"(d[19]), "+f"(d[20]), "+f"(d[21]), "+f"(d[22]), "+f"(d[23]), "+f"(d[24]), "+f"(d[25]), "+f"(d[26]), "+f"(d[27]), "+f"(d[28]), "+f"(d[29]), "+f"(d[30]), "+f"(d[31]), "+f"(d[32]), "+f"(d[33]), "+f"(d[34]), "+f"(d[35])
        : "l"(da), "l"(db));
}
__device__ __forceinline__ void wg_ss_n80_ta0_tb1_d(float (&d)[40], uint64_t da, uint64_t db) {
    asm volatile("{\n.reg .pred p;\nsetp.ne.b32 p, 1, 0;\n"
        "wgmma.mma_async.sync.aligned.m64n80k16.f32.bf16.bf16 {%0, %1, %2, %3, %4, %5, %6, %7, %8, %9, %10, %11, %12, %13, %14, %15, %16, %17, %18, %19, %20, %21, %22, %23, %24, %25, %26, %27, %28, %29, %30, %31, %32, %33, %34, %35, %36, %37, %38, %39}, %40, %41, p, 1, 1, 0, 1;\n}\n"
        : "+f"(d[0]), "+f"(d[1]), "+f"(d[2]), "+f"(d[3]), "+f"(d[4]), "+f"(d[5]), "+f"(d[6]), "+f"(d[7]), "+f"(d[8]), "+f"(d[9]), "+f"(d[10]), "+f"(d[11]), "+f"(d[12]), "+f"(d[13]), "+f"(d[14]), "+f"(d[15]), "+f"(d[16]), "+f"(d[17]), "+f"(d[18]), "+f"(d[19]), "+f"(d[20]), "+f"(d[21]), "+f"(d[22]), "+f"(d[23]), "+f"(d[24]), "+f"(d[25]), "+f"(d[26]), "+f"(d[27]), "+f"(d[28]), "+f"(d[29]), "+f"(d[30]), "+f"(d[31]), "+f"(d[32]), "+f"(d[33]), "+f"(d[34]), "+f"(d[35]), "+f"(d[36]), "+f"(d[37]), "+f"(d[38]), "+f"(d[39])
        : "l"(da), "l"(db));
}
__device__ __forceinline__ void wg_ss_n80_ta0_tb1_initd(float (&d)[40], uint64_t da, uint64_t db) {
    asm volatile("{\n.reg .pred p;\nsetp.ne.b32 p, 0, 0;\n"
        "wgmma.mma_async.sync.aligned.m64n80k16.f32.bf16.bf16 {%0, %1, %2, %3, %4, %5, %6, %7, %8, %9, %10, %11, %12, %13, %14, %15, %16, %17, %18, %19, %20, %21, %22, %23, %24, %25, %26, %27, %28, %29, %30, %31, %32, %33, %34, %35, %36, %37, %38, %39}, %40, %41, p, 1, 1, 0, 1;\n}\n"
        : "=f"(d[0]), "=f"(d[1]), "=f"(d[2]), "=f"(d[3]), "=f"(d[4]), "=f"(d[5]), "=f"(d[6]), "=f"(d[7]), "=f"(d[8]), "=f"(d[9]), "=f"(d[10]), "=f"(d[11]), "=f"(d[12]), "=f"(d[13]), "=f"(d[14]), "=f"(d[15]), "=f"(d[16]), "=f"(d[17]), "=f"(d[18]), "=f"(d[19]), "=f"(d[20]), "=f"(d[21]), "=f"(d[22]), "=f"(d[23]), "=f"(d[24]), "=f"(d[25]), "=f"(d[26]), "=f"(d[27]), "=f"(d[28]), "=f"(d[29]), "=f"(d[30]), "=f"(d[31]), "=f"(d[32]), "=f"(d[33]), "=f"(d[34]), "=f"(d[35]), "=f"(d[36]), "=f"(d[37]), "=f"(d[38]), "=f"(d[39])
        : "l"(da), "l"(db));
}
__device__ __forceinline__ void wg_ss_n88_ta0_tb1_d(float (&d)[44], uint64_t da, uint64_t db) {
    asm volatile("{\n.reg .pred p;\nsetp.ne.b32 p, 1, 0;\n"
        "wgmma.mma_async.sync.aligned.m64n88k16.f32.bf16.bf16 {%0, %1, %2, %3, %4, %5, %6, %7, %8, %9, %10, %11, %12, %13, %14, %15, %16, %17, %18, %19, %20, %21, %22, %23, %24, %25, %26, %27, %28, %29, %30, %31, %32, %33, %34, %35, %36, %37, %38, %39, %40, %41, %42, %43}, %44, %45, p, 1, 1, 0, 1;\n}\n"
        : "+f"(d[0]), "+f"(d[1]), "+f"(d[2]), "+f"(d[3]), "+f"(d[4]), "+f"(d[5]), "+f"(d[6]), "+f"(d[7]), "+f"(d[8]), "+f"(d[9]), "+f"(d[10]), "+f"(d[11]), "+f"(d[12]), "+f"(d[13]), "+f"(d[14]), "+f"(d[15]), "+f"(d[16]), "+f"(d[17]), "+f"(d[18]), "+f"(d[19]), "+f"(d[20]), "+f"(d[21]), "+f"(d[22]), "+f"(d[23]), "+f"(d[24]), "+f"(d[25]), "+f"(d[26]), "+f"(d[27]), "+f"(d[28]), "+f"(d[29]), "+f"(d[30]), "+f"(d[31]), "+f"(d[32]), "+f"(d[33]), "+f"(d[34]), "+f"(d[35]), "+f"(d[36]), "+f"(d[37]), "+f"(d[38]), "+f"(d[39]), "+f"(d[40]), "+f"(d[41]), "+f"(d[42]), "+f"(d[43])
        : "l"(da), "l"(db));
}

#define WG_FENCE() asm volatile("wgmma.fence.sync.aligned;" ::: "memory")
#define WG_COMMIT() asm volatile("wgmma.commit_group.sync.aligned;" ::: "memory")
#define WG_WAIT(n) asm volatile("wgmma.wait_group.sync.aligned %0;" :: "n"(n) : "memory")
template <int NR> __device__ __forceinline__ void fence_regs(float (&d)[NR]) {
#pragma unroll
    for (int i = 0; i < NR; i++) asm volatile("" : "+f"(d[i]) :: "memory");
}
template <int NR> __device__ __forceinline__ void zero_regs(float (&d)[NR]) {
#pragma unroll
    for (int i = 0; i < NR; i++) asm volatile("mov.b32 %0, 0;" : "=f"(d[i]) :: "memory");
}
constexpr uint32_t SW128 = 1u << 30, SW32 = 3u << 30;
__device__ __forceinline__ constexpr uint32_t dlo(uint32_t lbo) { return (lbo >> 4) << 16; }

__device__ __forceinline__ void bar_sync(int id, int n) { asm volatile("bar.sync %0, %1;" :: "r"(id), "r"(n) : "memory"); }
__device__ __forceinline__ void bar_arrive(int id, int n) { asm volatile("bar.arrive %0, %1;" :: "r"(id), "r"(n) : "memory"); }
__device__ __forceinline__ void mbar_init(uint32_t bar, uint32_t cnt) { asm volatile("mbarrier.init.shared::cta.b64 [%0], %1;" :: "r"(bar), "r"(cnt) : "memory"); }
__device__ __forceinline__ void mbar_arrive(uint32_t bar) { asm volatile("mbarrier.arrive.shared::cta.b64 _, [%0];" :: "r"(bar) : "memory"); }
__device__ __forceinline__ void mbar_expect(uint32_t bar, uint32_t bytes) { asm volatile("mbarrier.arrive.expect_tx.shared::cta.b64 _, [%0], %1;" :: "r"(bar), "r"(bytes) : "memory"); }
__device__ __forceinline__ void mbar_wait(uint32_t bar, uint32_t parity) {
    asm volatile("{\n.reg .pred p;\n.reg .u32 n;\nmov.u32 n, 0;\n"
                 "MW_LOOP:\nmbarrier.try_wait.parity.shared::cta.b64 p, [%0], %1;\n@p bra.uni MW_DONE;\n"
                 "add.u32 n, n, 1;\nsetp.lt.u32 p, n, 32768;\n@p bra.uni MW_LOOP;\nMW_DONE:\n}"
                 :: "r"(bar), "r"(parity) : "memory");
}
__device__ __forceinline__ bool mbar_test(uint32_t bar, uint32_t parity) {
    uint32_t r;
    asm volatile("{\n.reg .pred p;\nmbarrier.test_wait.parity.shared::cta.b64 p, [%1], %2;\nselp.u32 %0, 1, 0, p;\n}" : "=r"(r) : "r"(bar), "r"(parity) : "memory");
    return r;
}
__device__ __forceinline__ void count_wait(uint32_t addr, uint32_t seen, uint32_t need) {
    asm volatile("{\n.reg .pred p;\n.reg .u32 n, v;\nmov.u32 n, 0;\nmov.u32 v, %1;\n"
                 "CW_LOOP:\nsetp.ge.u32 p, v, %2;\n@p bra.uni CW_DONE;\nld.volatile.shared.u32 v, [%0];\n"
                 "add.u32 n, n, 1;\nsetp.lt.u32 p, n, 0x400000;\n@p bra.uni CW_LOOP;\nCW_DONE:\n}"
                 :: "r"(addr), "r"(seen), "r"(need) : "memory");
}
__device__ __forceinline__ uint32_t queue_wait(uint32_t addr) {
    uint32_t v;
    asm volatile("{\n.reg .pred p;\n.reg .u32 n;\nmov.u32 n, 0;\n"
                 "QW_LOOP:\nld.acquire.cta.shared::cta.u32 %0, [%1];\nsetp.ne.u32 p, %0, 0;\n@p bra.uni QW_DONE;\n"
                 "add.u32 n, n, 1;\nsetp.lt.u32 p, n, 0x400000;\n@p bra.uni QW_LOOP;\nmov.u32 %0, 1;\nQW_DONE:\n}"
                 : "=r"(v) : "r"(addr) : "memory");
    return v;
}
__device__ __forceinline__ void tma2d(uint32_t dst, const CUtensorMap* m, int x, int y, uint32_t bar) {
    asm volatile("cp.async.bulk.tensor.2d.shared::cluster.global.mbarrier::complete_tx::bytes [%0], [%1, {%2, %3}], [%4];"
                 :: "r"(dst), "l"(m), "r"(x), "r"(y), "r"(bar) : "memory");
}
__device__ __forceinline__ void bulk1d(uint32_t dst, const void* src, uint32_t bytes, uint32_t bar) {
    asm volatile("cp.async.bulk.shared::cluster.global.mbarrier::complete_tx::bytes [%0], [%1], %2, [%3];"
                 :: "r"(dst), "l"(src), "r"(bytes), "r"(bar) : "memory");
}
__device__ __forceinline__ void tma3d(uint32_t dst, const CUtensorMap* m, int y, int z, uint32_t bar) {
    asm volatile("cp.async.bulk.tensor.3d.shared::cluster.global.mbarrier::complete_tx::bytes [%0], [%1, {0, %2, %3}], [%4];"
                 :: "r"(dst), "l"(m), "r"(y), "r"(z), "r"(bar) : "memory");
}
__device__ __forceinline__ void tma2d_store(const CUtensorMap* m, int x, int y, uint32_t src) {
    asm volatile("cp.async.bulk.tensor.2d.global.shared::cta.bulk_group [%0, {%1, %2}], [%3];" :: "l"(m), "r"(x), "r"(y), "r"(src) : "memory");
}
__device__ __forceinline__ void bulk_store(void* dst, uint32_t src, uint32_t bytes) {
    asm volatile("cp.async.bulk.global.shared::cta.bulk_group [%0], [%1], %2;" :: "l"(dst), "r"(src), "r"(bytes) : "memory");
}
__device__ __forceinline__ void bulk_add_f32(void* dst, uint32_t src, uint32_t bytes) {
    asm volatile("cp.reduce.async.bulk.global.shared::cta.bulk_group.add.f32 [%0], [%1], %2;" :: "l"(dst), "r"(src), "r"(bytes) : "memory");
}
__device__ __forceinline__ void bulk_commit() { asm volatile("cp.async.bulk.commit_group;" ::: "memory"); }
__device__ __forceinline__ void bulk_wait() {
    asm volatile("cp.async.bulk.wait_group 0;\nfence.proxy.async.global;" ::: "memory");
}
__device__ __forceinline__ void prefetch_l2(const void* p, uint32_t bytes) { asm volatile("cp.async.bulk.prefetch.L2.global [%0], %1;" :: "l"(p), "r"(bytes) : "memory"); }
__device__ __forceinline__ void prefetch_map(const CUtensorMap* m) { asm volatile("prefetch.tensormap [%0];" :: "l"(m) : "memory"); }
__device__ __forceinline__ uint32_t opaque_tid() { uint32_t t; asm volatile("mov.u32 %0, %tid.x;" : "=r"(t) :: "memory"); return t; }
__device__ __forceinline__ uint32_t opaque_cta() { uint32_t t; asm volatile("mov.u32 %0, %ctaid.x;" : "=r"(t) :: "memory"); return t; }
__device__ __forceinline__ bool elect_one() {
    uint32_t p;
    asm volatile("{\n.reg .pred p;\nelect.sync _|p, 0xffffffff;\nselp.u32 %0, 1, 0, p;\n}" : "=r"(p));
    return p;
}
__device__ __forceinline__ void fence_async() { asm volatile("fence.proxy.async.global;" ::: "memory"); }
__device__ __forceinline__ void fence_async_smem() { asm volatile("fence.proxy.async.shared::cta;" ::: "memory"); }
__device__ __forceinline__ void st_flag(uint16_t* p, uint32_t v) { asm volatile("st.release.gpu.global.u16 [%0], %1;" :: "l"(p), "h"((uint16_t)v) : "memory"); }
__device__ __forceinline__ void st_relaxed(void* p, uint32_t v) { asm volatile("st.relaxed.gpu.global.u32 [%0], %1;" :: "l"(p), "r"(v) : "memory"); }
__device__ __forceinline__ uint4 ld_relaxed128(const void* p) { uint4 v; asm volatile("ld.relaxed.gpu.global.v4.u32 {%0, %1, %2, %3}, [%4];" : "=r"(v.x), "=r"(v.y), "=r"(v.z), "=r"(v.w) : "l"(p) : "memory"); return v; }
__device__ __forceinline__ uint4 ld_acquire128(const void* p) { uint4 v; asm volatile("ld.acquire.gpu.global.v4.u32 {%0, %1, %2, %3}, [%4];" : "=r"(v.x), "=r"(v.y), "=r"(v.z), "=r"(v.w) : "l"(p) : "memory"); return v; }
__device__ __forceinline__ void poll1(const uint16_t* p, uint32_t tag) {
#pragma unroll 1
    for (uint32_t spin = 0; spin < (1u << 17); spin++) {
        uint16_t v;
        asm volatile("ld.acquire.gpu.global.u16 %0, [%1];" : "=h"(v) : "l"(p) : "memory");
        if (v == (uint16_t)tag) break;
    }
    fence_async();
}
__device__ __forceinline__ void poll8(const uint16_t* p, uint32_t tag) {
    const uint32_t t2 = (tag & 0xFFFFu) * 0x10001u;
#pragma unroll 1
    for (uint32_t spin = 0; spin < (1u << 17); spin++) {
        const uint4 a = ld_acquire128(p);
        if (a.x == t2 && a.y == t2 && a.z == t2 && a.w == t2) break;
    }
    fence_async();
}
__device__ __forceinline__ uint32_t lds32(uint32_t a) { uint32_t v; asm volatile("ld.shared.u32 %0, [%1];" : "=r"(v) : "r"(a) : "memory"); return v; }
__device__ __forceinline__ void sts32(uint32_t a, uint32_t v) { asm volatile("st.shared.u32 [%0], %1;" :: "r"(a), "r"(v) : "memory"); }
__device__ __forceinline__ void sts16(uint32_t a, uint16_t v) { asm volatile("st.shared.u16 [%0], %1;" :: "r"(a), "h"(v) : "memory"); }
__device__ __forceinline__ void sts64(uint32_t a, uint32_t x, uint32_t y) { asm volatile("st.shared.v2.u32 [%0], {%1, %2};" :: "r"(a), "r"(x), "r"(y) : "memory"); }
__device__ __forceinline__ void sts128(uint32_t a, uint32_t x, uint32_t y, uint32_t z, uint32_t w) { asm volatile("st.shared.v4.u32 [%0], {%1, %2, %3, %4};" :: "r"(a), "r"(x), "r"(y), "r"(z), "r"(w) : "memory"); }
__device__ __forceinline__ uint2 lds64(uint32_t a) { uint2 v; asm volatile("ld.shared.v2.u32 {%0, %1}, [%2];" : "=r"(v.x), "=r"(v.y) : "r"(a) : "memory"); return v; }
__device__ __forceinline__ uint4 lds128(uint32_t a) { uint4 v; asm volatile("ld.shared.v4.u32 {%0, %1, %2, %3}, [%4];" : "=r"(v.x), "=r"(v.y), "=r"(v.z), "=r"(v.w) : "r"(a) : "memory"); return v; }
__device__ __forceinline__ float ex2f(float x) { float y; asm("ex2.approx.ftz.f32 %0, %1;" : "=f"(y) : "f"(x)); return y; }
__device__ __forceinline__ float rcpf(float x) { float y; asm("rcp.approx.ftz.f32 %0, %1;" : "=f"(y) : "f"(x)); return y; }
__device__ __forceinline__ void stsm4(uint32_t a, uint32_t x, uint32_t y, uint32_t z, uint32_t w) {
    asm volatile("stmatrix.sync.aligned.m8n8.x4.shared.b16 [%0], {%1, %2, %3, %4};" :: "r"(a), "r"(x), "r"(y), "r"(z), "r"(w) : "memory");
}
__device__ __forceinline__ uint32_t pack_bf16(float lo, float hi) { uint32_t r; asm("cvt.rn.bf16x2.f32 %0, %1, %2;" : "=r"(r) : "f"(hi), "f"(lo)); return r; }
__device__ __forceinline__ float bf_lo(uint32_t v) { return __uint_as_float(v << 16); }
__device__ __forceinline__ float bf_hi(uint32_t v) { return __uint_as_float(v & 0xFFFF0000u); }
__device__ __forceinline__ uint32_t phi2(float t0, float t1) {
    uint32_t r;
    asm("{\n.reg .b32 one, eps, p, e;\nmov.b32 one, 0x3F803F80;\nmov.b32 eps, 0x35863586;\n"
        "add.rn.bf16x2 p, %1, one;\nmin.bf16x2 e, %2, one;\nmax.NaN.bf16x2 p, p, e;\nadd.rn.bf16x2 %0, p, eps;\n}"
        : "=r"(r) : "r"(pack_bf16(t0, t1)), "r"(pack_bf16(ex2f(t0 * LOG2E), ex2f(t1 * LOG2E))));
    return r;
}
template <int MODE> __device__ __forceinline__ void stage_tile(uint32_t x, uint32_t step, const float (&a)[40]) {
#pragma unroll
    for (int k = 0; k < 5; k++) {
        uint32_t r[4];
#pragma unroll
        for (int e = 0; e < 4; e++) {
            const float t0 = a[8 * k + 2 * e], t1 = a[8 * k + 2 * e + 1];
            r[e] = MODE == 0 ? pack_bf16(t0, t1) : MODE == 1 ? pack_bf16(t0 * QSCALE, t1 * QSCALE) : phi2(t0, t1);
        }
        stsm4(x + 2 * k * step, r[0], r[1], r[2], r[3]);
    }
}

__device__ __forceinline__ uint32_t exp2_pair(float t0, float t1, uint32_t ca) {
    uint32_t y, u, g;
    asm("prmt.b32 %0, %1, %2, 0x6521;" : "=r"(y) : "r"(__float_as_uint(t0)), "r"(__float_as_uint(t1)));
    u = y & 0x007F007Fu;
    asm("{.reg .b32 c; mov.b32 c, 0xF963F963; fma.rn.f16x2 %0, %1, c, %2;}" : "=r"(g) : "r"(u), "r"(ca));
    asm("mul.rn.f16x2 %0, %1, %2;" : "=r"(g) : "r"(g), "r"(u));
    return y - g;
}

__device__ __forceinline__ uint64_t desc(uint32_t addr, uint32_t lbo, uint32_t hi) { return ((uint64_t)hi << 32) | ((addr >> 4) + dlo(lbo)); }
template <int J> __device__ __forceinline__ void exp_steps(const float (&s)[32], uint32_t (&p)[16], float (&o)[12], uint64_t& dv, uint32_t ca) {
    if constexpr (J < 4) {
#pragma unroll
        for (int g = 2 * J; g < 2 * J + 2; g++) {
            if ((MUFU_MASK >> g) & 1) {
                p[2 * g] = pack_bf16(ex2f(s[4 * g]), ex2f(s[4 * g + 1]));
                p[2 * g + 1] = pack_bf16(ex2f(s[4 * g + 2]), ex2f(s[4 * g + 3]));
            } else {
                p[2 * g] = exp2_pair(s[4 * g], s[4 * g + 1], ca);
                p[2 * g + 1] = exp2_pair(s[4 * g + 2], s[4 * g + 3], ca);
            }
        }
        WG_FENCE();
        wg_rs_n24_tb1_d(o, p[4 * J], p[4 * J + 1], p[4 * J + 2], p[4 * J + 3], dv);
        dv += 96;
        exp_steps<J + 1>(s, p, o, dv, ca);
    }
}

struct Ring { uint32_t slot, phase; };
__device__ __forceinline__ void next_stage(Ring& r) { if (++r.slot == 3) { r.slot = 0; r.phase ^= 1; } }

#define BUNR 4
template <bool FAST>
__device__ __forceinline__ void attend(uint32_t sb, uint32_t& slot, int pass, const uint32_t (&q)[6], float (&o)[12], uint32_t ca, uint32_t z0, uint32_t z1) {
    float m0 = -INFINITY, m1 = -INFINITY;
    constexpr int UNR = FAST ? BUNR : 1;
#pragma unroll 1
    for (int c = 0; c < 8; c++) {
        const uint32_t base = sb + OFF_RING + slot * RING_BYTES;
        uint64_t dk = desc(base, 128, 768 >> 4), dv = desc(base + 384, 768, 128 >> 4);
        uint32_t seen;
#pragma unroll UNR
        for (int b = 0; b < 4; b++) {
            float s[32];
            uint32_t p[16];
            WG_FENCE();
            wg_rs_n64_tb0_initd(s, q[0], q[1], q[2], q[3], dk);
            dk += 16;
            wg_rs_n64_tb0_d(s, q[4], q[5], z0, z1, dk);
            dk += 368;
            WG_COMMIT();
            if (UNR < 4 || b == 3) seen = lds32(sb + OFF_PUB);
            WG_WAIT(0);
            fence_regs(s);
            if constexpr (FAST) {
                exp_steps<0>(s, p, o, dv, ca);
            } else {
                fence_regs(o);
                float x0 = m0, x1 = m1;
#pragma unroll
                for (int g = 0; g < 8; g++) {
                    if (!((MUFU_MASK >> g) & 1)) {
#pragma unroll
                        for (int e = 0; e < 4; e++) s[4 * g + e] *= 2.f;
                    }
                    x0 = fmaxf(x0, fmaxf(s[4 * g], s[4 * g + 1]));
                    x1 = fmaxf(x1, fmaxf(s[4 * g + 2], s[4 * g + 3]));
                }
                x0 = fmaxf(x0, __shfl_xor_sync(~0u, x0, 1)); x0 = fmaxf(x0, __shfl_xor_sync(~0u, x0, 2));
                x1 = fmaxf(x1, __shfl_xor_sync(~0u, x1, 1)); x1 = fmaxf(x1, __shfl_xor_sync(~0u, x1, 2));
                const float a0 = ex2f(m0 - x0), a1 = ex2f(m1 - x1);
                m0 = x0; m1 = x1;
#pragma unroll
                for (int b = 0; b < 3; b++) { o[4 * b] *= a0; o[4 * b + 1] *= a0; o[4 * b + 2] *= a1; o[4 * b + 3] *= a1; }
#pragma unroll
                for (int g = 0; g < 8; g++) {
                    p[2 * g] = pack_bf16(ex2f(s[4 * g] - x0), ex2f(s[4 * g + 1] - x0));
                    p[2 * g + 1] = pack_bf16(ex2f(s[4 * g + 2] - x1), ex2f(s[4 * g + 3] - x1));
                }
            }
            if constexpr (!FAST) {
                WG_FENCE();
#pragma unroll
                for (int k = 0; k < 4; k++) { wg_rs_n24_tb1_d(o, p[4 * k], p[4 * k + 1], p[4 * k + 2], p[4 * k + 3], dv); dv += 96; }
            }
            WG_COMMIT();
            WG_WAIT(0);
            fence_regs(o);
        }
        if ((threadIdx.x & 31) == 0) mbar_arrive(sb + BAR_EMPTY_KV + slot * 8);
        slot = slot == 2 ? 0 : slot + 1;
        count_wait(sb + OFF_PUB, seen, min(pass * 8 + c + 2, 16));
    }
}

__device__ __forceinline__ void gemm_pass(uint32_t sb, int pass, float (&a)[40], float (&b)[40]) {
    zero_regs(a); zero_regs(b);
    const uint32_t n0 = __shfl_sync(~0u, pass, 0) * 10;
    uint32_t slot = n0 % 3, phase = (n0 / 3) & 1;
    const bool lead = (threadIdx.x & 31) == 0;
#pragma unroll 1
    for (int c = 0; c < 10; c++) {
        mbar_wait(sb + BAR_FULL_G + slot * 8, phase);
        const uint32_t st = sb + OFF_STAGE + slot * STAGE_BYTES;
        const uint64_t dx = desc(st, 16, SW128 | 64), dw = desc(st + 16384, 2048, SW32 | 16);
        WG_FENCE();
#pragma unroll
        for (int k = 0; k < 4; k++) {
            wg_ss_n80_ta0_tb1_d(a, dx + 2 * k, dw + 32 * k);
            wg_ss_n80_ta0_tb1_d(b, dx + 512 + 2 * k, dw + 32 * k);
        }
        WG_COMMIT();
        WG_WAIT(0);
        if (lead) mbar_arrive(sb + BAR_EMPTY_G + slot * 8);
        if (++slot == 3) { slot = 0; phase ^= 1; }
    }
    fence_regs(a); fence_regs(b);
}

__device__ __forceinline__ void gemm_half(uint32_t sb, float (&a)[40]) {
    zero_regs(a);
    const bool lead = (threadIdx.x & 31) == 0;
#pragma unroll 1
    for (int c = 0; c < 10; c++) {
        mbar_wait(sb + BAR_FULL_X + (c & 3) * 8, (c >> 2) & 1);
        const uint64_t dx = desc(sb + OFF_XA + (c & 3) * 8192, 16, SW128 | 64), dw = desc(sb + OFF_WA + c * 10240, 2048, SW32 | 16);
        WG_FENCE();
#pragma unroll
        for (int k = 0; k < 4; k++) wg_ss_n80_ta0_tb1_d(a, dx + 2 * k, dw + 32 * k);
        WG_COMMIT();
        WG_WAIT(1);
        if (c > 0 && lead) mbar_arrive(sb + BAR_EMPTY_X + ((c - 1) & 3) * 8);
    }
    WG_WAIT(0);
    fence_regs(a);
}

__device__ __forceinline__ void store_tile(uint32_t stage, __nv_bfloat16* dst, int lane, const float (&a)[40]) {
    stage_tile<0>(stage + (lane & 15) * 160 + (lane >> 4) * 16, 16, a);
    __syncwarp();
#pragma unroll
    for (int u = 0; u < 5; u++) {
        const int x = lane + 32 * u, row = (x * 205) >> 11;
        const uint4 v = lds128(stage + x * 16);
        *reinterpret_cast<uint4*>(dst + row * (1280 - 80) + x * 8) = v;
    }
    __syncwarp();
}

__device__ __forceinline__ void linear_out(uint32_t sb, int half, uint32_t dst, int q) {
    float d[44]; zero_regs(d);
    const uint64_t da = desc(sb + OFF_PK + half * 10240, 128, 80), db = desc(sb + OFF_KVB, 1408, 8);
    WG_FENCE();
#pragma unroll
    for (int k = 0; k < 5; k++) wg_ss_n88_ta0_tb1_d(d, da + 16 * k, db + 176 * k);
    WG_COMMIT();
    WG_WAIT(0);
    fence_regs(d);
    bar_sync(6, 128);
    float r0[4], r1[4];
    const int base = (threadIdx.x & 31) & ~3;
#pragma unroll
    for (int e = 0; e < 4; e++) d[40 + e] = rcpf(d[40 + e] + 1e-6f);
#pragma unroll
    for (int h = 0; h < 4; h++) {
        r0[h] = __shfl_sync(~0u, d[40 + (h & 1)], base + (h >> 1));
        r1[h] = __shfl_sync(~0u, d[42 + (h & 1)], base + (h >> 1));
    }
    uint32_t r[20];
#pragma unroll
    for (int b = 0; b < 10; b++) {
        const int hl = (8 * b) / 20, hh = (8 * b + 6) / 20;
        const bool up = hl != hh && q >= 2;
        const float s0 = up ? r0[hh] : r0[hl], s1 = up ? r1[hh] : r1[hl];
        r[2 * b] = pack_bf16(d[4 * b] * s0, d[4 * b + 1] * s0);
        r[2 * b + 1] = pack_bf16(d[4 * b + 2] * s1, d[4 * b + 3] * s1);
    }
#pragma unroll
    for (int k = 0; k < 5; k++) stsm4(dst + 32 * k, r[4 * k], r[4 * k + 1], r[4 * k + 2], r[4 * k + 3]);
}

__global__ void __launch_bounds__(NTHR, 1) fused_kernel(const __grid_constant__ Params P) {
    extern __shared__ __align__(1024) uint8_t smem[];
    const uint32_t sb = (uint32_t)__cvta_generic_to_shared(smem);
    const int tid = threadIdx.x, lane = tid & 31;
    const int wg = __shfl_sync(~0u, tid >> 7, 0), warp = __shfl_sync(~0u, (tid >> 5) & 3, 0);
    const int cta = blockIdx.x, i = cta >> 3, j = cta & 7;
    const int q = lane & 3, r0 = 16 * warp + (lane >> 2);
    if (wg == 4 || wg == 0) TS(wg == 4 ? 0 : 16);

    const uint32_t tag = *(volatile uint32_t*)&g_epoch + 1;

    if (cta >= NCTA) {
        if (tid < 64 && elect_one()) {
            const int jj = 2 * (cta - NCTA) + warp;
            const uint32_t buf = sb + warp * 102400, bar = sb + OFF_BAR + warp * 80;
#pragma unroll 1
            for (int s = 0; s < 10; s++) mbar_init(bar + s * 8, 1);
            asm volatile("fence.mbarrier_init.release.cluster;" ::: "memory");
            int lp = 0, lc = 0;
#pragma unroll 1
            for (int n = -8; n < 40; n++) {
                if (n >= 0) {
                    const int part = n / 10, c = n - 10 * part;
                    mbar_wait(bar + c * 8, part & 1);
                    bulk_store(g_wt + ((part * 8 + jj) * 10 + c) * 10240, buf + c * 10240, 10240);
                    bulk_commit();
                    if (c == 9) { bulk_wait(); st_flag(g_flag_w + part * 8 + jj, tag); }
                    else asm volatile("cp.async.bulk.wait_group.read 2;" ::: "memory");
                }
                if (lp < 4) {
                    mbar_expect(bar + lc * 8, 10240);
                    tma3d(buf + lc * 10240, lp < 2 ? &P.wqkv : lp == 2 ? &P.wob : &P.woa, 64 * lc, 5 * jj + (lp == 0 ? 80 : 0), bar + lc * 8);
                    if (++lc == 10) { lc = 0; lp++; }
                }
            }
        }
        return;
    }
    if (tid == 640) {
        mbar_init(sb + BAR_KVIN, 1);
        asm volatile("fence.mbarrier_init.release.cluster;" ::: "memory");
        mbar_expect(sb + BAR_KVIN, 51200 + 20480);
        tma3d(sb + OFF_X16, &P.xa16, 16 * cta, 0, sb + BAR_KVIN);
#pragma unroll
        for (int u = 0; u < 4; u++) {
            const int v = (u + cta) & 3;
            bulk1d(sb + OFF_WRAW + v * 12800, P.in[2 + (v >> 1)] + (v & 1) * 12800, 12800, sb + BAR_KVIN);
        }
    } else if (tid == 672) {
#pragma unroll
        for (int s = 0; s < 3; s++) {
            mbar_init(sb + BAR_FULL_G + s * 8, 2);
            mbar_init(sb + BAR_EMPTY_G + s * 8, 4);
            mbar_init(sb + BAR_FULL_KV + s * 8, 1);
            mbar_init(sb + BAR_EMPTY_KV + s * 8, 16);
        }
        mbar_init(sb + BAR_OA, 16);
        mbar_init(sb + BAR_OA + 8, 16);
        asm volatile("fence.mbarrier_init.release.cluster;" ::: "memory");
    } else if (tid == 704) {
        prefetch_map(&P.xa);
        prefetch_map(&P.wq);
        prefetch_l2(P.in[1] + cta * 6400, 6400);
        mbar_init(sb + BAR_WA, 1);
        mbar_init(sb + BAR_PART, 4);
        mbar_init(sb + BAR_KVB, 1);
        mbar_init(sb + BAR_OB, 4);
        sts32(sb + OFF_PUB, 0);
        sts128(sb + OFF_STAT + 16, 0x357F357Fu, 0u, 0u, 0u);
        asm volatile("fence.mbarrier_init.release.cluster;" ::: "memory");
    } else if (tid == 736) {
#pragma unroll
        for (int s = 0; s < 4; s++) { mbar_init(sb + BAR_FULL_X + s * 8, 1); mbar_init(sb + BAR_EMPTY_X + s * 8, 4); }
#pragma unroll
        for (int s = 0; s < 4; s++) sts128(sb + OFF_QUEUE + s * 16, 0u, 0u, 0u, 0u);
        mbar_init(sb + BAR_A0, 1);
        asm volatile("fence.mbarrier_init.release.cluster;" ::: "memory");
    }
    __syncthreads();

    if (wg == 5) {
        asm volatile("setmaxnreg.dec.sync.aligned.u32 32;");
        if (warp == 0) {
            if (elect_one()) {
                Ring r{0, 1};
#pragma unroll 1
                for (int pass = 0; pass < NPASS; pass++) {
                    const CUtensorMap* m = pass == 0 ? &P.xa : pass <= 3 ? &P.xb : &P.ob;
                    if (pass == 1) count_wait(sb + OFF_PUB, 0, HOLD);
                    if (pass == 4) {
                        mbar_wait(sb + BAR_OB, 0);
                        tma2d_store(&P.ob_st, 80 * j, 128 * i, sb + OFF_PK);
                        bulk_commit();
                        bulk_wait();
                        st_flag(g_flag_b2 + cta, tag);
                        poll8(g_flag_b2 + i * 8, tag);
                    }
#pragma unroll 1
                    for (int c = 0; c < 10; c++) {
                        if (pass == 3 && c == 3) {
                            mbar_wait(sb + BAR_PART, 0);
                            bulk_add_f32(g_part + j * 1920, sb + OFF_PST, 7680);
                            bulk_commit();
                        }
                        if (pass > 0 || c >= 3) mbar_wait(sb + BAR_EMPTY_G + r.slot * 8, r.phase);
                        mbar_expect(sb + BAR_FULL_G + r.slot * 8, 16384);
                        tma2d(sb + OFF_STAGE + r.slot * STAGE_BYTES, m, 64 * c, 128 * i, sb + BAR_FULL_G + r.slot * 8);
                        next_stage(r);
                        if (pass == 3 && c == 3) {
                            bulk_wait();
                            st_flag(g_flag_b1 + j * 16 + i, tag);
                        }
                    }
                }
                if (NPASS == 5) {
                    poll8(g_flag_a + i * 8, tag);
                    mbar_arrive(sb + BAR_A0);
#pragma unroll 1
                    for (int c = 0; c < 10; c++) {
                        const uint32_t s = c & 3;
                        if (c >= 4) mbar_wait(sb + BAR_EMPTY_X + s * 8, ((c >> 2) - 1) & 1);
                        mbar_expect(sb + BAR_FULL_X + s * 8, 8192);
                        tma2d(sb + OFF_XA + s * 8192, &P.oa, 64 * c, 128 * i, sb + BAR_FULL_X + s * 8);
                    }
                }
            }
        } else if (warp == 2) {
            if (elect_one()) {
                Ring r{0, 1};
#pragma unroll 1
                for (int pass = 0; pass < NPASS; pass++) {
                    const CUtensorMap* m = pass == 0 ? &P.wq : pass <= 3 ? &P.wqkv : &P.wob;
                    const int col = 5 * j + (pass == 1 ? 40 : pass == 2 ? 80 : 0);
                    if (pass == 1) count_wait(sb + OFF_PUB, 0, HOLD);
                    const bool pre = pass >= 2 && P.helpers;
                    if (pre) poll1(g_flag_w + (pass - 2) * 8 + j, tag);
#pragma unroll 1
                    for (int c = 0; c < 10; c++) {
                        if (pass > 0 || c >= 3) mbar_wait(sb + BAR_EMPTY_G + r.slot * 8, r.phase);
                        const uint32_t bar = sb + BAR_FULL_G + r.slot * 8;
                        mbar_expect(bar, 10240);
                        const uint32_t dst = sb + OFF_STAGE + r.slot * STAGE_BYTES + 16384;
                        if (pre) bulk1d(dst, g_wt + (((pass - 2) * 8 + j) * 10 + c) * 10240, 10240, bar);
                        else tma3d(dst, m, 64 * c, col, bar);
                        next_stage(r);
                    }
                }
                if (NPASS == 5) {
                    if (P.helpers) poll1(g_flag_w + 24 + j, tag);
#pragma unroll 1
                    for (int c = 0; c < 3; c++) { mbar_wait(sb + BAR_EMPTY_G + r.slot * 8, r.phase); next_stage(r); }
                    mbar_expect(sb + BAR_WA, 102400);
                    if (P.helpers) bulk1d(sb + OFF_WA, g_wt + (24 + j) * 102400, 102400, sb + BAR_WA);
                    else {
#pragma unroll 1
                        for (int c = 0; c < 10; c++) tma3d(sb + OFF_WA + c * 10240, &P.woa, 64 * c, 5 * j, sb + BAR_WA);
                    }
                }
            }
        } else if (warp == 3) {
            if (elect_one()) {
                mbar_wait(sb + BAR_FULL_G, 0);
                mbar_wait(sb + BAR_FULL_G, 1);
                mbar_wait(sb + BAR_FULL_G, 0);
                prefetch_l2(P.in[5] + cta * 20480, 20480);
#pragma unroll 1
                for (int u = 0; u < 5; u++) prefetch_l2(P.in[6] + (cta * 5 + u) * 3840 + 1280, 1280);
            }
            __syncwarp();
            if (NPASS == 5) {
                if (elect_one()) {
                    poll8(g_flag_b1 + j * 16, tag);
                    poll8(g_flag_b1 + j * 16 + 8, tag);
                    mbar_expect(sb + BAR_KVB, 7680);
                    bulk1d(sb + OFF_PST, g_part + j * 1920, 7680, sb + BAR_KVB);
                }
            }
            if (elect_one()) {
                mbar_wait(sb + BAR_OA, 0);
                tma2d_store(&P.oa_st, 80 * j, 128 * i, sb + OFF_Q);
                bulk_commit();
                bulk_wait();
                st_flag(g_flag_a + cta, tag);
            }
        } else if (warp == 1) {
            uint32_t sk, sv, spin = 0;
            bar_sync(12, 64);
#pragma unroll 1
            while (true) {
                const uint4 f = ld_relaxed128(g_flag_kv + 2 * lane), g = ld_relaxed128(g_flag_kv + 2 * lane + 64);
                const bool ok = f.y == tag && f.w == tag && g.y == tag && g.w == tag;
                sk = max(max(f.x >> 16, f.z >> 16), max(g.x >> 16, g.z >> 16));
                sv = max(max(f.x & 0xFFFFu, f.z & 0xFFFFu), max(g.x & 0xFFFFu, g.z & 0xFFFFu));
                if (__all_sync(~0u, ok) || ++spin > (1u << 17)) break;
            }
            asm volatile("fence.acq_rel.cta;" ::: "memory");
            sk = __reduce_max_sync(~0u, sk);
            sv = __reduce_max_sync(~0u, sv);
            if (elect_one()) {
                const bool vok = sv == 0 || (sv >= ((127 - 40) << 7) && sv <= ((127 + 40) << 7));
                sts32(sb + OFF_STAT, vok ? sk << 16 : 0x7FC00000u);
                fence_async();
#pragma unroll 1
                for (int n = 0; n < 3; n++) {
                    mbar_expect(sb + BAR_FULL_KV + n * 8, RING_BYTES);
                    bulk1d(sb + OFF_RING + n * RING_BYTES, g_kv + n * RING_BYTES, RING_BYTES, sb + BAR_FULL_KV + n * 8);
                }
                Ring r{0, 0};
#pragma unroll 1
                for (int n = 0; n < 16; n++) {
                    if (n >= 3) {
                        mbar_wait(sb + BAR_EMPTY_KV + r.slot * 8, r.phase ^ 1);
                        mbar_expect(sb + BAR_FULL_KV + r.slot * 8, RING_BYTES);
                        bulk1d(sb + OFF_RING + r.slot * RING_BYTES, g_kv + (n & 7) * RING_BYTES, RING_BYTES, sb + BAR_FULL_KV + r.slot * 8);
                    }
                    mbar_wait(sb + BAR_FULL_KV + r.slot * 8, r.phase);
                    asm volatile("st.release.cta.shared::cta.u32 [%0], %1;" :: "r"(sb + OFF_PUB), "r"(n + 1) : "memory");
                    next_stage(r);
                }
            }
        }
    } else if (wg < 4) {
        {
            if (tid < 30) reinterpret_cast<uint4*>(g_part + j * 1920 + i * 120)[tid] = make_uint4(0u, 0u, 0u, 0u);
            const int k = tid / 5, m0 = 4 * (tid - 5 * k), m1 = m0 + 20;
            const uint32_t row = sb + OFF_WKV + (k >> 3) * 880 + (k & 7) * 16;
            const uint32_t a0 = row + (m0 >> 3) * 176 + (m0 & 7) * 2, a1 = row + (m1 >> 3) * 176 + (m1 & 7) * 2;
            mbar_wait(sb + BAR_KVIN, 0);
            if (wg == 0) TS(13);
            uint2 w[14];
#pragma unroll
            for (int n = 0; n < 7; n++) if (tid < (n < 6 ? 480 : 320)) { w[2 * n] = lds64(sb + OFF_WRAW + tid * 8 + n * 3840); w[2 * n + 1] = lds64(sb + OFF_WRAW + 25600 + tid * 8 + n * 3840); }
#pragma unroll
            for (int n = 0; n < 7; n++) if (tid < (n < 6 ? 480 : 320)) { sts64(a0 + n * 10560, w[2 * n].x, w[2 * n].y); sts64(a1 + n * 10560, w[2 * n + 1].x, w[2 * n + 1].y); }
        }
        fence_async_smem();
        bar_sync(1, 512);
        if (wg == 0) {
            TS(14);
            float d[8];
            const uint64_t da = desc(sb + OFF_WKV, 880, 11), db = desc(sb + OFF_X16, 16, SW128 | 64);
            WG_FENCE();
            wg_ss_n16_ta1_tb0_initd(d, da, db);
#pragma unroll
            for (int k = 1; k < 40; k++) wg_ss_n16_ta1_tb0_d(d, da + 110 * k, db + (k >> 2) * 128 + (k & 3) * 2);
            WG_COMMIT();
            if (tid < 16) {
                const int g = tid >> 3;
                const bool mu = (MUFU_MASK >> ((2 * cta + g) & 7)) & 1;
                const uint32_t a = sb + OFF_IMG + g * 768 + (tid & 7) * 16 + 8;
                sts64(a + 256, mu ? 0u : 0x3F00433Fu, mu ? 0u : 0x00003B4Au);
                sts64(a + 640, 0x00003F80u, 0u);
            }
            WG_WAIT(0);
            fence_regs(d);
            bar_arrive(2, 256);
            TS(15);
#pragma unroll
            for (int hh = 0; hh < 2; hh++) {
                const int m = r0 + 8 * hh;
                if (m < 40) {
                    const int isv = m >= 20, dd = m - 20 * isv;
#pragma unroll
                    for (int g = 0; g < 2; g++) {
                        const bool mu = (MUFU_MASK >> ((2 * cta + g) & 7)) & 1;
                        const float sc = (isv || mu) ? 1.f : 0.5f;
                        const uint32_t pr = pack_bf16(d[4 * g + 2 * hh] * sc, d[4 * g + 2 * hh + 1] * sc);
                        const uint32_t a = sb + OFF_IMG + g * 768 + (3 * isv + (dd >> 3)) * 128 + (dd & 7) * 2 + 2 * q * 16;
                        sts16(a, (uint16_t)pr);
                        sts16(a + 16, (uint16_t)(pr >> 16));
                    }
                }
            }
            bar_sync(3, 128);
            if (warp == 0) {
#pragma unroll
                for (int u = 0; u < 3; u++) {
                    const uint4 v = lds128(sb + OFF_IMG + (lane + 32 * u) * 16);
                    *reinterpret_cast<uint4*>(g_kv + cta * 1536 + (lane + 32 * u) * 16) = v;
                }
                const int key = lane & 15, g = key >> 3;
                const uint32_t a = sb + OFF_IMG + g * 768 + (lane >> 4) * 384 + (key & 7) * 16;
                const uint4 w0 = lds128(a), w1 = lds128(a + 128);
                const uint2 w2 = lds64(a + 256);
                const uint32_t w[10] = {w0.x, w0.y, w0.z, w0.w, w1.x, w1.y, w1.z, w1.w, w2.x, w2.y};
                float n2 = 0.f;
                uint32_t mx = 0;
#pragma unroll
                for (int e = 0; e < 10; e++) {
                    n2 = fmaf(bf_lo(w[e]), bf_lo(w[e]), n2);
                    n2 = fmaf(bf_hi(w[e]), bf_hi(w[e]), n2);
                    mx = max(mx, max(w[e] & 0x7FFFu, (w[e] >> 16) & 0x7FFFu));
                }
                if (!((MUFU_MASK >> ((2 * cta + g) & 7)) & 1)) n2 *= 4.f;
                uint32_t st = lane < 16 ? min(((__float_as_uint(n2) & 0x7FFFFFFFu) + 0xFFFFu) >> 16, 0x7FFFu) : mx;
#pragma unroll
                for (int x = 1; x < 16; x <<= 1) st = max(st, __shfl_xor_sync(~0u, st, x));
                const uint32_t sv = __shfl_sync(~0u, st, 16);
                __syncwarp();
                if (lane == 0) {
                    const unsigned long long f = ((unsigned long long)tag << 32) | (st << 16) | sv;
                    asm volatile("st.release.gpu.global.u64 [%0], %1;" :: "l"(g_flag_kv + cta), "l"(f) : "memory");
                }
                __syncwarp();
                bar_arrive(12, 64);
            }
            TS(17);
        }
        bar_sync(4, 640);
        uint32_t slot = 0;
        const uint4 cz = lds128(sb + OFF_STAT + 16);
#pragma unroll 1
        for (int pass = 0; pass < 2; pass++) {
            uint32_t qf[6];
            const uint32_t qa = sb + OFF_Q + pass * 10240 + r0 * 160 + wg * 40 + q * 4;
            qf[0] = lds32(qa); qf[1] = lds32(qa + 8 * 160);
            qf[2] = lds32(qa + 16); qf[3] = lds32(qa + 8 * 160 + 16);
            qf[4] = q < 2 ? lds32(qa + 32) : 0u; qf[5] = q < 2 ? lds32(qa + 8 * 160 + 32) : 0u;
            if (pass == 0) { count_wait(sb + OFF_PUB, 0, 1); if (wg == 0) { TS(19); TC(26); } }
            float n0 = 0.f, n1 = 0.f;
#pragma unroll
            for (int e = 0; e < 3; e++) {
                n0 = fmaf(bf_lo(qf[2 * e]), bf_lo(qf[2 * e]), fmaf(bf_hi(qf[2 * e]), bf_hi(qf[2 * e]), n0));
                n1 = fmaf(bf_lo(qf[2 * e + 1]), bf_lo(qf[2 * e + 1]), fmaf(bf_hi(qf[2 * e + 1]), bf_hi(qf[2 * e + 1]), n1));
            }
            n0 += __shfl_xor_sync(~0u, n0, 1); n0 += __shfl_xor_sync(~0u, n0, 2);
            n1 += __shfl_xor_sync(~0u, n1, 1); n1 += __shfl_xor_sync(~0u, n1, 2);
            const float k2 = __uint_as_float(lds32(sb + OFF_STAT));
            const uint32_t bad = !(n0 * k2 <= 4000.f && n1 * k2 <= 4000.f);
            uint32_t anybad;
            asm volatile("{\n.reg .pred p, r;\nsetp.ne.u32 p, %1, 0;\nbar.red.or.pred r, %2, 128, p;\nselp.u32 %0, 1, 0, r;\n}" : "=r"(anybad) : "r"(bad), "r"(8 + wg) : "memory");
            float o[12];
#pragma unroll
            for (int k = 0; k < 12; k++) o[k] = 0.f;
            fence_regs(o);
            if (!__shfl_sync(~0u, anybad, 0)) {
                if (q >= 2) qf[4] = qf[5] = q == 2 ? 0x3F803F80u : 0x00003F80u;
                attend<true>(sb, slot, pass, qf, o, cz.x, cz.y, cz.z);
            } else {
                attend<false>(sb, slot, pass, qf, o, cz.x, cz.y, cz.z);
            }
            const float i0 = rcpf(__shfl_sync(~0u, o[8], (lane & ~3) | 2)), i1 = rcpf(__shfl_sync(~0u, o[10], (lane & ~3) | 2));
            const uint32_t ot = opaque_tid(), ol = ot & 31, oq = ot & 3;
            uint8_t* const gx = g_ox + opaque_cta() * 10240;
#pragma unroll
            for (int b = 0; b < 3; b++) {
                if (b < 2 || oq < 2) {
                    const uint32_t v0 = pack_bf16(o[4 * b] * i0, o[4 * b + 1] * i0), v1 = pack_bf16(o[4 * b + 2] * i1, o[4 * b + 3] * i1);
                    const uint32_t col = 20 * (ot >> 7) + 8 * b + 2 * oq;
                    const uint32_t x = (col >> 4) * 2048 + (ot & 96) * 16 + (col & 8) * 16 + (ol >> 2) * 16 + (col & 7) * 2;
                    st_relaxed(gx + x, pass ? v0 : ~0u);
                    st_relaxed(gx + x + 256, pass ? v1 : ~0u);
                    const uint32_t dst = sb + OFF_Q + (pass ? 10240 + x : (((ot & 96) >> 1) + (ol >> 2)) * 160 + col * 2);
                    sts32(dst, v0);
                    sts32(dst + (pass ? 256 : 8 * 160), v1);
                }
            }
            fence_async_smem();
            __syncwarp();
            if (lane == 0) mbar_arrive(sb + BAR_OA + pass * 8);
            if (wg == 0) { TS(20 + pass); TC(27 + pass); }
        }
        TS(22 + wg);
        if (NPASS == 5) {
            const uint32_t ot = opaque_tid(), oc = opaque_cta();
            const int lane = ot & 31, i = oc >> 3, j = oc & 7;
            if (wg != 0) {
                const int u = 4 * (3 - wg) + warp;
                uint4 v[12];
                const uint8_t* src[3];
                uint32_t entry = u + 1;
#pragma unroll
                for (int t = 0; t < 3; t++) {
                    const int s = min(3 * u + t, 34), h = (s * 37) >> 8;
                    const int g = 5 * ((j + 1 + s - 7 * h) & 7) + 4 - h;
                    src[t] = g_ox + (i * 40 + g) * 2048 + lane * 16;
                    entry |= g << (8 * t + 8);
                }
#pragma unroll
                for (int k = 0; k < 12; k++) v[k] = make_uint4(k >= 8 && u == 11 ? 0u : ~0u, 0u, 0u, 0u);
                const uint8_t* const probe = (lane < 8 ? src[0] : lane < 16 ? src[1] : src[2]) - lane * 16 + (lane & 6) * 256 + (lane & 1) * 128 + 368;
                uint32_t wait = u == 11 ? 0xFFFFu : 0xFFFFFFu;
                mbar_wait(sb + BAR_A0, 0);
#pragma unroll 1
                for (uint32_t spin = 0; spin < (1u << 16); spin++) {
                    uint4 p = make_uint4(0u, 0u, 0u, 0u);
                    if (mbar_test(sb + BAR_OA + 8, 0)) wait = 0;
                    if ((wait >> lane) & 1) p = ld_relaxed128(probe);
#pragma unroll
                    for (int k = 0; k < 12; k++) if (!((wait >> (2 * (k & 12))) & 0xFF) && v[k].x == ~0u) v[k] = ld_relaxed128(src[k >> 2] + (k & 3) * 512);
                    wait = __ballot_sync(~0u, p.x == ~0u || p.w == ~0u);
                    bool ok = true;
#pragma unroll
                    for (int k = 0; k < 12; k++) {
                        if (v[k].y == ~0u || v[k].z == ~0u || v[k].w == ~0u) v[k].x = ~0u;
                        ok = ok && v[k].x != ~0u;
                    }
                    if (__all_sync(~0u, ok)) break;
                }
                mbar_wait(sb + BAR_OA + 8, 0);
#pragma unroll
                for (int k = 0; k < 12; k++) sts128(sb + OFF_RING + u * 6144 + k * 512 + lane * 16, v[k].x, v[k].y, v[k].z, v[k].w);
                fence_async_smem();
                __syncwarp();
                if (lane == 0) {
                    uint32_t n;
                    asm volatile("atom.relaxed.cta.shared::cta.add.u32 %0, [%1], 1;" : "=r"(n) : "r"(sb + OFF_QUEUE + 48) : "memory");
                    asm volatile("st.release.cta.shared::cta.u32 [%0], %1;" :: "r"(sb + OFF_QUEUE + n * 4), "r"(entry) : "memory");
                }
                if (wg == 1) TS(10);
            } else {
                float a[40];
                mbar_wait(sb + BAR_WA, 0);
                mbar_wait(sb + BAR_OA + 8, 0);
                TS(30);
                const uint64_t dw = desc(sb + OFF_WA, 2048, SW32 | 16);
                {
                    const uint64_t da = desc(sb + OFF_Q + 10240, 128, 16);
                    WG_FENCE();
#pragma unroll
                    for (int t = 0; t < 5; t++) {
                        const uint32_t g = 5 * j + t;
                        if (t == 0) wg_ss_n80_ta0_tb1_initd(a, da, dw + (g >> 2) * 640 + (g & 3) * 32);
                        else wg_ss_n80_ta0_tb1_d(a, da + 128 * t, dw + (g >> 2) * 640 + (g & 3) * 32);
                    }
                    WG_COMMIT();
                }
#pragma unroll 1
                for (int n = 0; n < 12; n++) {
                    const uint32_t e = __shfl_sync(~0u, queue_wait(sb + OFF_QUEUE + n * 4), 0);
                    const uint64_t da = desc(sb + OFF_RING - 6144 + (e & 15) * 6144, 128, 16);
                    WG_FENCE();
#pragma unroll
                    for (int t = 0; t < 3; t++) {
                        const uint32_t g = (e >> (8 * t + 8)) & 63;
                        wg_ss_n80_ta0_tb1_d(a, da + 128 * t, dw + (g >> 2) * 640 + (g & 3) * 32);
                    }
                    WG_COMMIT();
                }
                WG_WAIT(0);
                fence_regs(a);
                bar_sync(8, 128);
                store_tile(sb + OFF_Q + 10240 + warp * 2560, P.out + (128 * i + 64 + 16 * warp) * 1280 + 80 * j, lane, a);
                TS(11);
            }
        }
    } else {
        asm volatile("setmaxnreg.inc.sync.aligned.u32 128;");
        const uint32_t mrow = 16 * warp + (lane & 15), mcol = lane >> 4;
        const uint32_t xrow = mrow * 160 + mcol * 16, xgrp = (mrow & 7) * 16 + mcol * 128;
#pragma unroll 1
        for (int pass = 0; pass < NPASS; pass++) {
        if (pass == 4) {
        mbar_wait(sb + BAR_KVB, 0);
        TS(7);
        if (tid < 592) {
            const int m = tid - 512, h = m / 20;
            const uint32_t x0 = sb + OFF_KVB + (m >> 3) * 1408 + (m & 7) * 16;
#pragma unroll
            for (int e = 0; e < 5; e++) {
                const uint4 v = lds128(sb + OFF_PST + m * 96 + e * 16);
                const int n = 20 * h + 4 * e;
                sts64(x0 + (n >> 3) * 128 + (n & 4) * 2, pack_bf16(__uint_as_float(v.x), __uint_as_float(v.y)), pack_bf16(__uint_as_float(v.z), __uint_as_float(v.w)));
            }
            sts16(x0 + 1280 + h * 2, (uint16_t)pack_bf16(__uint_as_float(lds32(sb + OFF_PST + m * 96 + 80)), 0.f));
        }
        fence_async_smem();
        bar_sync(6, 128);
#pragma unroll 1
        for (int half = 0; half < 2; half++) linear_out(sb, half, sb + OFF_PK + half * 10240 + xrow, q);
        fence_async_smem();
        __syncwarp();
        if (lane == 0) mbar_arrive(sb + BAR_OB);
        }
        float a[40], b[40];
        gemm_pass(sb, pass, a, b);
        if (pass == 0) {
        TS(1);
        bar_sync(2, 256);
        stage_tile<1>(sb + OFF_Q + xrow, 16, a);
        stage_tile<1>(sb + OFF_Q + 10240 + xrow, 16, b);
        bar_arrive(4, 640);
        TS(2);
        } else if (pass == 1 || pass == 3) {
        TS(pass == 1 ? 3 : 6);
        stage_tile<2>(sb + OFF_PK + (mrow >> 3) * 1280 + xgrp, 128, a);
        stage_tile<2>(sb + OFF_PK + (8 + (mrow >> 3)) * 1280 + xgrp, 128, b);
        } else if (pass == 2) {
        TS(4);
        stage_tile<0>(sb + OFF_V + 128 + (mrow >> 3) * 1536 + xgrp, 128, a);
        stage_tile<0>(sb + OFF_V + 128 + (8 + (mrow >> 3)) * 1536 + xgrp, 128, b);
        {
            const uint32_t x = sb + OFF_V + ((tid - 512) >> 3) * 1536 + (tid & 7) * 16;
            sts128(x, 0x3F80u, 0u, 0u, 0u);
            sts128(x + 11 * 128, 0x3F80u, 0u, 0u, 0u);
        }
        fence_async_smem();
        bar_sync(6, 128);
        {
            float d1[36], d2[16]; zero_regs(d1); zero_regs(d2);
            const uint64_t da = desc(sb + OFF_PK, 1280, 8), db = desc(sb + OFF_V, 1536, 8);
            WG_FENCE();
#pragma unroll
            for (int k = 0; k < 8; k++) {
                wg_ss_n72_ta1_tb1_d(d1, da + 160 * k, db + 192 * k);
                wg_ss_n32_ta1_tb1_d(d2, da + 16 + 160 * k, db + 64 + 192 * k);
            }
            WG_COMMIT();
            WG_WAIT(0);
            fence_regs(d1); fence_regs(d2);
            bar_sync(6, 128);
#pragma unroll
            for (int u = 0; u < 7; u++) if (u < 6 || tid < 624) sts128(sb + OFF_KVB + (tid - 512 + 128 * u) * 16, 0u, 0u, 0u, 0u);
            const uint32_t part = sb + OFF_PST;
#pragma unroll
            for (int hh = 0; hh < 2; hh++) {
                const int m = r0 + 8 * hh;
                if (m < 60) {
                    const int h20 = (m / 20) * 20;
                    if (q == 0) sts128(part + m * 96 + 80, __float_as_uint(d1[2 * hh]), 0u, 0u, 0u);
#pragma unroll
                    for (int k = 1; k < 9; k++) {
                        const int e = 8 * (k - 1) + 2 * q - h20;
                        if (e >= 0 && e < 20) sts64(part + m * 96 + e * 4, __float_as_uint(d1[4 * k + 2 * hh]), __float_as_uint(d1[4 * k + 2 * hh + 1]));
                    }
                }
                if (m >= 44) {
                    if (q == 0) sts128(part + (m + 16) * 96 + 80, __float_as_uint(d2[12 + 2 * hh]), 0u, 0u, 0u);
#pragma unroll
                    for (int k = 0; k < 3; k++) {
                        const int e = 8 * k + 2 * q - 4;
                        if (e >= 0) sts64(part + (m + 16) * 96 + e * 4, __float_as_uint(d2[4 * k + 2 * hh]), __float_as_uint(d2[4 * k + 2 * hh + 1]));
                    }
                }
            }
            fence_async_smem();
            __syncwarp();
            if (lane == 0) mbar_arrive(sb + BAR_PART);
        }
        } else {
        __nv_bfloat16* out = P.out + (128 * i + 16 * warp) * 1280 + 80 * j + 640;
        mbar_wait(sb + BAR_A0, 0);
        store_tile(sb + OFF_Q + warp * 2560, out, lane, a);
        store_tile(sb + OFF_Q + warp * 2560, out + 64 * 1280, lane, b);
        TS(9);
        }
        }
        if (NPASS == 5) {
            mbar_wait(sb + BAR_WA, 0);
            float a[40];
            gemm_half(sb, a);
            store_tile(sb + OFF_Q + warp * 2560, P.out + (128 * i + 16 * warp) * 1280 + 80 * j, lane, a);
            TS(12);
        }
        if (cta == 0 && tid == 512) *(volatile uint32_t*)&g_epoch = tag;
    }
}

typedef CUresult (*EncodeFn)(CUtensorMap*, CUtensorMapDataType, cuuint32_t, void*, const cuuint64_t*, const cuuint64_t*,
                             const cuuint32_t*, const cuuint32_t*, CUtensorMapInterleave, CUtensorMapSwizzle,
                             CUtensorMapL2promotion, CUtensorMapFloatOOBfill);

void make_map(EncodeFn enc, CUtensorMap* m, const void* p, uint32_t box_cols, uint32_t box_rows) {
    cuuint64_t dims[2] = {640, 2048}, strides[1] = {1280};
    cuuint32_t box[2] = {box_cols, box_rows}, es[2] = {1, 1};
    enc(m, CU_TENSOR_MAP_DATA_TYPE_BFLOAT16, 2, const_cast<void*>(p), dims, strides, box, es, CU_TENSOR_MAP_INTERLEAVE_NONE,
        box_cols == 64 ? CU_TENSOR_MAP_SWIZZLE_128B : CU_TENSOR_MAP_SWIZZLE_NONE, CU_TENSOR_MAP_L2_PROMOTION_L2_128B, CU_TENSOR_MAP_FLOAT_OOB_FILL_NONE);
}
void make_x16map(EncodeFn enc, CUtensorMap* m, const void* p) {
    cuuint64_t dims[3] = {64, 2048, 10}, strides[2] = {1280, 128};
    cuuint32_t box[3] = {64, 16, 10}, es[3] = {1, 1, 1};
    enc(m, CU_TENSOR_MAP_DATA_TYPE_BFLOAT16, 3, const_cast<void*>(p), dims, strides, box, es, CU_TENSOR_MAP_INTERLEAVE_NONE,
        CU_TENSOR_MAP_SWIZZLE_128B, CU_TENSOR_MAP_L2_PROMOTION_L2_128B, CU_TENSOR_MAP_FLOAT_OOB_FILL_NONE);
}
void make_wmap(EncodeFn enc, CUtensorMap* m, const void* p, uint64_t cols) {
    cuuint64_t dims[3] = {16, 640, cols / 16}, strides[2] = {cols * 2, 32};
    cuuint32_t box[3] = {16, 64, 5}, es[3] = {1, 1, 1};
    enc(m, CU_TENSOR_MAP_DATA_TYPE_BFLOAT16, 3, const_cast<void*>(p), dims, strides, box, es, CU_TENSOR_MAP_INTERLEAVE_NONE,
        CU_TENSOR_MAP_SWIZZLE_32B, CU_TENSOR_MAP_L2_PROMOTION_L2_128B, CU_TENSOR_MAP_FLOAT_OOB_FILL_NONE);
}

}

extern "C" void kernel_launch(void* const* d_in, const int* in_sizes, int n_in, void* d_out, int out_size) {
    static EncodeFn enc = nullptr;
    static void *oa = nullptr, *ob = nullptr;
    static int sms = 0;
    if (!enc) {
        void* fn = nullptr;
        cudaDriverEntryPointQueryResult qr;
        cudaGetDriverEntryPoint("cuTensorMapEncodeTiled", &fn, cudaEnableDefault, &qr);
        enc = (EncodeFn)fn;
        int dev = 0;
        cudaGetDevice(&dev);
        cudaDeviceGetAttribute(&sms, cudaDevAttrMultiProcessorCount, dev);
        cudaGetSymbolAddress(&oa, g_oa);
        cudaGetSymbolAddress(&ob, g_ob);
        cudaFuncSetAttribute(fused_kernel, cudaFuncAttributeMaxDynamicSharedMemorySize, SMEM_BYTES);
    }
    Params P;
    make_map(enc, &P.xa, d_in[0], 64, 128);
    make_x16map(enc, &P.xa16, d_in[0]);
    make_map(enc, &P.xb, d_in[5], 64, 128);
    make_wmap(enc, &P.wq, d_in[1], 640);
    make_wmap(enc, &P.wqkv, d_in[6], 1920);
    make_wmap(enc, &P.woa, d_in[4], 640);
    make_wmap(enc, &P.wob, d_in[7], 640);
    make_map(enc, &P.oa, oa, 64, 64);
    make_map(enc, &P.ob, ob, 64, 128);
    make_map(enc, &P.oa_st, oa, 80, 64);
    make_map(enc, &P.ob_st, ob, 80, 128);
    for (int k = 0; k < 8; k++) P.in[k] = (const uint8_t*)d_in[k];
    P.out = (__nv_bfloat16*)d_out;
    P.helpers = sms >= NCTA + 4;
    fused_kernel<<<P.helpers ? NCTA + 4 : NCTA, NTHR, SMEM_BYTES, cudaStreamPerThread>>>(P);
}
```

```cpp
#include <cuda_runtime.h>
#include <cuda_bf16.h>
#include <cuda.h>
#include <stdint.h>

namespace {

constexpr int NCTA = 128;
constexpr int NTHR = 768;

constexpr uint32_t OFF_STAGE = 0;
constexpr uint32_t STAGE_BYTES = 26624;
constexpr uint32_t OFF_PK = 79872;
constexpr uint32_t OFF_V = 100352;
constexpr uint32_t OFF_KVB = OFF_V;
constexpr uint32_t OFF_PST = OFF_V + 14336;
constexpr uint32_t OFF_WA = 0;
constexpr uint32_t OFF_XA = 102400;
constexpr uint32_t OFF_RING = 135168;
constexpr uint32_t RING_BYTES = 24576;
constexpr uint32_t OFF_WRAW = OFF_RING;
constexpr uint32_t OFF_KVP = OFF_RING + 51200;
constexpr uint32_t OFF_Q = 208896;
constexpr uint32_t OFF_X16 = OFF_Q;
constexpr uint32_t OFF_MISC = 229376;
constexpr uint32_t OFF_BAR = OFF_MISC;
constexpr uint32_t BAR_FULL_G = OFF_BAR, BAR_EMPTY_G = OFF_BAR + 24, BAR_FULL_KV = OFF_BAR + 48, BAR_EMPTY_KV = OFF_BAR + 72;
constexpr uint32_t BAR_OA = OFF_BAR + 96, BAR_WA = OFF_BAR + 112, BAR_FULL_X = OFF_BAR + 120, BAR_EMPTY_X = OFF_BAR + 152, BAR_A0 = OFF_BAR + 184;
constexpr uint32_t OFF_QUEUE = OFF_BAR + 192;
constexpr uint32_t BAR_PART = OFF_BAR + 264, BAR_KVB = OFF_BAR + 272, BAR_OB = OFF_BAR + 280, BAR_KVIN = OFF_BAR + 288;
constexpr uint32_t OFF_PUB = OFF_BAR + 296;
constexpr uint32_t OFF_STAT = OFF_BAR + 304;
constexpr uint32_t BAR_Q = OFF_BAR + 336, BAR_C0 = OFF_BAR + 352, BAR_WQ = OFF_BAR + 360;
constexpr uint32_t OFF_KST = OFF_MISC + 384;
constexpr uint32_t OFF_TS = OFF_KST + 256;
constexpr uint32_t SMEM_BYTES = OFF_TS + 256;

#define MUFU_MASK 0x4A

#define TAILM 1
#define QK 30
#define CP 0
#define SP 1200
#define GD 700
#define FD 600
#define KVF 1
#define SPN 0
#define WD 4
#define QD 4
#define QDN 10
#define HOLD 0
#define NPASS 5
constexpr float LOG2E = 1.4426950408889634f;
constexpr float QSCALE = 0.22360679774997896f * LOG2E;

struct Params {
    CUtensorMap xa, xa16, wq64, wq16, xb, wqkv, woa, wob, oa, ob, oa_st, ob_st;
    const uint8_t* in[8];
    __nv_bfloat16* out;
    int helpers;
};

}

__device__ __align__(1024) uint8_t g_kv[256 * 768];
__device__ __align__(1024) __nv_bfloat16 g_oa[2048 * 640];
__device__ __align__(1024) __nv_bfloat16 g_ob[2048 * 640];
__device__ __align__(1024) uint8_t g_ox[16 * 40 * 2048];
__device__ __align__(128) float g_part[8 * 1920];
__device__ __align__(1024) unsigned long long g_kt[128 * 384];
__device__ __align__(128) uint32_t g_stat[128];
__device__ __align__(128) uint16_t g_flag_kv[128];
__device__ __align__(128) uint16_t g_flag_b1[128];
__device__ __align__(128) uint16_t g_flag_b2[128];
__device__ __align__(128) uint16_t g_flag_a[128];
__device__ __align__(128) uint16_t g_flag_w[32];
__device__ __align__(1024) uint8_t g_wt[320 * 10240];
__device__ uint32_t g_epoch;
#define TS(k)
#define TC(k)

namespace {

__device__ __forceinline__ void wg_rs_n24_tb1_d(float (&d)[12], uint32_t a0, uint32_t a1, uint32_t a2, uint32_t a3, uint64_t db) {
    asm volatile("{\n.reg .pred p;\nsetp.ne.b32 p, 1, 0;\n"
        "wgmma.mma_async.sync.aligned.m64n24k16.f32.bf16.bf16 {%0, %1, %2, %3, %4, %5, %6, %7, %8, %9, %10, %11}, {%12, %13, %14, %15}, %16, p, 1, 1, 1;\n}\n"
        : "+f"(d[0]), "+f"(d[1]), "+f"(d[2]), "+f"(d[3]), "+f"(d[4]), "+f"(d[5]), "+f"(d[6]), "+f"(d[7]), "+f"(d[8]), "+f"(d[9]), "+f"(d[10]), "+f"(d[11])
        : "r"(a0), "r"(a1), "r"(a2), "r"(a3), "l"(db));
}
__device__ __forceinline__ void wg_rs_n64_tb0_d(float (&d)[32], uint32_t a0, uint32_t a1, uint32_t a2, uint32_t a3, uint64_t db) {
    asm volatile("{\n.reg .pred p;\nsetp.ne.b32 p, 1, 0;\n"
        "wgmma.mma_async.sync.aligned.m64n64k16.f32.bf16.bf16 {%0, %1, %2, %3, %4, %5, %6, %7, %8, %9, %10, %11, %12, %13, %14, %15, %16, %17, %18, %19, %20, %21, %22, %23, %24, %25, %26, %27, %28, %29, %30, %31}, {%32, %33, %34, %35}, %36, p, 1, 1, 0;\n}\n"
        : "+f"(d[0]), "+f"(d[1]), "+f"(d[2]), "+f"(d[3]), "+f"(d[4]), "+f"(d[5]), "+f"(d[6]), "+f"(d[7]), "+f"(d[8]), "+f"(d[9]), "+f"(d[10]), "+f"(d[11]), "+f"(d[12]), "+f"(d[13]), "+f"(d[14]), "+f"(d[15]), "+f"(d[16]), "+f"(d[17]), "+f"(d[18]), "+f"(d[19]), "+f"(d[20]), "+f"(d[21]), "+f"(d[22]), "+f"(d[23]), "+f"(d[24]), "+f"(d[25]), "+f"(d[26]), "+f"(d[27]), "+f"(d[28]), "+f"(d[29]), "+f"(d[30]), "+f"(d[31])
        : "r"(a0), "r"(a1), "r"(a2), "r"(a3), "l"(db));
}
__device__ __forceinline__ void wg_rs_n64_tb0_initd(float (&d)[32], uint32_t a0, uint32_t a1, uint32_t a2, uint32_t a3, uint64_t db) {
    asm volatile("{\n.reg .pred p;\nsetp.ne.b32 p, 0, 0;\n"
        "wgmma.mma_async.sync.aligned.m64n64k16.f32.bf16.bf16 {%0, %1, %2, %3, %4, %5, %6, %7, %8, %9, %10, %11, %12, %13, %14, %15, %16, %17, %18, %19, %20, %21, %22, %23, %24, %25, %26, %27, %28, %29, %30, %31}, {%32, %33, %34, %35}, %36, p, 1, 1, 0;\n}\n"
        : "=f"(d[0]), "=f"(d[1]), "=f"(d[2]), "=f"(d[3]), "=f"(d[4]), "=f"(d[5]), "=f"(d[6]), "=f"(d[7]), "=f"(d[8]), "=f"(d[9]), "=f"(d[10]), "=f"(d[11]), "=f"(d[12]), "=f"(d[13]), "=f"(d[14]), "=f"(d[15]), "=f"(d[16]), "=f"(d[17]), "=f"(d[18]), "=f"(d[19]), "=f"(d[20]), "=f"(d[21]), "=f"(d[22]), "=f"(d[23]), "=f"(d[24]), "=f"(d[25]), "=f"(d[26]), "=f"(d[27]), "=f"(d[28]), "=f"(d[29]), "=f"(d[30]), "=f"(d[31])
        : "r"(a0), "r"(a1), "r"(a2), "r"(a3), "l"(db));
}
__device__ __forceinline__ void wg_ss_n16_ta0_tb1_d(float (&d)[8], uint64_t da, uint64_t db) {
    asm volatile("{\n.reg .pred p;\nsetp.ne.b32 p, 1, 0;\n"
        "wgmma.mma_async.sync.aligned.m64n16k16.f32.bf16.bf16 {%0, %1, %2, %3, %4, %5, %6, %7}, %8, %9, p, 1, 1, 0, 1;\n}\n"
        : "+f"(d[0]), "+f"(d[1]), "+f"(d[2]), "+f"(d[3]), "+f"(d[4]), "+f"(d[5]), "+f"(d[6]), "+f"(d[7])
        : "l"(da), "l"(db));
}
__device__ __forceinline__ void wg_ss_n32_ta1_tb1_d(float (&d)[16], uint64_t da, uint64_t db) {
    asm volatile("{\n.reg .pred p;\nsetp.ne.b32 p, 1, 0;\n"
        "wgmma.mma_async.sync.aligned.m64n32k16.f32.bf16.bf16 {%0, %1, %2, %3, %4, %5, %6, %7, %8, %9, %10, %11, %12, %13, %14, %15}, %16, %17, p, 1, 1, 1, 1;\n}\n"
        : "+f"(d[0]), "+f"(d[1]), "+f"(d[2]), "+f"(d[3]), "+f"(d[4]), "+f"(d[5]), "+f"(d[6]), "+f"(d[7]), "+f"(d[8]), "+f"(d[9]), "+f"(d[10]), "+f"(d[11]), "+f"(d[12]), "+f"(d[13]), "+f"(d[14]), "+f"(d[15])
        : "l"(da), "l"(db));
}
__device__ __forceinline__ void wg_ss_n64_ta0_tb1_d(float (&d)[32], uint64_t da, uint64_t db) {
    asm volatile("{\n.reg .pred p;\nsetp.ne.b32 p, 1, 0;\n"
        "wgmma.mma_async.sync.aligned.m64n64k16.f32.bf16.bf16 {%0, %1, %2, %3, %4, %5, %6, %7, %8, %9, %10, %11, %12, %13, %14, %15, %16, %17, %18, %19, %20, %21, %22, %23, %24, %25, %26, %27, %28, %29, %30, %31}, %32, %33, p, 1, 1, 0, 1;\n}\n"
        : "+f"(d[0]), "+f"(d[1]), "+f"(d[2]), "+f"(d[3]), "+f"(d[4]), "+f"(d[5]), "+f"(d[6]), "+f"(d[7]), "+f"(d[8]), "+f"(d[9]), "+f"(d[10]), "+f"(d[11]), "+f"(d[12]), "+f"(d[13]), "+f"(d[14]), "+f"(d[15]), "+f"(d[16]), "+f"(d[17]), "+f"(d[18]), "+f"(d[19]), "+f"(d[20]), "+f"(d[21]), "+f"(d[22]), "+f"(d[23]), "+f"(d[24]), "+f"(d[25]), "+f"(d[26]), "+f"(d[27]), "+f"(d[28]), "+f"(d[29]), "+f"(d[30]), "+f"(d[31])
        : "l"(da), "l"(db));
}
__device__ __forceinline__ void wg_ss_n72_ta1_tb1_d(float (&d)[36], uint64_t da, uint64_t db) {
    asm volatile("{\n.reg .pred p;\nsetp.ne.b32 p, 1, 0;\n"
        "wgmma.mma_async.sync.aligned.m64n72k16.f32.bf16.bf16 {%0, %1, %2, %3, %4, %5, %6, %7, %8, %9, %10, %11, %12, %13, %14, %15, %16, %17, %18, %19, %20, %21, %22, %23, %24, %25, %26, %27, %28, %29, %30, %31, %32, %33, %34, %35}, %36, %37, p, 1, 1, 1, 1;\n}\n"
        : "+f"(d[0]), "+f"(d[1]), "+f"(d[2]), "+f"(d[3]), "+f"(d[4]), "+f"(d[5]), "+f"(d[6]), "+f"(d[7]), "+f"(d[8]), "+f"(d[9]), "+f"(d[10]), "+f"(d[11]), "+f"(d[12]), "+f"(d[13]), "+f"(d[14]), "+f"(d[15]), "+f"(d[16]), "+f"(d[17]), "+f"(d[18]), "+f"(d[19]), "+f"(d[20]), "+f"(d[21]), "+f"(d[22]), "+f"(d[23]), "+f"(d[24]), "+f"(d[25]), "+f"(d[26]), "+f"(d[27]), "+f"(d[28]), "+f"(d[29]), "+f"(d[30]), "+f"(d[31]), "+f"(d[32]), "+f"(d[33]), "+f"(d[34]), "+f"(d[35])
        : "l"(da), "l"(db));
}
__device__ __forceinline__ void wg_ss_n80_ta0_tb1_d(float (&d)[40], uint64_t da, uint64_t db) {
    asm volatile("{\n.reg .pred p;\nsetp.ne.b32 p, 1, 0;\n"
        "wgmma.mma_async.sync.aligned.m64n80k16.f32.bf16.bf16 {%0, %1, %2, %3, %4, %5, %6, %7, %8, %9, %10, %11, %12, %13, %14, %15, %16, %17, %18, %19, %20, %21, %22, %23, %24, %25, %26, %27, %28, %29, %30, %31, %32, %33, %34, %35, %36, %37, %38, %39}, %40, %41, p, 1, 1, 0, 1;\n}\n"
        : "+f"(d[0]), "+f"(d[1]), "+f"(d[2]), "+f"(d[3]), "+f"(d[4]), "+f"(d[5]), "+f"(d[6]), "+f"(d[7]), "+f"(d[8]), "+f"(d[9]), "+f"(d[10]), "+f"(d[11]), "+f"(d[12]), "+f"(d[13]), "+f"(d[14]), "+f"(d[15]), "+f"(d[16]), "+f"(d[17]), "+f"(d[18]), "+f"(d[19]), "+f"(d[20]), "+f"(d[21]), "+f"(d[22]), "+f"(d[23]), "+f"(d[24]), "+f"(d[25]), "+f"(d[26]), "+f"(d[27]), "+f"(d[28]), "+f"(d[29]), "+f"(d[30]), "+f"(d[31]), "+f"(d[32]), "+f"(d[33]), "+f"(d[34]), "+f"(d[35]), "+f"(d[36]), "+f"(d[37]), "+f"(d[38]), "+f"(d[39])
        : "l"(da), "l"(db));
}
__device__ __forceinline__ void wg_ss_n80_ta0_tb1_initd(float (&d)[40], uint64_t da, uint64_t db) {
    asm volatile("{\n.reg .pred p;\nsetp.ne.b32 p, 0, 0;\n"
        "wgmma.mma_async.sync.aligned.m64n80k16.f32.bf16.bf16 {%0, %1, %2, %3, %4, %5, %6, %7, %8, %9, %10, %11, %12, %13, %14, %15, %16, %17, %18, %19, %20, %21, %22, %23, %24, %25, %26, %27, %28, %29, %30, %31, %32, %33, %34, %35, %36, %37, %38, %39}, %40, %41, p, 1, 1, 0, 1;\n}\n"
        : "=f"(d[0]), "=f"(d[1]), "=f"(d[2]), "=f"(d[3]), "=f"(d[4]), "=f"(d[5]), "=f"(d[6]), "=f"(d[7]), "=f"(d[8]), "=f"(d[9]), "=f"(d[10]), "=f"(d[11]), "=f"(d[12]), "=f"(d[13]), "=f"(d[14]), "=f"(d[15]), "=f"(d[16]), "=f"(d[17]), "=f"(d[18]), "=f"(d[19]), "=f"(d[20]), "=f"(d[21]), "=f"(d[22]), "=f"(d[23]), "=f"(d[24]), "=f"(d[25]), "=f"(d[26]), "=f"(d[27]), "=f"(d[28]), "=f"(d[29]), "=f"(d[30]), "=f"(d[31]), "=f"(d[32]), "=f"(d[33]), "=f"(d[34]), "=f"(d[35]), "=f"(d[36]), "=f"(d[37]), "=f"(d[38]), "=f"(d[39])
        : "l"(da), "l"(db));
}
__device__ __forceinline__ void wg_ss_n88_ta0_tb1_d(float (&d)[44], uint64_t da, uint64_t db) {
    asm volatile("{\n.reg .pred p;\nsetp.ne.b32 p, 1, 0;\n"
        "wgmma.mma_async.sync.aligned.m64n88k16.f32.bf16.bf16 {%0, %1, %2, %3, %4, %5, %6, %7, %8, %9, %10, %11, %12, %13, %14, %15, %16, %17, %18, %19, %20, %21, %22, %23, %24, %25, %26, %27, %28, %29, %30, %31, %32, %33, %34, %35, %36, %37, %38, %39, %40, %41, %42, %43}, %44, %45, p, 1, 1, 0, 1;\n}\n"
        : "+f"(d[0]), "+f"(d[1]), "+f"(d[2]), "+f"(d[3]), "+f"(d[4]), "+f"(d[5]), "+f"(d[6]), "+f"(d[7]), "+f"(d[8]), "+f"(d[9]), "+f"(d[10]), "+f"(d[11]), "+f"(d[12]), "+f"(d[13]), "+f"(d[14]), "+f"(d[15]), "+f"(d[16]), "+f"(d[17]), "+f"(d[18]), "+f"(d[19]), "+f"(d[20]), "+f"(d[21]), "+f"(d[22]), "+f"(d[23]), "+f"(d[24]), "+f"(d[25]), "+f"(d[26]), "+f"(d[27]), "+f"(d[28]), "+f"(d[29]), "+f"(d[30]), "+f"(d[31]), "+f"(d[32]), "+f"(d[33]), "+f"(d[34]), "+f"(d[35]), "+f"(d[36]), "+f"(d[37]), "+f"(d[38]), "+f"(d[39]), "+f"(d[40]), "+f"(d[41]), "+f"(d[42]), "+f"(d[43])
        : "l"(da), "l"(db));
}

#define WG_FENCE() asm volatile("wgmma.fence.sync.aligned;" ::: "memory")
#define WG_COMMIT() asm volatile("wgmma.commit_group.sync.aligned;" ::: "memory")
#define WG_WAIT(n) asm volatile("wgmma.wait_group.sync.aligned %0;" :: "n"(n) : "memory")
template <int NR> __device__ __forceinline__ void fence_regs(float (&d)[NR]) {
#pragma unroll
    for (int i = 0; i < NR; i++) asm volatile("" : "+f"(d[i]) :: "memory");
}
template <int NR> __device__ __forceinline__ void zero_regs(float (&d)[NR]) {
#pragma unroll
    for (int i = 0; i < NR; i++) asm volatile("mov.b32 %0, 0;" : "=f"(d[i]) :: "memory");
}
constexpr uint32_t SW128 = 1u << 30, SW32 = 3u << 30;
__device__ __forceinline__ constexpr uint32_t dlo(uint32_t lbo) { return (lbo >> 4) << 16; }

__device__ __forceinline__ void bar_sync(int id, int n) { asm volatile("bar.sync %0, %1;" :: "r"(id), "r"(n) : "memory"); }
__device__ __forceinline__ void bar_arrive(int id, int n) { asm volatile("bar.arrive %0, %1;" :: "r"(id), "r"(n) : "memory"); }
__device__ __forceinline__ void mbar_init(uint32_t bar, uint32_t cnt) { asm volatile("mbarrier.init.shared::cta.b64 [%0], %1;" :: "r"(bar), "r"(cnt) : "memory"); }
__device__ __forceinline__ void mbar_arrive(uint32_t bar) { asm volatile("mbarrier.arrive.shared::cta.b64 _, [%0];" :: "r"(bar) : "memory"); }
__device__ __forceinline__ void mbar_expect(uint32_t bar, uint32_t bytes) { asm volatile("mbarrier.arrive.expect_tx.shared::cta.b64 _, [%0], %1;" :: "r"(bar), "r"(bytes) : "memory"); }
__device__ __forceinline__ void mbar_wait(uint32_t bar, uint32_t parity) {
    asm volatile("{\n.reg .pred p;\n.reg .u32 n;\nmov.u32 n, 0;\n"
                 "MW_LOOP:\nmbarrier.try_wait.parity.shared::cta.b64 p, [%0], %1;\n@p bra.uni MW_DONE;\n"
                 "add.u32 n, n, 1;\nsetp.lt.u32 p, n, 32768;\n@p bra.uni MW_LOOP;\nMW_DONE:\n}"
                 :: "r"(bar), "r"(parity) : "memory");
}
__device__ __forceinline__ void mbar_spin(uint32_t bar, uint32_t parity) {
    asm volatile("{\n.reg .pred p;\n.reg .u32 n;\nmov.u32 n, 0;\n"
                 "MS_LOOP:\nmbarrier.test_wait.parity.shared::cta.b64 p, [%0], %1;\n@p bra.uni MS_DONE;\n"
                 "add.u32 n, n, 1;\nsetp.lt.u32 p, n, 0x400000;\n@p bra.uni MS_LOOP;\nMS_DONE:\n}"
                 :: "r"(bar), "r"(parity) : "memory");
}
__device__ __forceinline__ bool mbar_test(uint32_t bar, uint32_t parity) {
    uint32_t r;
    asm volatile("{\n.reg .pred p;\nmbarrier.test_wait.parity.shared::cta.b64 p, [%1], %2;\nselp.u32 %0, 1, 0, p;\n}" : "=r"(r) : "r"(bar), "r"(parity) : "memory");
    return r;
}
__device__ __forceinline__ void count_wait(uint32_t addr, uint32_t seen, uint32_t need) {
    asm volatile("{\n.reg .pred p;\n.reg .u32 n, v;\nmov.u32 n, 0;\nmov.u32 v, %1;\n"
                 "CW_LOOP:\nsetp.ge.u32 p, v, %2;\n@p bra.uni CW_DONE;\nld.volatile.shared.u32 v, [%0];\n"
                 "add.u32 n, n, 1;\nsetp.lt.u32 p, n, 0x400000;\n@p bra.uni CW_LOOP;\nCW_DONE:\n}"
                 :: "r"(addr), "r"(seen), "r"(need) : "memory");
}
__device__ __forceinline__ uint32_t queue_wait(uint32_t addr) {
    uint32_t v;
    asm volatile("{\n.reg .pred p;\n.reg .u32 n;\nmov.u32 n, 0;\n"
                 "QW_LOOP:\nld.acquire.cta.shared::cta.u32 %0, [%1];\nsetp.ne.u32 p, %0, 0;\n@p bra.uni QW_DONE;\n"
                 "add.u32 n, n, 1;\nsetp.lt.u32 p, n, 0x400000;\n@p bra.uni QW_LOOP;\nmov.u32 %0, 1;\nQW_DONE:\n}"
                 : "=r"(v) : "r"(addr) : "memory");
    return v;
}
__device__ __forceinline__ void tma2d(uint32_t dst, const CUtensorMap* m, int x, int y, uint32_t bar) {
    asm volatile("cp.async.bulk.tensor.2d.shared::cluster.global.mbarrier::complete_tx::bytes [%0], [%1, {%2, %3}], [%4];"
                 :: "r"(dst), "l"(m), "r"(x), "r"(y), "r"(bar) : "memory");
}
__device__ __forceinline__ void bulk1d(uint32_t dst, const void* src, uint32_t bytes, uint32_t bar) {
    asm volatile("cp.async.bulk.shared::cluster.global.mbarrier::complete_tx::bytes [%0], [%1], %2, [%3];"
                 :: "r"(dst), "l"(src), "r"(bytes), "r"(bar) : "memory");
}
__device__ __forceinline__ void tma3d(uint32_t dst, const CUtensorMap* m, int y, int z, uint32_t bar) {
    asm volatile("cp.async.bulk.tensor.3d.shared::cluster.global.mbarrier::complete_tx::bytes [%0], [%1, {0, %2, %3}], [%4];"
                 :: "r"(dst), "l"(m), "r"(y), "r"(z), "r"(bar) : "memory");
}
__device__ __forceinline__ void tma2d_store(const CUtensorMap* m, int x, int y, uint32_t src) {
    asm volatile("cp.async.bulk.tensor.2d.global.shared::cta.bulk_group [%0, {%1, %2}], [%3];" :: "l"(m), "r"(x), "r"(y), "r"(src) : "memory");
}
__device__ __forceinline__ void bulk_store(void* dst, uint32_t src, uint32_t bytes) {
    asm volatile("cp.async.bulk.global.shared::cta.bulk_group [%0], [%1], %2;" :: "l"(dst), "r"(src), "r"(bytes) : "memory");
}
__device__ __forceinline__ void bulk_add_f32(void* dst, uint32_t src, uint32_t bytes) {
    asm volatile("cp.reduce.async.bulk.global.shared::cta.bulk_group.add.f32 [%0], [%1], %2;" :: "l"(dst), "r"(src), "r"(bytes) : "memory");
}
__device__ __forceinline__ void bulk_commit() { asm volatile("cp.async.bulk.commit_group;" ::: "memory"); }
__device__ __forceinline__ void bulk_wait() {
    asm volatile("cp.async.bulk.wait_group 0;\nfence.proxy.async.global;" ::: "memory");
}
__device__ __forceinline__ void prefetch_l2(const void* p, uint32_t bytes) { asm volatile("cp.async.bulk.prefetch.L2.global [%0], %1;" :: "l"(p), "r"(bytes) : "memory"); }
__device__ __forceinline__ void prefetch_map(const CUtensorMap* m) { asm volatile("prefetch.tensormap [%0];" :: "l"(m) : "memory"); }
__device__ __forceinline__ uint32_t opaque_tid() { uint32_t t; asm volatile("mov.u32 %0, %tid.x;" : "=r"(t) :: "memory"); return t; }
__device__ __forceinline__ uint32_t opaque_cta() { uint32_t t; asm volatile("mov.u32 %0, %ctaid.x;" : "=r"(t) :: "memory"); return t; }
__device__ __forceinline__ bool elect_one() {
    uint32_t p;
    asm volatile("{\n.reg .pred p;\nelect.sync _|p, 0xffffffff;\nselp.u32 %0, 1, 0, p;\n}" : "=r"(p));
    return p;
}
__device__ __forceinline__ void fence_async() { asm volatile("fence.proxy.async.global;" ::: "memory"); }
__device__ __forceinline__ void fence_async_smem() { asm volatile("fence.proxy.async.shared::cta;" ::: "memory"); }
__device__ __forceinline__ void st_flag(uint16_t* p, uint32_t v) { asm volatile("st.release.gpu.global.u16 [%0], %1;" :: "l"(p), "h"((uint16_t)v) : "memory"); }
__device__ __forceinline__ void st_relaxed(void* p, uint32_t v) { asm volatile("st.relaxed.gpu.global.u32 [%0], %1;" :: "l"(p), "r"(v) : "memory"); }
__device__ __forceinline__ void st_relaxed64(void* p, unsigned long long v) { asm volatile("st.relaxed.gpu.global.u64 [%0], %1;" :: "l"(p), "l"(v) : "memory"); }
__device__ __forceinline__ uint4 ld_relaxed2x64(const void* p) {
    uint4 v;
    asm volatile("{\n.reg .b64 a, b;\nld.relaxed.gpu.global.v2.u64 {a, b}, [%4];\nmov.b64 {%0, %1}, a;\nmov.b64 {%2, %3}, b;\n}" : "=r"(v.x), "=r"(v.y), "=r"(v.z), "=r"(v.w) : "l"(p) : "memory");
    return v;
}
__device__ __forceinline__ uint4 ld_relaxed128(const void* p) { uint4 v; asm volatile("ld.relaxed.gpu.global.v4.u32 {%0, %1, %2, %3}, [%4];" : "=r"(v.x), "=r"(v.y), "=r"(v.z), "=r"(v.w) : "l"(p) : "memory"); return v; }
__device__ __forceinline__ uint4 ld_acquire128(const void* p) { uint4 v; asm volatile("ld.acquire.gpu.global.v4.u32 {%0, %1, %2, %3}, [%4];" : "=r"(v.x), "=r"(v.y), "=r"(v.z), "=r"(v.w) : "l"(p) : "memory"); return v; }
__device__ __forceinline__ void poll1(const uint16_t* p, uint32_t tag) {
#pragma unroll 1
    for (uint32_t spin = 0; spin < (1u << 17); spin++) {
        uint16_t v;
        asm volatile("ld.acquire.gpu.global.u16 %0, [%1];" : "=h"(v) : "l"(p) : "memory");
        if (v == (uint16_t)tag) break;
    }
    fence_async();
}
__device__ __forceinline__ void poll8(const uint16_t* p, uint32_t tag) {
    const uint32_t t2 = (tag & 0xFFFFu) * 0x10001u;
#pragma unroll 1
    for (uint32_t spin = 0; spin < (1u << 17); spin++) {
        const uint4 a = ld_acquire128(p);
        if (a.x == t2 && a.y == t2 && a.z == t2 && a.w == t2) break;
    }
    fence_async();
}
__device__ __forceinline__ uint32_t lds32(uint32_t a) { uint32_t v; asm volatile("ld.shared.u32 %0, [%1];" : "=r"(v) : "r"(a) : "memory"); return v; }
__device__ __forceinline__ void sts32(uint32_t a, uint32_t v) { asm volatile("st.shared.u32 [%0], %1;" :: "r"(a), "r"(v) : "memory"); }
__device__ __forceinline__ void sts16(uint32_t a, uint16_t v) { asm volatile("st.shared.u16 [%0], %1;" :: "r"(a), "h"(v) : "memory"); }
__device__ __forceinline__ void sts64(uint32_t a, uint32_t x, uint32_t y) { asm volatile("st.shared.v2.u32 [%0], {%1, %2};" :: "r"(a), "r"(x), "r"(y) : "memory"); }
__device__ __forceinline__ void sts128(uint32_t a, uint32_t x, uint32_t y, uint32_t z, uint32_t w) { asm volatile("st.shared.v4.u32 [%0], {%1, %2, %3, %4};" :: "r"(a), "r"(x), "r"(y), "r"(z), "r"(w) : "memory"); }
__device__ __forceinline__ uint2 lds64(uint32_t a) { uint2 v; asm volatile("ld.shared.v2.u32 {%0, %1}, [%2];" : "=r"(v.x), "=r"(v.y) : "r"(a) : "memory"); return v; }
__device__ __forceinline__ uint4 lds128(uint32_t a) { uint4 v; asm volatile("ld.shared.v4.u32 {%0, %1, %2, %3}, [%4];" : "=r"(v.x), "=r"(v.y), "=r"(v.z), "=r"(v.w) : "r"(a) : "memory"); return v; }
__device__ __forceinline__ float ex2f(float x) { float y; asm("ex2.approx.ftz.f32 %0, %1;" : "=f"(y) : "f"(x)); return y; }
__device__ __forceinline__ float rcpf(float x) { float y; asm("rcp.approx.ftz.f32 %0, %1;" : "=f"(y) : "f"(x)); return y; }
__device__ __forceinline__ void stsm4(uint32_t a, uint32_t x, uint32_t y, uint32_t z, uint32_t w) {
    asm volatile("stmatrix.sync.aligned.m8n8.x4.shared.b16 [%0], {%1, %2, %3, %4};" :: "r"(a), "r"(x), "r"(y), "r"(z), "r"(w) : "memory");
}
__device__ __forceinline__ uint32_t pack_bf16(float lo, float hi) { uint32_t r; asm("cvt.rn.bf16x2.f32 %0, %1, %2;" : "=r"(r) : "f"(hi), "f"(lo)); return r; }
__device__ __forceinline__ float bf_lo(uint32_t v) { return __uint_as_float(v << 16); }
__device__ __forceinline__ float bf_hi(uint32_t v) { return __uint_as_float(v & 0xFFFF0000u); }
__device__ __forceinline__ uint32_t phi2(float t0, float t1) {
    uint32_t r;
    asm("{\n.reg .b32 one, eps, p, e;\nmov.b32 one, 0x3F803F80;\nmov.b32 eps, 0x35863586;\n"
        "add.rn.bf16x2 p, %1, one;\nmin.bf16x2 e, %2, one;\nmax.NaN.bf16x2 p, p, e;\nadd.rn.bf16x2 %0, p, eps;\n}"
        : "=r"(r) : "r"(pack_bf16(t0, t1)), "r"(pack_bf16(ex2f(t0 * LOG2E), ex2f(t1 * LOG2E))));
    return r;
}
template <int MODE> __device__ __forceinline__ void stage_tile(uint32_t x, uint32_t step, const float (&a)[40]) {
#pragma unroll
    for (int k = 0; k < 5; k++) {
        uint32_t r[4];
#pragma unroll
        for (int e = 0; e < 4; e++) {
            const float t0 = a[8 * k + 2 * e], t1 = a[8 * k + 2 * e + 1];
            r[e] = MODE == 0 ? pack_bf16(t0, t1) : MODE == 1 ? pack_bf16(t0 * QSCALE, t1 * QSCALE) : phi2(t0, t1);
        }
        stsm4(x + 2 * k * step, r[0], r[1], r[2], r[3]);
    }
}

__device__ __forceinline__ uint32_t exp2_pair(float t0, float t1, uint32_t ca) {
    uint32_t y, u, g;
    asm("prmt.b32 %0, %1, %2, 0x6521;" : "=r"(y) : "r"(__float_as_uint(t0)), "r"(__float_as_uint(t1)));
    u = y & 0x007F007Fu;
    asm("{.reg .b32 c; mov.b32 c, 0xF963F963; fma.rn.f16x2 %0, %1, c, %2;}" : "=r"(g) : "r"(u), "r"(ca));
    asm("mul.rn.f16x2 %0, %1, %2;" : "=r"(g) : "r"(g), "r"(u));
    return y - g;
}

__device__ __forceinline__ uint64_t desc(uint32_t addr, uint32_t lbo, uint32_t hi) { return ((uint64_t)hi << 32) | ((addr >> 4) + dlo(lbo)); }
template <int J> __device__ __forceinline__ void exp_steps(const float (&s)[32], uint32_t (&p)[16], float (&o)[12], uint64_t& dv, uint32_t ca) {
    if constexpr (J < 4) {
#pragma unroll
        for (int g = 2 * J; g < 2 * J + 2; g++) {
            if ((MUFU_MASK >> g) & 1) {
                p[2 * g] = pack_bf16(ex2f(s[4 * g]), ex2f(s[4 * g + 1]));
                p[2 * g + 1] = pack_bf16(ex2f(s[4 * g + 2]), ex2f(s[4 * g + 3]));
            } else {
                p[2 * g] = exp2_pair(s[4 * g], s[4 * g + 1], ca);
                p[2 * g + 1] = exp2_pair(s[4 * g + 2], s[4 * g + 3], ca);
            }
        }
        WG_FENCE();
        wg_rs_n24_tb1_d(o, p[4 * J], p[4 * J + 1], p[4 * J + 2], p[4 * J + 3], dv);
        dv += 96;
        exp_steps<J + 1>(s, p, o, dv, ca);
    }
}

struct Ring { uint32_t slot, phase; };
__device__ __forceinline__ void next_stage(Ring& r) { if (++r.slot == 3) { r.slot = 0; r.phase ^= 1; } }

#define BUNR 4
template <bool FAST>
__device__ __forceinline__ void attend(uint32_t sb, uint32_t& slot, int pass, const uint32_t (&q)[6], float (&o)[12], uint32_t ca, uint32_t z0, uint32_t z1) {
    float m0 = -INFINITY, m1 = -INFINITY;
    constexpr int UNR = FAST ? BUNR : 1;
#pragma unroll 1
    for (int c = 0; c < 8; c++) {
        const uint32_t base = sb + OFF_RING + slot * RING_BYTES;
        uint64_t dk = desc(base, 128, 768 >> 4), dv = desc(base + 384, 768, 128 >> 4);
        uint32_t seen;
#pragma unroll UNR
        for (int b = 0; b < 4; b++) {
            float s[32];
            uint32_t p[16];
            WG_FENCE();
            wg_rs_n64_tb0_initd(s, q[0], q[1], q[2], q[3], dk);
            dk += 16;
            wg_rs_n64_tb0_d(s, q[4], q[5], z0, z1, dk);
            dk += 368;
            WG_COMMIT();
            if (UNR < 4 || b == 3) seen = lds32(sb + OFF_PUB);
            WG_WAIT(0);
            fence_regs(s);
            if constexpr (FAST) {
                exp_steps<0>(s, p, o, dv, ca);
            } else {
                fence_regs(o);
                float x0 = m0, x1 = m1;
#pragma unroll
                for (int g = 0; g < 8; g++) {
                    if (!((MUFU_MASK >> g) & 1)) {
#pragma unroll
                        for (int e = 0; e < 4; e++) s[4 * g + e] *= 2.f;
                    }
                    x0 = fmaxf(x0, fmaxf(s[4 * g], s[4 * g + 1]));
                    x1 = fmaxf(x1, fmaxf(s[4 * g + 2], s[4 * g + 3]));
                }
                x0 = fmaxf(x0, __shfl_xor_sync(~0u, x0, 1)); x0 = fmaxf(x0, __shfl_xor_sync(~0u, x0, 2));
                x1 = fmaxf(x1, __shfl_xor_sync(~0u, x1, 1)); x1 = fmaxf(x1, __shfl_xor_sync(~0u, x1, 2));
                const float a0 = ex2f(m0 - x0), a1 = ex2f(m1 - x1);
                m0 = x0; m1 = x1;
#pragma unroll
                for (int b = 0; b < 3; b++) { o[4 * b] *= a0; o[4 * b + 1] *= a0; o[4 * b + 2] *= a1; o[4 * b + 3] *= a1; }
#pragma unroll
                for (int g = 0; g < 8; g++) {
                    p[2 * g] = pack_bf16(ex2f(s[4 * g] - x0), ex2f(s[4 * g + 1] - x0));
                    p[2 * g + 1] = pack_bf16(ex2f(s[4 * g + 2] - x1), ex2f(s[4 * g + 3] - x1));
                }
            }
            if constexpr (!FAST) {
                WG_FENCE();
#pragma unroll
                for (int k = 0; k < 4; k++) { wg_rs_n24_tb1_d(o, p[4 * k], p[4 * k + 1], p[4 * k + 2], p[4 * k + 3], dv); dv += 96; }
            }
            WG_COMMIT();
            WG_WAIT(0);
            fence_regs(o);
        }
        if ((threadIdx.x & 31) == 0) mbar_arrive(sb + BAR_EMPTY_KV + slot * 8);
        slot = slot == 2 ? 0 : slot + 1;
        count_wait(sb + OFF_PUB, seen, min(pass * 8 + c + 2, 16));
    }
}

__device__ __forceinline__ void gemm_pass(uint32_t sb, int pass, float (&a)[40], float (&b)[40]) {
    zero_regs(a); zero_regs(b);
    const uint32_t n0 = (__shfl_sync(~0u, pass, 0) - 1) * 10;
    uint32_t slot = n0 % 3, phase = (n0 / 3) & 1;
    const bool lead = (threadIdx.x & 31) == 0;
#pragma unroll 1
    for (int c = 0; c < 10; c++) {
        mbar_wait(sb + BAR_FULL_G + slot * 8, phase);
        const uint32_t st = sb + OFF_STAGE + slot * STAGE_BYTES;
        const uint64_t dx = desc(st, 16, SW128 | 64), dw = desc(st + 16384, 2048, SW32 | 16);
        WG_FENCE();
#pragma unroll
        for (int k = 0; k < 4; k++) {
            wg_ss_n80_ta0_tb1_d(a, dx + 2 * k, dw + 32 * k);
            wg_ss_n80_ta0_tb1_d(b, dx + 512 + 2 * k, dw + 32 * k);
        }
        WG_COMMIT();
        WG_WAIT(0);
        if (lead) mbar_arrive(sb + BAR_EMPTY_G + slot * 8);
        if (++slot == 3) { slot = 0; phase ^= 1; }
    }
    fence_regs(a); fence_regs(b);
}

template <bool SPLIT> __device__ __forceinline__ void gemm_half(uint32_t sb, uint32_t n0_, float (&a)[40]) {
    zero_regs(a);
    const uint32_t n0 = __shfl_sync(~0u, n0_, 0);
    const bool lead = (threadIdx.x & 31) == 0;
#pragma unroll 1
    for (uint32_t c = 0; c < 10; c++) {
        const uint32_t n = n0 + c;
        if (SPLIT && WD == 4 && (n == 4 || n == 7)) mbar_wait(sb + BAR_WQ + (n == 4 ? 0 : 8), 0);
        if (SPLIT && (SPN & 8)) mbar_spin(sb + BAR_FULL_X + (n & 3) * 8, (n >> 2) & 1); else mbar_wait(sb + BAR_FULL_X + (n & 3) * 8, (n >> 2) & 1);
        const uint64_t dx = desc(sb + OFF_XA + (n & 3) * 8192, 16, SW128 | 64), dw = desc(sb + OFF_WA + c * 10240 + (SPLIT ? 8192 : 0), 2048, SW32 | 16);
        const uint64_t dv = desc(sb + OFF_WA + c * 10240, 8192, SW128 | 64);
        WG_FENCE();
#pragma unroll
        for (int k = 0; k < 4; k++) {
            if constexpr (SPLIT) {
                wg_ss_n64_ta0_tb1_d(*reinterpret_cast<float(*)[32]>(&a[0]), dx + 2 * k, dv + 128 * k);
                wg_ss_n16_ta0_tb1_d(*reinterpret_cast<float(*)[8]>(&a[32]), dx + 2 * k, dw + 32 * k);
            } else {
                wg_ss_n80_ta0_tb1_d(a, dx + 2 * k, dw + 32 * k);
            }
        }
        WG_COMMIT();
        WG_WAIT(1);
        if (lead && c) mbar_arrive(sb + BAR_EMPTY_X + ((n - 1) & 3) * 8);
    }
    WG_WAIT(0);
    if (lead) mbar_arrive(sb + BAR_EMPTY_X + ((n0 + 9) & 3) * 8);
    fence_regs(a);
}

__device__ __forceinline__ void mma16816(float (&d)[4], uint32_t a0, uint32_t a1, uint32_t a2, uint32_t a3, uint32_t b0, uint32_t b1) {
    asm volatile("mma.sync.aligned.m16n8k16.row.col.f32.bf16.bf16.f32 {%0, %1, %2, %3}, {%4, %5, %6, %7}, {%8, %9}, {%0, %1, %2, %3};"
                 : "+f"(d[0]), "+f"(d[1]), "+f"(d[2]), "+f"(d[3]) : "r"(a0), "r"(a1), "r"(a2), "r"(a3), "r"(b0), "r"(b1));
}

__device__ __forceinline__ void store_tile(uint32_t stage, __nv_bfloat16* dst, int lane, const float (&a)[40]) {
    stage_tile<0>(stage + (lane & 15) * 160 + (lane >> 4) * 16, 16, a);
    __syncwarp();
#pragma unroll
    for (int u = 0; u < 5; u++) {
        const int x = lane + 32 * u, row = (x * 205) >> 11;
        const uint4 v = lds128(stage + x * 16);
        *reinterpret_cast<uint4*>(dst + row * (1280 - 80) + x * 8) = v;
    }
    __syncwarp();
}

__device__ __forceinline__ void linear_out(uint32_t sb, int half, uint32_t dst, int q) {
    float d[44]; zero_regs(d);
    const uint64_t da = desc(sb + OFF_PK + half * 10240, 128, 80), db = desc(sb + OFF_KVB, 1408, 8);
    WG_FENCE();
#pragma unroll
    for (int k = 0; k < 5; k++) wg_ss_n88_ta0_tb1_d(d, da + 16 * k, db + 176 * k);
    WG_COMMIT();
    WG_WAIT(0);
    fence_regs(d);
    bar_sync(6, 128);
    float r0[4], r1[4];
    const int base = (threadIdx.x & 31) & ~3;
#pragma unroll
    for (int e = 0; e < 4; e++) d[40 + e] = rcpf(d[40 + e] + 1e-6f);
#pragma unroll
    for (int h = 0; h < 4; h++) {
        r0[h] = __shfl_sync(~0u, d[40 + (h & 1)], base + (h >> 1));
        r1[h] = __shfl_sync(~0u, d[42 + (h & 1)], base + (h >> 1));
    }
    uint32_t r[20];
#pragma unroll
    for (int b = 0; b < 10; b++) {
        const int hl = (8 * b) / 20, hh = (8 * b + 6) / 20;
        const bool up = hl != hh && q >= 2;
        const float s0 = up ? r0[hh] : r0[hl], s1 = up ? r1[hh] : r1[hl];
        r[2 * b] = pack_bf16(d[4 * b] * s0, d[4 * b + 1] * s0);
        r[2 * b + 1] = pack_bf16(d[4 * b + 2] * s1, d[4 * b + 3] * s1);
    }
#pragma unroll
    for (int k = 0; k < 5; k++) stsm4(dst + 32 * k, r[4 * k], r[4 * k + 1], r[4 * k + 2], r[4 * k + 3]);
}

__global__ void __launch_bounds__(NTHR, 1) fused_kernel(const __grid_constant__ Params P) {
    extern __shared__ __align__(1024) uint8_t smem[];
    const uint32_t sb = (uint32_t)__cvta_generic_to_shared(smem);
    const int tid = threadIdx.x, lane = tid & 31;
    const int wg = __shfl_sync(~0u, tid >> 7, 0), warp = __shfl_sync(~0u, (tid >> 5) & 3, 0);
    const int cta = blockIdx.x, i = cta >> 3, j = cta & 7;
    const int q = lane & 3, r0 = 16 * warp + (lane >> 2);
    if (wg == 4 || wg == 0) TS(wg == 4 ? 0 : 16);

    const uint32_t tag = *(volatile uint32_t*)&g_epoch + 1;

    if (cta >= NCTA) {
        if (tid < 64 && elect_one()) {
            const int jj = 2 * (cta - NCTA) + warp;
            const uint32_t buf = sb + warp * 102400, bar = sb + OFF_BAR + warp * 80;
#pragma unroll 1
            for (int s = 0; s < 10; s++) mbar_init(bar + s * 8, 1);
            asm volatile("fence.mbarrier_init.release.cluster;" ::: "memory");
            int lp = 0, lc = 0;
#pragma unroll 1
            for (int n = -8; n < 40; n++) {
                if (n >= 0) {
                    const int part = n / 10, c = n - 10 * part;
                    mbar_wait(bar + c * 8, part & 1);
                    bulk_store(g_wt + ((part * 8 + jj) * 10 + c) * 10240, buf + c * 10240, 10240);
                    bulk_commit();
                    if (c == 9) { bulk_wait(); st_flag(g_flag_w + part * 8 + jj, tag); }
                    else asm volatile("cp.async.bulk.wait_group.read 2;" ::: "memory");
                }
                if (lp < 4) {
                    mbar_expect(bar + lc * 8, 10240);
                    tma3d(buf + lc * 10240, lp < 2 ? &P.wqkv : lp == 2 ? &P.wob : &P.woa, 64 * lc, 5 * jj + (lp == 0 ? 80 : 0), bar + lc * 8);
                    if (++lc == 10) { lc = 0; lp++; }
                }
            }
        }
        return;
    }
    if (tid == 640) {
        mbar_init(sb + BAR_KVIN, 1);
        asm volatile("fence.mbarrier_init.release.cluster;" ::: "memory");
        mbar_expect(sb + BAR_KVIN, 51200 + 20480);
        tma3d(sb + OFF_X16, &P.xa16, 16 * cta, 0, sb + BAR_KVIN);
#pragma unroll
        for (int u = 0; u < 4; u++) {
            const int v = (u + cta) & 3;
            bulk1d(sb + OFF_WRAW + v * 12800, P.in[2 + (v >> 1)] + (v & 1) * 12800, 12800, sb + BAR_KVIN);
        }
    } else if (tid == 672) {
#pragma unroll
        for (int s = 0; s < 3; s++) {
            mbar_init(sb + BAR_FULL_G + s * 8, 2);
            mbar_init(sb + BAR_EMPTY_G + s * 8, 4);
            mbar_init(sb + BAR_FULL_KV + s * 8, 1);
            mbar_init(sb + BAR_EMPTY_KV + s * 8, 16);
        }
        mbar_init(sb + BAR_OA, 16);
        mbar_init(sb + BAR_OA + 8, 16);
        asm volatile("fence.mbarrier_init.release.cluster;" ::: "memory");
    } else if (tid == 704) {
        prefetch_map(&P.xa);
        prefetch_map(&P.wq64);
        prefetch_map(&P.wq16);
        prefetch_l2(P.in[1] + cta * 6400, 6400);
        mbar_init(sb + BAR_WA, 1);
        mbar_init(sb + BAR_PART, 4);
        mbar_init(sb + BAR_KVB, 1);
        mbar_init(sb + BAR_OB, 4);
        sts32(sb + OFF_PUB, 0);
        sts128(sb + OFF_STAT + 16, 0x357F357Fu, 0u, 0u, 0u);
        asm volatile("fence.mbarrier_init.release.cluster;" ::: "memory");
    } else if (tid == 736) {
#pragma unroll
        for (int s = 0; s < 4; s++) { mbar_init(sb + BAR_FULL_X + s * 8, 1); mbar_init(sb + BAR_EMPTY_X + s * 8, 4); }
#pragma unroll
        for (int s = 0; s < 4; s++) sts128(sb + OFF_QUEUE + s * 16, 0u, 0u, 0u, 0u);
        mbar_init(sb + BAR_A0, 1);
        mbar_init(sb + BAR_Q, 4);
        mbar_init(sb + BAR_Q + 8, 4);
        mbar_init(sb + BAR_C0, 16);
        for (int s = 0; s < 2; s++) mbar_init(sb + BAR_WQ + s * 8, 1);
        asm volatile("fence.mbarrier_init.release.cluster;" ::: "memory");
    }
    __syncthreads();

    if (wg == 5) {
        asm volatile("setmaxnreg.dec.sync.aligned.u32 32;");
        if (warp == 0) {
            if (elect_one()) {
#pragma unroll 1
                for (int n = 0; n < 20; n++) {
                    const uint32_t s = n & 3, bar = sb + BAR_FULL_X + s * 8;
                    if (n == 10) count_wait(sb + OFF_PUB, 0, HOLD);
                    if (n >= QD && n < QDN) mbar_wait(sb + BAR_FULL_X + ((n - QD) & 3) * 8, ((n - QD) >> 2) & 1);
                    if (n >= 4) { if (SPN & 8) mbar_spin(sb + BAR_EMPTY_X + s * 8, ((n >> 2) - 1) & 1); else mbar_wait(sb + BAR_EMPTY_X + s * 8, ((n >> 2) - 1) & 1); }
                    mbar_expect(bar, n < WD ? 18432 : 8192);
                    tma2d(sb + OFF_XA + s * 8192, &P.xa, n < 10 ? 64 * n : 64 * n - 640, 128 * i + (n < 10 ? 0 : 64), bar);
                    if (n < WD) {
                        tma2d(sb + OFF_WA + n * 10240, &P.wq64, 80 * j, 64 * n, bar);
                        tma2d(sb + OFF_WA + n * 10240 + 8192, &P.wq16, 80 * j + 64, 64 * n, bar);
                    }
                    if (WD == 4 && n == 3) {
                        mbar_expect(sb + BAR_WQ, 30720);
                        mbar_expect(sb + BAR_WQ + 8, 30720);
#pragma unroll 1
                        for (int c = 4; c < 10; c++) {
                            tma2d(sb + OFF_WA + c * 10240, &P.wq64, 80 * j, 64 * c, sb + BAR_WQ + (c < 7 ? 0 : 8));
                            tma2d(sb + OFF_WA + c * 10240 + 8192, &P.wq16, 80 * j + 64, 64 * c, sb + BAR_WQ + (c < 7 ? 0 : 8));
                        }
                    }
                }
                Ring r{0, 0};
#pragma unroll 1
                for (int pass = 1; pass < NPASS; pass++) {
                    const CUtensorMap* m = pass <= 3 ? &P.xb : &P.ob;
                    if (pass == 4) {
                        mbar_wait(sb + BAR_OB, 0);
                        tma2d_store(&P.ob_st, 80 * j, 128 * i, sb + OFF_PK);
                        bulk_commit();
                        bulk_wait();
                        st_flag(g_flag_b2 + cta, tag);
                        poll8(g_flag_b2 + i * 8, tag);
                    }
#pragma unroll 1
                    for (int c = 0; c < 10; c++) {
                        if (pass == 3 && c == 3) {
                            mbar_wait(sb + BAR_PART, 0);
                            bulk_add_f32(g_part + j * 1920, sb + OFF_PST, 7680);
                            bulk_commit();
                        }
                        mbar_wait(sb + BAR_EMPTY_G + r.slot * 8, r.phase);
                        mbar_expect(sb + BAR_FULL_G + r.slot * 8, 16384);
                        tma2d(sb + OFF_STAGE + r.slot * STAGE_BYTES, m, 64 * c, 128 * i, sb + BAR_FULL_G + r.slot * 8);
                        next_stage(r);
                        if (pass == 3 && c == 3) {
                            bulk_wait();
                            st_flag(g_flag_b1 + j * 16 + i, tag);
                        }
                    }
                }
                if (NPASS == 5) {
                    poll8(g_flag_a + i * 8, tag);
                    mbar_arrive(sb + BAR_A0);
#pragma unroll 1
                    for (int c = 0; c < 10; c++) {
                        const uint32_t s = c & 3;
                        mbar_wait(sb + BAR_EMPTY_X + s * 8, (c >> 2) & 1);
                        mbar_expect(sb + BAR_FULL_X + s * 8, 8192);
                        tma2d(sb + OFF_XA + s * 8192, &P.oa, 64 * c, 128 * i, sb + BAR_FULL_X + s * 8);
                    }
                }
            }
        } else if (warp == 2) {
            if (elect_one()) {
                Ring r{0, 0};
#pragma unroll 1
                for (int pass = 1; pass < NPASS; pass++) {
                    const CUtensorMap* m = pass <= 3 ? &P.wqkv : &P.wob;
                    const int col = 5 * j + (pass == 1 ? 40 : pass == 2 ? 80 : 0);
                    const bool pre = pass >= 2 && P.helpers;
                    if (pre) poll1(g_flag_w + (pass - 2) * 8 + j, tag);
#pragma unroll 1
                    for (int c = 0; c < 10; c++) {
                        mbar_wait(sb + BAR_EMPTY_G + r.slot * 8, r.phase);
                        const uint32_t bar = sb + BAR_FULL_G + r.slot * 8;
                        mbar_expect(bar, 10240);
                        const uint32_t dst = sb + OFF_STAGE + r.slot * STAGE_BYTES + 16384;
                        if (pre) bulk1d(dst, g_wt + (((pass - 2) * 8 + j) * 10 + c) * 10240, 10240, bar);
                        else tma3d(dst, m, 64 * c, col, bar);
                        next_stage(r);
                    }
                }
                if (NPASS == 5) {
                    if (P.helpers) poll1(g_flag_w + 24 + j, tag);
#pragma unroll 1
                    for (int c = 0; c < 3; c++) { mbar_wait(sb + BAR_EMPTY_G + r.slot * 8, r.phase); next_stage(r); }
                    mbar_expect(sb + BAR_WA, 102400);
                    if (P.helpers) bulk1d(sb + OFF_WA, g_wt + (24 + j) * 102400, 102400, sb + BAR_WA);
                    else {
#pragma unroll 1
                        for (int c = 0; c < 10; c++) tma3d(sb + OFF_WA + c * 10240, &P.woa, 64 * c, 5 * j, sb + BAR_WA);
                    }
                }
            }
        } else if (warp == 3) {
            bar_sync(12, SP ? 96 : 64);
            if (elect_one()) {
                st_flag(g_flag_kv + cta, tag);
                prefetch_l2(P.in[5] + cta * 20480, 20480);
#pragma unroll 1
                for (int u = 0; u < 5; u++) prefetch_l2(P.in[6] + (cta * 5 + u) * 3840 + 1280, 1280);
            }
            __syncwarp();
            if (NPASS == 5) {
                if (elect_one()) {
                    poll8(g_flag_b1 + j * 16, tag);
                    poll8(g_flag_b1 + j * 16 + 8, tag);
                    mbar_expect(sb + BAR_KVB, 7680);
                    bulk1d(sb + OFF_PST, g_part + j * 1920, 7680, sb + BAR_KVB);
                }
            }
            if (elect_one()) {
                mbar_wait(sb + BAR_OA, 0);
                tma2d_store(&P.oa_st, 80 * j, 128 * i, sb + OFF_Q);
                bulk_commit();
                bulk_wait();
                st_flag(g_flag_a + cta, tag);
            }
        } else if (warp == 1) {
            uint32_t sk, spin = 0;
            bar_sync(12, 96);
            __nanosleep(SP);
#pragma unroll 1
            while (true) {
                const uint4 f = ld_relaxed128(g_stat + 4 * lane);
                const uint32_t t = tag << 16;
                sk = max(max(f.x ^ t, f.y ^ t), max(f.z ^ t, f.w ^ t));
                sk = __reduce_max_sync(~0u, sk);
                if (sk < 0x10000u || ++spin > (1u << 17)) break;
            }
            if (lane == 0) {
                sts32(sb + OFF_STAT, sk << 16);
            }
            if (SPN & 1) mbar_spin(sb + BAR_C0, 0); else mbar_wait(sb + BAR_C0, 0);
            if (lane == 0) {
                mbar_arrive(sb + BAR_FULL_KV);
                asm volatile("st.release.cta.shared::cta.u32 [%0], %1;" :: "r"(sb + OFF_PUB), "r"(1) : "memory");
            }
            __syncwarp();
            if (FD) __nanosleep(FD);
            const uint32_t t2 = (tag & 0xFFFFu) * 0x10001u;
#pragma unroll 1
            for (spin = 0; spin < (1u << 17); spin++) {
                const uint4 f = ld_acquire128(g_flag_kv + 8 * (lane & 15));
                if (__all_sync(~0u, f.x == t2 && f.y == t2 && f.z == t2 && f.w == t2)) break;
            }
            if (elect_one()) {
                fence_async();
                const uint32_t rot = i >> 1;
#pragma unroll 1
                for (int n = 1; n < 3; n++) {
                    mbar_expect(sb + BAR_FULL_KV + n * 8, RING_BYTES);
                    bulk1d(sb + OFF_RING + n * RING_BYTES, g_kv + ((n + rot) & 7) * RING_BYTES, RING_BYTES, sb + BAR_FULL_KV + n * 8);
                }
                Ring r{1, 0};
#pragma unroll 1
                for (int n = 1; n < 16; n++) {
                    if (n >= 3) {
                        mbar_wait(sb + BAR_EMPTY_KV + r.slot * 8, r.phase ^ 1);
                        mbar_expect(sb + BAR_FULL_KV + r.slot * 8, RING_BYTES);
                        bulk1d(sb + OFF_RING + r.slot * RING_BYTES, g_kv + ((n + rot) & 7) * RING_BYTES, RING_BYTES, sb + BAR_FULL_KV + r.slot * 8);
                    }
                    mbar_wait(sb + BAR_FULL_KV + r.slot * 8, r.phase);
                    asm volatile("st.release.cta.shared::cta.u32 [%0], %1;" :: "r"(sb + OFF_PUB), "r"(n + 1) : "memory");
                    next_stage(r);
                }
            }
        }
    } else if (wg < 4) {
        if (tid < 30) reinterpret_cast<uint4*>(g_part + j * 1920 + i * 120)[tid] = make_uint4(0u, 0u, 0u, 0u);
        if (wg < 2) {
            const uint32_t kw = 4 * wg + warp, g = lane >> 2;
            const uint32_t w0 = sb + OFF_WRAW + (80 * kw + 4 * q) * 40;
            const uint32_t wa[3] = {w0 + g * 4, w0 + g * 4 + 25600, w0 + 32 + (g & 1) * 4 + (g & 2) * 12800};
            float d[3][2][4];
#pragma unroll
            for (int e = 0; e < 24; e++) (&d[0][0][0])[e] = 0.f;
            if (SPN & 2) mbar_spin(sb + BAR_KVIN, 0); else mbar_wait(sb + BAR_KVIN, 0);
            if (wg == 0) TS(13);
            uint2 x[2][2];
            uint32_t u[2][12];
#pragma unroll
            for (int s = 0; s < 6; s++) {
                if (s < 5) {
                    const uint32_t st = 5 * kw + s;
                    const uint32_t xa = sb + OFF_X16 + (st >> 2) * 2048 + g * 128 + (((2 * (st & 3) + (q >> 1)) ^ g) << 4) + (q & 1) * 8;
                    x[s & 1][0] = lds64(xa); x[s & 1][1] = lds64(xa + 1024);
#pragma unroll
                    for (int e = 0; e < 12; e++) u[s & 1][e] = lds32(wa[e >> 2] + s * 640 + (e & 3) * 40);
                }
                if (s > 0) {
                    const int p = (s - 1) & 1;
#pragma unroll
                    for (int t = 0; t < 3; t++) {
                        const uint32_t a0 = __byte_perm(u[p][4 * t], u[p][4 * t + 1], 0x5410), a1 = __byte_perm(u[p][4 * t], u[p][4 * t + 1], 0x7632);
                        const uint32_t a2 = __byte_perm(u[p][4 * t + 2], u[p][4 * t + 3], 0x5410), a3 = __byte_perm(u[p][4 * t + 2], u[p][4 * t + 3], 0x7632);
                        mma16816(d[t][0], a0, a1, a2, a3, x[p][0].x, x[p][0].y);
                        mma16816(d[t][1], a0, a1, a2, a3, x[p][1].x, x[p][1].y);
                    }
                }
            }
            if (KVF < 2) bar_arrive(2, 384);
#pragma unroll
            for (int t = 0; t < 3; t++) {
                const uint32_t pr = t == 0 ? g : t == 1 ? 10 + g : 8 + (g & 1) + 5 * (g & 2);
                if (t < 2 || g < 4) {
#pragma unroll
                    for (int h = 0; h < 2; h++) {
                        const uint32_t a = sb + OFF_KVP + kw * 2560 + ((8 * h + 2 * q) * 20 + pr) * 8;
                        sts64(a, __float_as_uint(d[t][h][0]), __float_as_uint(d[t][h][2]));
                        sts64(a + 160, __float_as_uint(d[t][h][1]), __float_as_uint(d[t][h][3]));
                    }
                }
            }
            if (wg == 0) TS(14);
        }
        bar_sync(1, 512);
        if (wg < 3) {
            const uint32_t ch = 4 * wg + warp, grp = ch >= 6, c6 = ch - 6 * grp, isv = c6 >= 3, c3 = c6 - 3 * isv;
            const uint32_t key = 8 * grp + (lane >> 2);
            const bool mu = (MUFU_MASK >> ((2 * cta + grp) & 7)) & 1;
            uint32_t word;
            if (c3 == 2 && q >= 2) {
                word = isv ? (q == 2 ? 0x00003F80u : 0u) : mu ? 0u : q == 2 ? 0x3F00433Fu : 0x00003B4Au;
            } else {
                const uint32_t a = sb + OFF_KVP + (key * 20 + 10 * isv + 4 * c3 + q) * 8;
                float s0 = 0.f, s1 = 0.f;
#pragma unroll
                for (int u = 0; u < 8; u++) { const uint2 v = lds64(a + u * 2560); s0 += __uint_as_float(v.x); s1 += __uint_as_float(v.y); }
                const float sc = (isv || mu) ? 1.f : 0.5f;
                word = pack_bf16(s0 * sc, s1 * sc);
            }
            st_relaxed64(g_kt + cta * 384 + tid, ((unsigned long long)tag << 32) | word);
            reinterpret_cast<uint32_t*>(g_kv + cta * 1536)[tid] = word;
            if (c3 == 2 && q >= 2) word = 0;
            if (isv) {
                const uint32_t mx = __reduce_max_sync(~0u, max(word & 0x7FFFu, (word >> 16) & 0x7FFFu));
                if (lane == 0) sts32(sb + OFF_KST + 192 + (3 * grp + c3) * 4, mx);
            } else {
                float n2 = fmaf(bf_lo(word), bf_lo(word), bf_hi(word) * bf_hi(word));
                n2 += __shfl_xor_sync(~0u, n2, 1);
                n2 += __shfl_xor_sync(~0u, n2, 2);
                if (q == 0) sts32(sb + OFF_KST + (c3 * 16 + key) * 4, __float_as_uint(mu ? n2 : 4.f * n2));
            }
            if (KVF == 2) bar_arrive(2, 512);
            if (wg | warp) bar_arrive(3, 384);
            else {
                bar_sync(3, 384);
                TS(15);
                const uint32_t a = sb + OFF_KST + (lane & 15) * 4;
                const float n2 = __uint_as_float(lds32(a)) + __uint_as_float(lds32(a + 64)) + __uint_as_float(lds32(a + 128));
                const uint32_t sk = __reduce_max_sync(~0u, min(((__float_as_uint(n2) & 0x7FFFFFFFu) + 0xFFFFu) >> 16, 0x7FFFu));
                const uint32_t sv = __reduce_max_sync(~0u, lds32(sb + OFF_KST + 192 + min(lane, 5) * 4));
                if (lane == 0) {
                    const bool vok = sv == 0 || (sv >= ((127 - 40) << 7) && sv <= ((127 + 40) << 7));
                    st_relaxed(g_stat + cta, (tag << 16) | (vok ? sk : 0x7FFFu));
                }
                __syncwarp();
                bar_arrive(12, SP ? 96 : 64);
                TS(17);
            }
        }
        {
            const unsigned long long* src = g_kt + (i >> 1) * 6144 + tid * 2;
            uint4 v[6];
#pragma unroll
            for (int u = 0; u < 6; u++) v[u] = make_uint4(0u, ~tag, 0u, 0u);
            if (GD) __nanosleep(GD);
#pragma unroll 1
            for (uint32_t spin = 0; spin < (1u << 16); spin++) {
#pragma unroll
                for (int u = 0; u < 6; u++) if (v[u].y != tag) v[u] = ld_relaxed2x64(src + u * 1024);
                bool ok = true;
#pragma unroll
                for (int u = 0; u < 6; u++) { if (v[u].w != tag) v[u].y = ~tag; ok = ok && v[u].y == tag; }
                if (__all_sync(~0u, ok)) break;
            }
#pragma unroll
            for (int u = 0; u < 6; u++) sts64(sb + OFF_RING + tid * 8 + u * 4096, v[u].x, v[u].z);
            fence_async_smem();
            __syncwarp();
            if (lane == 0) mbar_arrive(sb + BAR_C0);
            if (wg == 0) TS(7);
        }
        uint32_t slot = 0;
        const uint4 cz = lds128(sb + OFF_STAT + 16);
#pragma unroll 1
        for (int pass = 0; pass < 2; pass++) {
            uint32_t qf[6];
            if (SPN & 1) mbar_spin(sb + BAR_Q + pass * 8, 0); else mbar_wait(sb + BAR_Q + pass * 8, 0);
            const uint32_t qa = sb + OFF_Q + pass * 10240 + r0 * 160 + wg * 40 + q * 4;
            qf[0] = lds32(qa); qf[1] = lds32(qa + 8 * 160);
            qf[2] = lds32(qa + 16); qf[3] = lds32(qa + 8 * 160 + 16);
            qf[4] = q < 2 ? lds32(qa + 32) : 0u; qf[5] = q < 2 ? lds32(qa + 8 * 160 + 32) : 0u;
            if (pass == 0) { count_wait(sb + OFF_PUB, 0, 1); if (wg == 0) { TS(19); TC(26); } }
            float n0 = 0.f, n1 = 0.f;
#pragma unroll
            for (int e = 0; e < 3; e++) {
                n0 = fmaf(bf_lo(qf[2 * e]), bf_lo(qf[2 * e]), fmaf(bf_hi(qf[2 * e]), bf_hi(qf[2 * e]), n0));
                n1 = fmaf(bf_lo(qf[2 * e + 1]), bf_lo(qf[2 * e + 1]), fmaf(bf_hi(qf[2 * e + 1]), bf_hi(qf[2 * e + 1]), n1));
            }
            n0 += __shfl_xor_sync(~0u, n0, 1); n0 += __shfl_xor_sync(~0u, n0, 2);
            n1 += __shfl_xor_sync(~0u, n1, 1); n1 += __shfl_xor_sync(~0u, n1, 2);
            const float k2 = __uint_as_float(lds32(sb + OFF_STAT));
            const uint32_t bad = !(n0 * k2 <= 4000.f && n1 * k2 <= 4000.f);
            uint32_t anybad;
            asm volatile("{\n.reg .pred p, r;\nsetp.ne.u32 p, %1, 0;\nbar.red.or.pred r, %2, 128, p;\nselp.u32 %0, 1, 0, r;\n}" : "=r"(anybad) : "r"(bad), "r"(8 + wg) : "memory");
            float o[12];
#pragma unroll
            for (int k = 0; k < 12; k++) o[k] = 0.f;
            fence_regs(o);
            if (!__shfl_sync(~0u, anybad, 0)) {
                if (q >= 2) qf[4] = qf[5] = q == 2 ? 0x3F803F80u : 0x00003F80u;
                attend<true>(sb, slot, pass, qf, o, cz.x, cz.y, cz.z);
            } else {
                attend<false>(sb, slot, pass, qf, o, cz.x, cz.y, cz.z);
            }
            const float i0 = rcpf(__shfl_sync(~0u, o[8], (lane & ~3) | 2)), i1 = rcpf(__shfl_sync(~0u, o[10], (lane & ~3) | 2));
            const uint32_t ot = opaque_tid(), ol = ot & 31, oq = ot & 3;
            uint8_t* const gx = g_ox + opaque_cta() * 10240;
#pragma unroll
            for (int b = 0; b < 3; b++) {
                if (b < 2 || oq < 2) {
                    const uint32_t v0 = pack_bf16(o[4 * b] * i0, o[4 * b + 1] * i0), v1 = pack_bf16(o[4 * b + 2] * i1, o[4 * b + 3] * i1);
                    const uint32_t col = 20 * (ot >> 7) + 8 * b + 2 * oq;
                    const uint32_t x = (col >> 4) * 2048 + (ot & 96) * 16 + (col & 8) * 16 + (ol >> 2) * 16 + (col & 7) * 2;
                    st_relaxed(gx + x, pass ? v0 : ~0u);
                    st_relaxed(gx + x + 256, pass ? v1 : ~0u);
                    const uint32_t dst = sb + OFF_Q + (pass ? 10240 + x : (((ot & 96) >> 1) + (ol >> 2)) * 160 + col * 2);
                    sts32(dst, v0);
                    sts32(dst + (pass ? 256 : 8 * 160), v1);
                }
            }
            fence_async_smem();
            __syncwarp();
            if (lane == 0) mbar_arrive(sb + BAR_OA + pass * 8);
            if (wg == 0) { TS(20 + pass); TC(27 + pass); }
        }
        TS(22 + wg);
        if (NPASS == 5) {
            const uint32_t ot = opaque_tid(), oc = opaque_cta();
            const int lane = ot & 31, i = oc >> 3, j = oc & 7;
            if (wg != 0) {
                const int u = 4 * (3 - wg) + warp;
                uint4 v[12];
                const uint8_t* src[3];
                uint32_t entry = u + 1;
#pragma unroll
                for (int t = 0; t < 3; t++) {
                    const int s = min(3 * u + t, 34), h = (s * 37) >> 8;
                    const int g = 5 * ((j + 1 + s - 7 * h) & 7) + 4 - h;
                    src[t] = g_ox + (i * 40 + g) * 2048 + lane * 16;
                    entry |= g << (8 * t + 8);
                }
#pragma unroll
                for (int k = 0; k < 12; k++) v[k] = make_uint4(k >= 8 && u == 11 ? 0u : ~0u, 0u, 0u, 0u);
                const uint8_t* const probe = (lane < 8 ? src[0] : lane < 16 ? src[1] : src[2]) - lane * 16 + (lane & 6) * 256 + (lane & 1) * 128 + 368;
                uint32_t wait = u == 11 ? 0xFFFFu : 0xFFFFFFu;
                mbar_wait(sb + BAR_A0, 0);
#pragma unroll 1
                for (uint32_t spin = 0; spin < (1u << 16); spin++) {
                    uint4 p = make_uint4(0u, 0u, 0u, 0u);
                    if (mbar_test(sb + BAR_OA + 8, 0)) wait = 0;
                    if ((wait >> lane) & 1) p = ld_relaxed128(probe);
#pragma unroll
                    for (int k = 0; k < 12; k++) if (!((wait >> (2 * (k & 12))) & 0xFF) && v[k].x == ~0u) v[k] = ld_relaxed128(src[k >> 2] + (k & 3) * 512);
                    wait = __ballot_sync(~0u, p.x == ~0u || p.w == ~0u);
                    bool ok = true;
#pragma unroll
                    for (int k = 0; k < 12; k++) {
                        if (v[k].y == ~0u || v[k].z == ~0u || v[k].w == ~0u) v[k].x = ~0u;
                        ok = ok && v[k].x != ~0u;
                    }
                    if (__all_sync(~0u, ok)) break;
                }
                if (SPN & 4) mbar_spin(sb + BAR_OA + 8, 0); else mbar_wait(sb + BAR_OA + 8, 0);
#pragma unroll
                for (int k = 0; k < 12; k++) sts128(sb + OFF_RING + u * 6144 + k * 512 + lane * 16, v[k].x, v[k].y, v[k].z, v[k].w);
                fence_async_smem();
                __syncwarp();
                if (lane == 0) {
                    uint32_t n;
                    asm volatile("atom.relaxed.cta.shared::cta.add.u32 %0, [%1], 1;" : "=r"(n) : "r"(sb + OFF_QUEUE + 48) : "memory");
                    asm volatile("st.release.cta.shared::cta.u32 [%0], %1;" :: "r"(sb + OFF_QUEUE + n * 4), "r"(entry) : "memory");
                }
            } else {
                float a[40];
                mbar_wait(sb + BAR_WA, 0);
                if (SPN & 4) mbar_spin(sb + BAR_OA + 8, 0); else mbar_wait(sb + BAR_OA + 8, 0);
                const uint64_t dw = desc(sb + OFF_WA, 2048, SW32 | 16);
                {
                    const uint64_t da = desc(sb + OFF_Q + 10240, 128, 16);
                    WG_FENCE();
#pragma unroll
                    for (int t = 0; t < 5; t++) {
                        const uint32_t g = 5 * j + t;
                        if (t == 0) wg_ss_n80_ta0_tb1_initd(a, da, dw + (g >> 2) * 640 + (g & 3) * 32);
                        else wg_ss_n80_ta0_tb1_d(a, da + 128 * t, dw + (g >> 2) * 640 + (g & 3) * 32);
                    }
                    WG_COMMIT();
                }
#pragma unroll 1
                for (int n = 0; n < 12; n++) {
                    const uint32_t e = __shfl_sync(~0u, queue_wait(sb + OFF_QUEUE + n * 4), 0);
                    const uint64_t da = desc(sb + OFF_RING - 6144 + (e & 15) * 6144, 128, 16);
                    WG_FENCE();
#pragma unroll
                    for (int t = 0; t < 3; t++) {
                        const uint32_t g = (e >> (8 * t + 8)) & 63;
                        wg_ss_n80_ta0_tb1_d(a, da + 128 * t, dw + (g >> 2) * 640 + (g & 3) * 32);
                    }
                    WG_COMMIT();
                }
                WG_WAIT(0);
                fence_regs(a);
                bar_sync(8, 128);
                store_tile(sb + OFF_Q + 10240 + warp * 2560, P.out + (128 * i + 64 + 16 * warp) * 1280 + 80 * j, lane, a);
                TS(11);
            }
        }
    } else {
        asm volatile("setmaxnreg.inc.sync.aligned.u32 128;");
        const uint32_t mrow = 16 * warp + (lane & 15), mcol = lane >> 4;
        const uint32_t xrow = mrow * 160 + mcol * 16, xgrp = (mrow & 7) * 16 + mcol * 128;
        bar_sync(2, KVF == 2 ? 512 : 384);
#pragma unroll 1
        for (int half = 0; half < 2; half++) {
            float a[40];
            gemm_half<true>(sb, 10 * half, a);
            if (half == 0) { TS(1); if (!KVF) bar_sync(2, 384); }
            else if (lane == 0) { mbar_arrive(sb + BAR_EMPTY_G); mbar_arrive(sb + BAR_EMPTY_G + 8); mbar_arrive(sb + BAR_EMPTY_G + 16); }
            stage_tile<1>(sb + OFF_Q + half * 10240 + xrow, 16, a);
            __syncwarp();
            if (lane == 0) mbar_arrive(sb + BAR_Q + half * 8);
            if (half) TS(2);
        }
#pragma unroll 1
        for (int pass = 1; pass < NPASS; pass++) {
        if (pass == 4) {
        mbar_wait(sb + BAR_KVB, 0);
        if (tid < 592) {
            const int m = tid - 512, h = m / 20;
            const uint32_t x0 = sb + OFF_KVB + (m >> 3) * 1408 + (m & 7) * 16;
#pragma unroll
            for (int e = 0; e < 5; e++) {
                const uint4 v = lds128(sb + OFF_PST + m * 96 + e * 16);
                const int n = 20 * h + 4 * e;
                sts64(x0 + (n >> 3) * 128 + (n & 4) * 2, pack_bf16(__uint_as_float(v.x), __uint_as_float(v.y)), pack_bf16(__uint_as_float(v.z), __uint_as_float(v.w)));
            }
            sts16(x0 + 1280 + h * 2, (uint16_t)pack_bf16(__uint_as_float(lds32(sb + OFF_PST + m * 96 + 80)), 0.f));
        }
        fence_async_smem();
        bar_sync(6, 128);
#pragma unroll 1
        for (int half = 0; half < 2; half++) linear_out(sb, half, sb + OFF_PK + half * 10240 + xrow, q);
        fence_async_smem();
        __syncwarp();
        if (lane == 0) mbar_arrive(sb + BAR_OB);
        }
        float a[40], b[40];
        gemm_pass(sb, pass, a, b);
        if (pass == 1 || pass == 3) {
        TS(pass == 1 ? 3 : 6);
        stage_tile<2>(sb + OFF_PK + (mrow >> 3) * 1280 + xgrp, 128, a);
        stage_tile<2>(sb + OFF_PK + (8 + (mrow >> 3)) * 1280 + xgrp, 128, b);
        } else if (pass == 2) {
        TS(4);
        stage_tile<0>(sb + OFF_V + 128 + (mrow >> 3) * 1536 + xgrp, 128, a);
        stage_tile<0>(sb + OFF_V + 128 + (8 + (mrow >> 3)) * 1536 + xgrp, 128, b);
        {
            const uint32_t x = sb + OFF_V + ((tid - 512) >> 3) * 1536 + (tid & 7) * 16;
            sts128(x, 0x3F80u, 0u, 0u, 0u);
            sts128(x + 11 * 128, 0x3F80u, 0u, 0u, 0u);
        }
        fence_async_smem();
        bar_sync(6, 128);
        {
            float d1[36], d2[16]; zero_regs(d1); zero_regs(d2);
            const uint64_t da = desc(sb + OFF_PK, 1280, 8), db = desc(sb + OFF_V, 1536, 8);
            WG_FENCE();
#pragma unroll
            for (int k = 0; k < 8; k++) {
                wg_ss_n72_ta1_tb1_d(d1, da + 160 * k, db + 192 * k);
                wg_ss_n32_ta1_tb1_d(d2, da + 16 + 160 * k, db + 64 + 192 * k);
            }
            WG_COMMIT();
            WG_WAIT(0);
            fence_regs(d1); fence_regs(d2);
            bar_sync(6, 128);
#pragma unroll
            for (int u = 0; u < 7; u++) if (u < 6 || tid < 624) sts128(sb + OFF_KVB + (tid - 512 + 128 * u) * 16, 0u, 0u, 0u, 0u);
            const uint32_t part = sb + OFF_PST;
#pragma unroll
            for (int hh = 0; hh < 2; hh++) {
                const int m = r0 + 8 * hh;
                if (m < 60) {
                    const int h20 = (m / 20) * 20;
                    if (q == 0) sts128(part + m * 96 + 80, __float_as_uint(d1[2 * hh]), 0u, 0u, 0u);
#pragma unroll
                    for (int k = 1; k < 9; k++) {
                        const int e = 8 * (k - 1) + 2 * q - h20;
                        if (e >= 0 && e < 20) sts64(part + m * 96 + e * 4, __float_as_uint(d1[4 * k + 2 * hh]), __float_as_uint(d1[4 * k + 2 * hh + 1]));
                    }
                }
                if (m >= 44) {
                    if (q == 0) sts128(part + (m + 16) * 96 + 80, __float_as_uint(d2[12 + 2 * hh]), 0u, 0u, 0u);
#pragma unroll
                    for (int k = 0; k < 3; k++) {
                        const int e = 8 * k + 2 * q - 4;
                        if (e >= 0) sts64(part + (m + 16) * 96 + e * 4, __float_as_uint(d2[4 * k + 2 * hh]), __float_as_uint(d2[4 * k + 2 * hh + 1]));
                    }
                }
            }
            fence_async_smem();
            __syncwarp();
            if (lane == 0) mbar_arrive(sb + BAR_PART);
        }
        } else {
        __nv_bfloat16* out = P.out + (128 * i + 16 * warp) * 1280 + 80 * j + 640;
        mbar_wait(sb + BAR_A0, 0);
        store_tile(sb + OFF_Q + warp * 2560, out, lane, a);
        store_tile(sb + OFF_Q + warp * 2560, out + 64 * 1280, lane, b);
        TS(9);
        }
        }
        if (NPASS == 5) {
            mbar_wait(sb + BAR_WA, 0);
            float a[40];
            gemm_half<false>(sb, 20, a);
            store_tile(sb + OFF_Q + warp * 2560, P.out + (128 * i + 16 * warp) * 1280 + 80 * j, lane, a);
            TS(12);
        }
        if (cta == 0 && tid == 512) *(volatile uint32_t*)&g_epoch = tag;
    }
}

typedef CUresult (*EncodeFn)(CUtensorMap*, CUtensorMapDataType, cuuint32_t, void*, const cuuint64_t*, const cuuint64_t*,
                             const cuuint32_t*, const cuuint32_t*, CUtensorMapInterleave, CUtensorMapSwizzle,
                             CUtensorMapL2promotion, CUtensorMapFloatOOBfill);

void make_map(EncodeFn enc, CUtensorMap* m, const void* p, uint32_t box_cols, uint32_t box_rows, uint64_t rows = 2048) {
    cuuint64_t dims[2] = {640, rows}, strides[1] = {1280};
    cuuint32_t box[2] = {box_cols, box_rows}, es[2] = {1, 1};
    enc(m, CU_TENSOR_MAP_DATA_TYPE_BFLOAT16, 2, const_cast<void*>(p), dims, strides, box, es, CU_TENSOR_MAP_INTERLEAVE_NONE,
        box_cols == 64 ? CU_TENSOR_MAP_SWIZZLE_128B : box_cols == 16 ? CU_TENSOR_MAP_SWIZZLE_32B : CU_TENSOR_MAP_SWIZZLE_NONE, CU_TENSOR_MAP_L2_PROMOTION_L2_128B, CU_TENSOR_MAP_FLOAT_OOB_FILL_NONE);
}
void make_x16map(EncodeFn enc, CUtensorMap* m, const void* p) {
    cuuint64_t dims[3] = {64, 2048, 10}, strides[2] = {1280, 128};
    cuuint32_t box[3] = {64, 16, 10}, es[3] = {1, 1, 1};
    enc(m, CU_TENSOR_MAP_DATA_TYPE_BFLOAT16, 3, const_cast<void*>(p), dims, strides, box, es, CU_TENSOR_MAP_INTERLEAVE_NONE,
        CU_TENSOR_MAP_SWIZZLE_128B, CU_TENSOR_MAP_L2_PROMOTION_L2_128B, CU_TENSOR_MAP_FLOAT_OOB_FILL_NONE);
}
void make_wmap(EncodeFn enc, CUtensorMap* m, const void* p, uint64_t cols) {
    cuuint64_t dims[3] = {16, 640, cols / 16}, strides[2] = {cols * 2, 32};
    cuuint32_t box[3] = {16, 64, 5}, es[3] = {1, 1, 1};
    enc(m, CU_TENSOR_MAP_DATA_TYPE_BFLOAT16, 3, const_cast<void*>(p), dims, strides, box, es, CU_TENSOR_MAP_INTERLEAVE_NONE,
        CU_TENSOR_MAP_SWIZZLE_32B, CU_TENSOR_MAP_L2_PROMOTION_L2_128B, CU_TENSOR_MAP_FLOAT_OOB_FILL_NONE);
}

}

extern "C" void kernel_launch(void* const* d_in, const int* in_sizes, int n_in, void* d_out, int out_size) {
    static EncodeFn enc = nullptr;
    static void *oa = nullptr, *ob = nullptr;
    static int sms = 0;
    if (!enc) {
        void* fn = nullptr;
        cudaDriverEntryPointQueryResult qr;
        cudaGetDriverEntryPoint("cuTensorMapEncodeTiled", &fn, cudaEnableDefault, &qr);
        enc = (EncodeFn)fn;
        int dev = 0;
        cudaGetDevice(&dev);
        cudaDeviceGetAttribute(&sms, cudaDevAttrMultiProcessorCount, dev);
        cudaGetSymbolAddress(&oa, g_oa);
        cudaGetSymbolAddress(&ob, g_ob);
        cudaFuncSetAttribute(fused_kernel, cudaFuncAttributeMaxDynamicSharedMemorySize, SMEM_BYTES);
    }
    Params P;
    make_map(enc, &P.xa, d_in[0], 64, 64);
    make_x16map(enc, &P.xa16, d_in[0]);
    make_map(enc, &P.wq64, d_in[1], 64, 64, 640);
    make_map(enc, &P.wq16, d_in[1], 16, 64, 640);
    make_map(enc, &P.xb, d_in[5], 64, 128);
    make_wmap(enc, &P.wqkv, d_in[6], 1920);
    make_wmap(enc, &P.woa, d_in[4], 640);
    make_wmap(enc, &P.wob, d_in[7], 640);
    make_map(enc, &P.oa, oa, 64, 64);
    make_map(enc, &P.ob, ob, 64, 128);
    make_map(enc, &P.oa_st, oa, 80, 64);
    make_map(enc, &P.ob_st, ob, 80, 128);
    for (int k = 0; k < 8; k++) P.in[k] = (const uint8_t*)d_in[k];
    P.out = (__nv_bfloat16*)d_out;
    P.helpers = sms >= NCTA + 4;
    fused_kernel<<<P.helpers ? NCTA + 4 : NCTA, NTHR, SMEM_BYTES, cudaStreamPerThread>>>(P);
}
```

```cpp
#include <cuda_runtime.h>
#include <cuda_bf16.h>
#include <cuda.h>
#include <stdint.h>

namespace {

constexpr int NCTA = 128;
constexpr int NTHR = 768;

constexpr uint32_t OFF_STAGE = 0;
constexpr uint32_t STAGE_BYTES = 26624;
constexpr uint32_t OFF_PK = 79872;
constexpr uint32_t OFF_V = 100352;
constexpr uint32_t OFF_KVB = OFF_V;
constexpr uint32_t OFF_PST = OFF_V + 14336;
constexpr uint32_t OFF_WA = 0;
constexpr uint32_t OFF_XA = 102400;
constexpr uint32_t OFF_RING = 135168;
constexpr uint32_t RING_BYTES = 24576;
constexpr uint32_t OFF_WRAW = OFF_RING;
constexpr uint32_t OFF_KVP = OFF_RING + 51200;
constexpr uint32_t OFF_Q = 208896;
constexpr uint32_t OFF_X16 = OFF_Q;
constexpr uint32_t OFF_MISC = 229376;
constexpr uint32_t OFF_BAR = OFF_MISC;
constexpr uint32_t BAR_FULL_G = OFF_BAR, BAR_EMPTY_G = OFF_BAR + 24, BAR_FULL_KV = OFF_BAR + 48, BAR_EMPTY_KV = OFF_BAR + 72;
constexpr uint32_t BAR_OA = OFF_BAR + 96, BAR_WA = OFF_BAR + 112, BAR_FULL_X = OFF_BAR + 120, BAR_EMPTY_X = OFF_BAR + 152, BAR_A0 = OFF_BAR + 184;
constexpr uint32_t OFF_QUEUE = OFF_BAR + 192;
constexpr uint32_t BAR_PART = OFF_BAR + 264, BAR_KVB = OFF_BAR + 272, BAR_OB = OFF_BAR + 280, BAR_KVIN = OFF_BAR + 288;
constexpr uint32_t OFF_PUB = OFF_BAR + 296;
constexpr uint32_t OFF_STAT = OFF_BAR + 304;
constexpr uint32_t BAR_Q = OFF_BAR + 336, BAR_C0 = OFF_BAR + 352, BAR_WQ = OFF_BAR + 360;
constexpr uint32_t OFF_KST = OFF_MISC + 384;
constexpr uint32_t OFF_TS = OFF_KST + 256;
constexpr uint32_t SMEM_BYTES = OFF_TS + 256;

#define MUFU_MASK 0x52

constexpr float LOG2E = 1.4426950408889634f;
constexpr float QSCALE = 0.22360679774997896f * LOG2E;

struct Params {
    CUtensorMap xa, xa16, wq64, wq16, xb, wqkv, woa, wob, oa, ob, oa_st, ob_st;
    const uint8_t* in[8];
    __nv_bfloat16* out;
    int helpers;
};

}

__device__ __align__(1024) uint8_t g_kv[256 * 768];
__device__ __align__(1024) __nv_bfloat16 g_oa[2048 * 640];
__device__ __align__(1024) __nv_bfloat16 g_ob[2048 * 640];
__device__ __align__(1024) uint8_t g_ox[16 * 40 * 2048];
__device__ __align__(128) float g_part[8 * 1920];
__device__ __align__(1024) unsigned long long g_kt[128 * 384];
__device__ __align__(128) uint32_t g_stat[128];
__device__ __align__(128) uint16_t g_flag_kv[128];
__device__ __align__(128) uint16_t g_flag_b1[128];
__device__ __align__(128) uint16_t g_flag_b2[128];
__device__ __align__(128) uint16_t g_flag_a[128];
__device__ __align__(128) uint16_t g_flag_w[32];
__device__ __align__(1024) uint8_t g_wt[320 * 10240];
__device__ uint32_t g_epoch;
#define TS(k)
#define TC(k)

namespace {

__device__ __forceinline__ void wg_rs_n24_tb1_d(float (&d)[12], uint32_t a0, uint32_t a1, uint32_t a2, uint32_t a3, uint64_t db) {
    asm volatile("{\n.reg .pred p;\nsetp.ne.b32 p, 1, 0;\n"
        "wgmma.mma_async.sync.aligned.m64n24k16.f32.bf16.bf16 {%0, %1, %2, %3, %4, %5, %6, %7, %8, %9, %10, %11}, {%12, %13, %14, %15}, %16, p, 1, 1, 1;\n}\n"
        : "+f"(d[0]), "+f"(d[1]), "+f"(d[2]), "+f"(d[3]), "+f"(d[4]), "+f"(d[5]), "+f"(d[6]), "+f"(d[7]), "+f"(d[8]), "+f"(d[9]), "+f"(d[10]), "+f"(d[11])
        : "r"(a0), "r"(a1), "r"(a2), "r"(a3), "l"(db));
}
__device__ __forceinline__ void wg_rs_n64_tb0_d(float (&d)[32], uint32_t a0, uint32_t a1, uint32_t a2, uint32_t a3, uint64_t db) {
    asm volatile("{\n.reg .pred p;\nsetp.ne.b32 p, 1, 0;\n"
        "wgmma.mma_async.sync.aligned.m64n64k16.f32.bf16.bf16 {%0, %1, %2, %3, %4, %5, %6, %7, %8, %9, %10, %11, %12, %13, %14, %15, %16, %17, %18, %19, %20, %21, %22, %23, %24, %25, %26, %27, %28, %29, %30, %31}, {%32, %33, %34, %35}, %36, p, 1, 1, 0;\n}\n"
        : "+f"(d[0]), "+f"(d[1]), "+f"(d[2]), "+f"(d[3]), "+f"(d[4]), "+f"(d[5]), "+f"(d[6]), "+f"(d[7]), "+f"(d[8]), "+f"(d[9]), "+f"(d[10]), "+f"(d[11]), "+f"(d[12]), "+f"(d[13]), "+f"(d[14]), "+f"(d[15]), "+f"(d[16]), "+f"(d[17]), "+f"(d[18]), "+f"(d[19]), "+f"(d[20]), "+f"(d[21]), "+f"(d[22]), "+f"(d[23]), "+f"(d[24]), "+f"(d[25]), "+f"(d[26]), "+f"(d[27]), "+f"(d[28]), "+f"(d[29]), "+f"(d[30]), "+f"(d[31])
        : "r"(a0), "r"(a1), "r"(a2), "r"(a3), "l"(db));
}
__device__ __forceinline__ void wg_rs_n64_tb0_initd(float (&d)[32], uint32_t a0, uint32_t a1, uint32_t a2, uint32_t a3, uint64_t db) {
    asm volatile("{\n.reg .pred p;\nsetp.ne.b32 p, 0, 0;\n"
        "wgmma.mma_async.sync.aligned.m64n64k16.f32.bf16.bf16 {%0, %1, %2, %3, %4, %5, %6, %7, %8, %9, %10, %11, %12, %13, %14, %15, %16, %17, %18, %19, %20, %21, %22, %23, %24, %25, %26, %27, %28, %29, %30, %31}, {%32, %33, %34, %35}, %36, p, 1, 1, 0;\n}\n"
        : "=f"(d[0]), "=f"(d[1]), "=f"(d[2]), "=f"(d[3]), "=f"(d[4]), "=f"(d[5]), "=f"(d[6]), "=f"(d[7]), "=f"(d[8]), "=f"(d[9]), "=f"(d[10]), "=f"(d[11]), "=f"(d[12]), "=f"(d[13]), "=f"(d[14]), "=f"(d[15]), "=f"(d[16]), "=f"(d[17]), "=f"(d[18]), "=f"(d[19]), "=f"(d[20]), "=f"(d[21]), "=f"(d[22]), "=f"(d[23]), "=f"(d[24]), "=f"(d[25]), "=f"(d[26]), "=f"(d[27]), "=f"(d[28]), "=f"(d[29]), "=f"(d[30]), "=f"(d[31])
        : "r"(a0), "r"(a1), "r"(a2), "r"(a3), "l"(db));
}
__device__ __forceinline__ void wg_ss_n16_ta0_tb1_d(float (&d)[8], uint64_t da, uint64_t db) {
    asm volatile("{\n.reg .pred p;\nsetp.ne.b32 p, 1, 0;\n"
        "wgmma.mma_async.sync.aligned.m64n16k16.f32.bf16.bf16 {%0, %1, %2, %3, %4, %5, %6, %7}, %8, %9, p, 1, 1, 0, 1;\n}\n"
        : "+f"(d[0]), "+f"(d[1]), "+f"(d[2]), "+f"(d[3]), "+f"(d[4]), "+f"(d[5]), "+f"(d[6]), "+f"(d[7])
        : "l"(da), "l"(db));
}
__device__ __forceinline__ void wg_ss_n32_ta1_tb1_d(float (&d)[16], uint64_t da, uint64_t db) {
    asm volatile("{\n.reg .pred p;\nsetp.ne.b32 p, 1, 0;\n"
        "wgmma.mma_async.sync.aligned.m64n32k16.f32.bf16.bf16 {%0, %1, %2, %3, %4, %5, %6, %7, %8, %9, %10, %11, %12, %13, %14, %15}, %16, %17, p, 1, 1, 1, 1;\n}\n"
        : "+f"(d[0]), "+f"(d[1]), "+f"(d[2]), "+f"(d[3]), "+f"(d[4]), "+f"(d[5]), "+f"(d[6]), "+f"(d[7]), "+f"(d[8]), "+f"(d[9]), "+f"(d[10]), "+f"(d[11]), "+f"(d[12]), "+f"(d[13]), "+f"(d[14]), "+f"(d[15])
        : "l"(da), "l"(db));
}
__device__ __forceinline__ void wg_ss_n64_ta0_tb1_d(float (&d)[32], uint64_t da, uint64_t db) {
    asm volatile("{\n.reg .pred p;\nsetp.ne.b32 p, 1, 0;\n"
        "wgmma.mma_async.sync.aligned.m64n64k16.f32.bf16.bf16 {%0, %1, %2, %3, %4, %5, %6, %7, %8, %9, %10, %11, %12, %13, %14, %15, %16, %17, %18, %19, %20, %21, %22, %23, %24, %25, %26, %27, %28, %29, %30, %31}, %32, %33, p, 1, 1, 0, 1;\n}\n"
        : "+f"(d[0]), "+f"(d[1]), "+f"(d[2]), "+f"(d[3]), "+f"(d[4]), "+f"(d[5]), "+f"(d[6]), "+f"(d[7]), "+f"(d[8]), "+f"(d[9]), "+f"(d[10]), "+f"(d[11]), "+f"(d[12]), "+f"(d[13]), "+f"(d[14]), "+f"(d[15]), "+f"(d[16]), "+f"(d[17]), "+f"(d[18]), "+f"(d[19]), "+f"(d[20]), "+f"(d[21]), "+f"(d[22]), "+f"(d[23]), "+f"(d[24]), "+f"(d[25]), "+f"(d[26]), "+f"(d[27]), "+f"(d[28]), "+f"(d[29]), "+f"(d[30]), "+f"(d[31])
        : "l"(da), "l"(db));
}
__device__ __forceinline__ void wg_ss_n72_ta1_tb1_d(float (&d)[36], uint64_t da, uint64_t db) {
    asm volatile("{\n.reg .pred p;\nsetp.ne.b32 p, 1, 0;\n"
        "wgmma.mma_async.sync.aligned.m64n72k16.f32.bf16.bf16 {%0, %1, %2, %3, %4, %5, %6, %7, %8, %9, %10, %11, %12, %13, %14, %15, %16, %17, %18, %19, %20, %21, %22, %23, %24, %25, %26, %27, %28, %29, %30, %31, %32, %33, %34, %35}, %36, %37, p, 1, 1, 1, 1;\n}\n"
        : "+f"(d[0]), "+f"(d[1]), "+f"(d[2]), "+f"(d[3]), "+f"(d[4]), "+f"(d[5]), "+f"(d[6]), "+f"(d[7]), "+f"(d[8]), "+f"(d[9]), "+f"(d[10]), "+f"(d[11]), "+f"(d[12]), "+f"(d[13]), "+f"(d[14]), "+f"(d[15]), "+f"(d[16]), "+f"(d[17]), "+f"(d[18]), "+f"(d[19]), "+f"(d[20]), "+f"(d[21]), "+f"(d[22]), "+f"(d[23]), "+f"(d[24]), "+f"(d[25]), "+f"(d[26]), "+f"(d[27]), "+f"(d[28]), "+f"(d[29]), "+f"(d[30]), "+f"(d[31]), "+f"(d[32]), "+f"(d[33]), "+f"(d[34]), "+f"(d[35])
        : "l"(da), "l"(db));
}
__device__ __forceinline__ void wg_ss_n80_ta0_tb1_d(float (&d)[40], uint64_t da, uint64_t db) {
    asm volatile("{\n.reg .pred p;\nsetp.ne.b32 p, 1, 0;\n"
        "wgmma.mma_async.sync.aligned.m64n80k16.f32.bf16.bf16 {%0, %1, %2, %3, %4, %5, %6, %7, %8, %9, %10, %11, %12, %13, %14, %15, %16, %17, %18, %19, %20, %21, %22, %23, %24, %25, %26, %27, %28, %29, %30, %31, %32, %33, %34, %35, %36, %37, %38, %39}, %40, %41, p, 1, 1, 0, 1;\n}\n"
        : "+f"(d[0]), "+f"(d[1]), "+f"(d[2]), "+f"(d[3]), "+f"(d[4]), "+f"(d[5]), "+f"(d[6]), "+f"(d[7]), "+f"(d[8]), "+f"(d[9]), "+f"(d[10]), "+f"(d[11]), "+f"(d[12]), "+f"(d[13]), "+f"(d[14]), "+f"(d[15]), "+f"(d[16]), "+f"(d[17]), "+f"(d[18]), "+f"(d[19]), "+f"(d[20]), "+f"(d[21]), "+f"(d[22]), "+f"(d[23]), "+f"(d[24]), "+f"(d[25]), "+f"(d[26]), "+f"(d[27]), "+f"(d[28]), "+f"(d[29]), "+f"(d[30]), "+f"(d[31]), "+f"(d[32]), "+f"(d[33]), "+f"(d[34]), "+f"(d[35]), "+f"(d[36]), "+f"(d[37]), "+f"(d[38]), "+f"(d[39])
        : "l"(da), "l"(db));
}
__device__ __forceinline__ void wg_ss_n80_ta0_tb1_initd(float (&d)[40], uint64_t da, uint64_t db) {
    asm volatile("{\n.reg .pred p;\nsetp.ne.b32 p, 0, 0;\n"
        "wgmma.mma_async.sync.aligned.m64n80k16.f32.bf16.bf16 {%0, %1, %2, %3, %4, %5, %6, %7, %8, %9, %10, %11, %12, %13, %14, %15, %16, %17, %18, %19, %20, %21, %22, %23, %24, %25, %26, %27, %28, %29, %30, %31, %32, %33, %34, %35, %36, %37, %38, %39}, %40, %41, p, 1, 1, 0, 1;\n}\n"
        : "=f"(d[0]), "=f"(d[1]), "=f"(d[2]), "=f"(d[3]), "=f"(d[4]), "=f"(d[5]), "=f"(d[6]), "=f"(d[7]), "=f"(d[8]), "=f"(d[9]), "=f"(d[10]), "=f"(d[11]), "=f"(d[12]), "=f"(d[13]), "=f"(d[14]), "=f"(d[15]), "=f"(d[16]), "=f"(d[17]), "=f"(d[18]), "=f"(d[19]), "=f"(d[20]), "=f"(d[21]), "=f"(d[22]), "=f"(d[23]), "=f"(d[24]), "=f"(d[25]), "=f"(d[26]), "=f"(d[27]), "=f"(d[28]), "=f"(d[29]), "=f"(d[30]), "=f"(d[31]), "=f"(d[32]), "=f"(d[33]), "=f"(d[34]), "=f"(d[35]), "=f"(d[36]), "=f"(d[37]), "=f"(d[38]), "=f"(d[39])
        : "l"(da), "l"(db));
}
__device__ __forceinline__ void wg_ss_n88_ta0_tb1_d(float (&d)[44], uint64_t da, uint64_t db) {
    asm volatile("{\n.reg .pred p;\nsetp.ne.b32 p, 1, 0;\n"
        "wgmma.mma_async.sync.aligned.m64n88k16.f32.bf16.bf16 {%0, %1, %2, %3, %4, %5, %6, %7, %8, %9, %10, %11, %12, %13, %14, %15, %16, %17, %18, %19, %20, %21, %22, %23, %24, %25, %26, %27, %28, %29, %30, %31, %32, %33, %34, %35, %36, %37, %38, %39, %40, %41, %42, %43}, %44, %45, p, 1, 1, 0, 1;\n}\n"
        : "+f"(d[0]), "+f"(d[1]), "+f"(d[2]), "+f"(d[3]), "+f"(d[4]), "+f"(d[5]), "+f"(d[6]), "+f"(d[7]), "+f"(d[8]), "+f"(d[9]), "+f"(d[10]), "+f"(d[11]), "+f"(d[12]), "+f"(d[13]), "+f"(d[14]), "+f"(d[15]), "+f"(d[16]), "+f"(d[17]), "+f"(d[18]), "+f"(d[19]), "+f"(d[20]), "+f"(d[21]), "+f"(d[22]), "+f"(d[23]), "+f"(d[24]), "+f"(d[25]), "+f"(d[26]), "+f"(d[27]), "+f"(d[28]), "+f"(d[29]), "+f"(d[30]), "+f"(d[31]), "+f"(d[32]), "+f"(d[33]), "+f"(d[34]), "+f"(d[35]), "+f"(d[36]), "+f"(d[37]), "+f"(d[38]), "+f"(d[39]), "+f"(d[40]), "+f"(d[41]), "+f"(d[42]), "+f"(d[43])
        : "l"(da), "l"(db));
}

#define WG_FENCE() asm volatile("wgmma.fence.sync.aligned;" ::: "memory")
#define WG_COMMIT() asm volatile("wgmma.commit_group.sync.aligned;" ::: "memory")
#define WG_WAIT(n) asm volatile("wgmma.wait_group.sync.aligned %0;" :: "n"(n) : "memory")
template <int NR> __device__ __forceinline__ void fence_regs(float (&d)[NR]) {
#pragma unroll
    for (int i = 0; i < NR; i++) asm volatile("" : "+f"(d[i]) :: "memory");
}
template <int NR> __device__ __forceinline__ void zero_regs(float (&d)[NR]) {
#pragma unroll
    for (int i = 0; i < NR; i++) asm volatile("mov.b32 %0, 0;" : "=f"(d[i]) :: "memory");
}
constexpr uint32_t SW128 = 1u << 30, SW32 = 3u << 30;
__device__ __forceinline__ constexpr uint32_t dlo(uint32_t lbo) { return (lbo >> 4) << 16; }

__device__ __forceinline__ void bar_sync(int id, int n) { asm volatile("bar.sync %0, %1;" :: "r"(id), "r"(n) : "memory"); }
__device__ __forceinline__ void bar_arrive(int id, int n) { asm volatile("bar.arrive %0, %1;" :: "r"(id), "r"(n) : "memory"); }
__device__ __forceinline__ void mbar_init(uint32_t bar, uint32_t cnt) { asm volatile("mbarrier.init.shared::cta.b64 [%0], %1;" :: "r"(bar), "r"(cnt) : "memory"); }
__device__ __forceinline__ void mbar_arrive(uint32_t bar) { asm volatile("mbarrier.arrive.shared::cta.b64 _, [%0];" :: "r"(bar) : "memory"); }
__device__ __forceinline__ void mbar_expect(uint32_t bar, uint32_t bytes) { asm volatile("mbarrier.arrive.expect_tx.shared::cta.b64 _, [%0], %1;" :: "r"(bar), "r"(bytes) : "memory"); }
__device__ __forceinline__ void mbar_wait(uint32_t bar, uint32_t parity) {
    asm volatile("{\n.reg .pred p;\n.reg .u32 n;\nmov.u32 n, 0;\n"
                 "MW_LOOP:\nmbarrier.try_wait.parity.shared::cta.b64 p, [%0], %1;\n@p bra.uni MW_DONE;\n"
                 "add.u32 n, n, 1;\nsetp.lt.u32 p, n, 32768;\n@p bra.uni MW_LOOP;\nMW_DONE:\n}"
                 :: "r"(bar), "r"(parity) : "memory");
}
__device__ __forceinline__ bool mbar_test(uint32_t bar, uint32_t parity) {
    uint32_t r;
    asm volatile("{\n.reg .pred p;\nmbarrier.test_wait.parity.shared::cta.b64 p, [%1], %2;\nselp.u32 %0, 1, 0, p;\n}" : "=r"(r) : "r"(bar), "r"(parity) : "memory");
    return r;
}
__device__ __forceinline__ void count_wait(uint32_t addr, uint32_t seen, uint32_t need) {
    asm volatile("{\n.reg .pred p;\n.reg .u32 n, v;\nmov.u32 n, 0;\nmov.u32 v, %1;\n"
                 "CW_LOOP:\nsetp.ge.u32 p, v, %2;\n@p bra.uni CW_DONE;\nld.volatile.shared.u32 v, [%0];\n"
                 "add.u32 n, n, 1;\nsetp.lt.u32 p, n, 0x400000;\n@p bra.uni CW_LOOP;\nCW_DONE:\n}"
                 :: "r"(addr), "r"(seen), "r"(need) : "memory");
}
__device__ __forceinline__ uint32_t queue_wait(uint32_t addr) {
    uint32_t v;
    asm volatile("{\n.reg .pred p;\n.reg .u32 n;\nmov.u32 n, 0;\n"
                 "QW_LOOP:\nld.acquire.cta.shared::cta.u32 %0, [%1];\nsetp.ne.u32 p, %0, 0;\n@p bra.uni QW_DONE;\n"
                 "add.u32 n, n, 1;\nsetp.lt.u32 p, n, 0x400000;\n@p bra.uni QW_LOOP;\nmov.u32 %0, 1;\nQW_DONE:\n}"
                 : "=r"(v) : "r"(addr) : "memory");
    return v;
}
__device__ __forceinline__ void tma2d(uint32_t dst, const CUtensorMap* m, int x, int y, uint32_t bar) {
    asm volatile("cp.async.bulk.tensor.2d.shared::cluster.global.mbarrier::complete_tx::bytes [%0], [%1, {%2, %3}], [%4];"
                 :: "r"(dst), "l"(m), "r"(x), "r"(y), "r"(bar) : "memory");
}
__device__ __forceinline__ void bulk1d(uint32_t dst, const void* src, uint32_t bytes, uint32_t bar) {
    asm volatile("cp.async.bulk.shared::cluster.global.mbarrier::complete_tx::bytes [%0], [%1], %2, [%3];"
                 :: "r"(dst), "l"(src), "r"(bytes), "r"(bar) : "memory");
}
__device__ __forceinline__ void tma3d(uint32_t dst, const CUtensorMap* m, int y, int z, uint32_t bar) {
    asm volatile("cp.async.bulk.tensor.3d.shared::cluster.global.mbarrier::complete_tx::bytes [%0], [%1, {0, %2, %3}], [%4];"
                 :: "r"(dst), "l"(m), "r"(y), "r"(z), "r"(bar) : "memory");
}
__device__ __forceinline__ void tma2d_store(const CUtensorMap* m, int x, int y, uint32_t src) {
    asm volatile("cp.async.bulk.tensor.2d.global.shared::cta.bulk_group [%0, {%1, %2}], [%3];" :: "l"(m), "r"(x), "r"(y), "r"(src) : "memory");
}
__device__ __forceinline__ void bulk_store(void* dst, uint32_t src, uint32_t bytes) {
    asm volatile("cp.async.bulk.global.shared::cta.bulk_group [%0], [%1], %2;" :: "l"(dst), "r"(src), "r"(bytes) : "memory");
}
__device__ __forceinline__ void bulk_add_f32(void* dst, uint32_t src, uint32_t bytes) {
    asm volatile("cp.reduce.async.bulk.global.shared::cta.bulk_group.add.f32 [%0], [%1], %2;" :: "l"(dst), "r"(src), "r"(bytes) : "memory");
}
__device__ __forceinline__ void bulk_commit() { asm volatile("cp.async.bulk.commit_group;" ::: "memory"); }
__device__ __forceinline__ void bulk_wait() {
    asm volatile("cp.async.bulk.wait_group 0;\nfence.proxy.async.global;" ::: "memory");
}
__device__ __forceinline__ void prefetch_l2(const void* p, uint32_t bytes) { asm volatile("cp.async.bulk.prefetch.L2.global [%0], %1;" :: "l"(p), "r"(bytes) : "memory"); }
__device__ __forceinline__ void prefetch_map(const CUtensorMap* m) { asm volatile("prefetch.tensormap [%0];" :: "l"(m) : "memory"); }
__device__ __forceinline__ uint32_t opaque_tid() { uint32_t t; asm volatile("mov.u32 %0, %tid.x;" : "=r"(t) :: "memory"); return t; }
__device__ __forceinline__ uint32_t opaque_cta() { uint32_t t; asm volatile("mov.u32 %0, %ctaid.x;" : "=r"(t) :: "memory"); return t; }
__device__ __forceinline__ bool elect_one() {
    uint32_t p;
    asm volatile("{\n.reg .pred p;\nelect.sync _|p, 0xffffffff;\nselp.u32 %0, 1, 0, p;\n}" : "=r"(p));
    return p;
}
__device__ __forceinline__ void fence_async() { asm volatile("fence.proxy.async.global;" ::: "memory"); }
__device__ __forceinline__ void fence_async_smem() { asm volatile("fence.proxy.async.shared::cta;" ::: "memory"); }
__device__ __forceinline__ void st_flag(uint16_t* p, uint32_t v) { asm volatile("st.release.gpu.global.u16 [%0], %1;" :: "l"(p), "h"((uint16_t)v) : "memory"); }
__device__ __forceinline__ void st_relaxed(void* p, uint32_t v) { asm volatile("st.relaxed.gpu.global.u32 [%0], %1;" :: "l"(p), "r"(v) : "memory"); }
__device__ __forceinline__ void st_relaxed64(void* p, unsigned long long v) { asm volatile("st.relaxed.gpu.global.u64 [%0], %1;" :: "l"(p), "l"(v) : "memory"); }
__device__ __forceinline__ uint4 ld_relaxed2x64(const void* p) {
    uint4 v;
    asm volatile("{\n.reg .b64 a, b;\nld.relaxed.gpu.global.v2.u64 {a, b}, [%4];\nmov.b64 {%0, %1}, a;\nmov.b64 {%2, %3}, b;\n}" : "=r"(v.x), "=r"(v.y), "=r"(v.z), "=r"(v.w) : "l"(p) : "memory");
    return v;
}
__device__ __forceinline__ uint4 ld_relaxed128(const void* p) { uint4 v; asm volatile("ld.relaxed.gpu.global.v4.u32 {%0, %1, %2, %3}, [%4];" : "=r"(v.x), "=r"(v.y), "=r"(v.z), "=r"(v.w) : "l"(p) : "memory"); return v; }
__device__ __forceinline__ uint4 ld_acquire128(const void* p) { uint4 v; asm volatile("ld.acquire.gpu.global.v4.u32 {%0, %1, %2, %3}, [%4];" : "=r"(v.x), "=r"(v.y), "=r"(v.z), "=r"(v.w) : "l"(p) : "memory"); return v; }
__device__ __forceinline__ void poll1(const uint16_t* p, uint32_t tag) {
#pragma unroll 1
    for (uint32_t spin = 0; spin < (1u << 17); spin++) {
        uint16_t v;
        asm volatile("ld.acquire.gpu.global.u16 %0, [%1];" : "=h"(v) : "l"(p) : "memory");
        if (v == (uint16_t)tag) break;
    }
    fence_async();
}
__device__ __forceinline__ void poll8(const uint16_t* p, uint32_t tag) {
    const uint32_t t2 = (tag & 0xFFFFu) * 0x10001u;
#pragma unroll 1
    for (uint32_t spin = 0; spin < (1u << 17); spin++) {
        const uint4 a = ld_acquire128(p);
        if (a.x == t2 && a.y == t2 && a.z == t2 && a.w == t2) break;
    }
    fence_async();
}
__device__ __forceinline__ uint32_t lds32(uint32_t a) { uint32_t v; asm volatile("ld.shared.u32 %0, [%1];" : "=r"(v) : "r"(a) : "memory"); return v; }
__device__ __forceinline__ void sts32(uint32_t a, uint32_t v) { asm volatile("st.shared.u32 [%0], %1;" :: "r"(a), "r"(v) : "memory"); }
__device__ __forceinline__ void sts16(uint32_t a, uint16_t v) { asm volatile("st.shared.u16 [%0], %1;" :: "r"(a), "h"(v) : "memory"); }
__device__ __forceinline__ void sts64(uint32_t a, uint32_t x, uint32_t y) { asm volatile("st.shared.v2.u32 [%0], {%1, %2};" :: "r"(a), "r"(x), "r"(y) : "memory"); }
__device__ __forceinline__ void sts128(uint32_t a, uint32_t x, uint32_t y, uint32_t z, uint32_t w) { asm volatile("st.shared.v4.u32 [%0], {%1, %2, %3, %4};" :: "r"(a), "r"(x), "r"(y), "r"(z), "r"(w) : "memory"); }
__device__ __forceinline__ uint2 lds64(uint32_t a) { uint2 v; asm volatile("ld.shared.v2.u32 {%0, %1}, [%2];" : "=r"(v.x), "=r"(v.y) : "r"(a) : "memory"); return v; }
__device__ __forceinline__ uint4 lds128(uint32_t a) { uint4 v; asm volatile("ld.shared.v4.u32 {%0, %1, %2, %3}, [%4];" : "=r"(v.x), "=r"(v.y), "=r"(v.z), "=r"(v.w) : "r"(a) : "memory"); return v; }
__device__ __forceinline__ float ex2f(float x) { float y; asm("ex2.approx.ftz.f32 %0, %1;" : "=f"(y) : "f"(x)); return y; }
__device__ __forceinline__ float rcpf(float x) { float y; asm("rcp.approx.ftz.f32 %0, %1;" : "=f"(y) : "f"(x)); return y; }
__device__ __forceinline__ void stsm4(uint32_t a, uint32_t x, uint32_t y, uint32_t z, uint32_t w) {
    asm volatile("stmatrix.sync.aligned.m8n8.x4.shared.b16 [%0], {%1, %2, %3, %4};" :: "r"(a), "r"(x), "r"(y), "r"(z), "r"(w) : "memory");
}
__device__ __forceinline__ uint32_t pack_bf16(float lo, float hi) { uint32_t r; asm("cvt.rn.bf16x2.f32 %0, %1, %2;" : "=r"(r) : "f"(hi), "f"(lo)); return r; }
__device__ __forceinline__ float bf_lo(uint32_t v) { return __uint_as_float(v << 16); }
__device__ __forceinline__ float bf_hi(uint32_t v) { return __uint_as_float(v & 0xFFFF0000u); }
__device__ __forceinline__ uint32_t phi2(float t0, float t1) {
    uint32_t r;
    asm("{\n.reg .b32 one, eps, p, e;\nmov.b32 one, 0x3F803F80;\nmov.b32 eps, 0x35863586;\n"
        "add.rn.bf16x2 p, %1, one;\nmin.bf16x2 e, %2, one;\nmax.NaN.bf16x2 p, p, e;\nadd.rn.bf16x2 %0, p, eps;\n}"
        : "=r"(r) : "r"(pack_bf16(t0, t1)), "r"(pack_bf16(ex2f(t0 * LOG2E), ex2f(t1 * LOG2E))));
    return r;
}
template <int MODE> __device__ __forceinline__ void stage_tile(uint32_t x, uint32_t step, const float (&a)[40]) {
#pragma unroll
    for (int k = 0; k < 5; k++) {
        uint32_t r[4];
#pragma unroll
        for (int e = 0; e < 4; e++) {
            const float t0 = a[8 * k + 2 * e], t1 = a[8 * k + 2 * e + 1];
            r[e] = MODE == 0 ? pack_bf16(t0, t1) : MODE == 1 ? pack_bf16(t0 * QSCALE, t1 * QSCALE) : phi2(t0, t1);
        }
        stsm4(x + 2 * k * step, r[0], r[1], r[2], r[3]);
    }
}

__device__ __forceinline__ uint32_t exp2_pair(float t0, float t1, uint32_t ca) {
    uint32_t y, u, g;
    asm("prmt.b32 %0, %1, %2, 0x6521;" : "=r"(y) : "r"(__float_as_uint(t0)), "r"(__float_as_uint(t1)));
    u = y & 0x007F007Fu;
    asm("{.reg .b32 c; mov.b32 c, 0xF963F963; fma.rn.f16x2 %0, %1, c, %2;}" : "=r"(g) : "r"(u), "r"(ca));
    asm("mul.rn.f16x2 %0, %1, %2;" : "=r"(g) : "r"(g), "r"(u));
    return y - g;
}

__device__ __forceinline__ uint64_t desc(uint32_t addr, uint32_t lbo, uint32_t hi) { return ((uint64_t)hi << 32) | ((addr >> 4) + dlo(lbo)); }
template <int J> __device__ __forceinline__ void exp_steps(const float (&s)[32], uint32_t (&p)[16], float (&o)[12], uint64_t& dv, uint32_t ca) {
    if constexpr (J < 4) {
#pragma unroll
        for (int g = 2 * J; g < 2 * J + 2; g++) {
            if ((MUFU_MASK >> g) & 1) {
                p[2 * g] = pack_bf16(ex2f(s[4 * g]), ex2f(s[4 * g + 1]));
                p[2 * g + 1] = pack_bf16(ex2f(s[4 * g + 2]), ex2f(s[4 * g + 3]));
            } else {
                p[2 * g] = exp2_pair(s[4 * g], s[4 * g + 1], ca);
                p[2 * g + 1] = exp2_pair(s[4 * g + 2], s[4 * g + 3], ca);
            }
        }
        WG_FENCE();
        wg_rs_n24_tb1_d(o, p[4 * J], p[4 * J + 1], p[4 * J + 2], p[4 * J + 3], dv);
        dv += 96;
        exp_steps<J + 1>(s, p, o, dv, ca);
    }
}

struct Ring { uint32_t slot, phase; };
__device__ __forceinline__ void next_stage(Ring& r) { if (++r.slot == 3) { r.slot = 0; r.phase ^= 1; } }

template <bool FAST>
__device__ __forceinline__ void attend(uint32_t sb, uint32_t& slot, int pass, const uint32_t (&q)[6], float (&o)[12], uint32_t ca, uint32_t z0, uint32_t z1) {
    float m0 = -INFINITY, m1 = -INFINITY;
    constexpr int UNR = FAST ? 4 : 1;
#pragma unroll 1
    for (int c = 0; c < 8; c++) {
        const uint32_t base = sb + OFF_RING + slot * RING_BYTES;
        uint64_t dk = desc(base, 128, 768 >> 4), dv = desc(base + 384, 768, 128 >> 4);
        uint32_t seen;
#pragma unroll UNR
        for (int b = 0; b < 4; b++) {
            float s[32];
            uint32_t p[16];
            WG_FENCE();
            wg_rs_n64_tb0_initd(s, q[0], q[1], q[2], q[3], dk);
            dk += 16;
            wg_rs_n64_tb0_d(s, q[4], q[5], z0, z1, dk);
            dk += 368;
            WG_COMMIT();
            if (UNR < 4 || b == 3) seen = lds32(sb + OFF_PUB);
            WG_WAIT(0);
            fence_regs(s);
            if constexpr (FAST) {
                exp_steps<0>(s, p, o, dv, ca);
            } else {
                fence_regs(o);
                float x0 = m0, x1 = m1;
#pragma unroll
                for (int g = 0; g < 8; g++) {
                    if (!((MUFU_MASK >> g) & 1)) {
#pragma unroll
                        for (int e = 0; e < 4; e++) s[4 * g + e] *= 2.f;
                    }
                    x0 = fmaxf(x0, fmaxf(s[4 * g], s[4 * g + 1]));
                    x1 = fmaxf(x1, fmaxf(s[4 * g + 2], s[4 * g + 3]));
                }
                x0 = fmaxf(x0, __shfl_xor_sync(~0u, x0, 1)); x0 = fmaxf(x0, __shfl_xor_sync(~0u, x0, 2));
                x1 = fmaxf(x1, __shfl_xor_sync(~0u, x1, 1)); x1 = fmaxf(x1, __shfl_xor_sync(~0u, x1, 2));
                const float a0 = ex2f(m0 - x0), a1 = ex2f(m1 - x1);
                m0 = x0; m1 = x1;
#pragma unroll
                for (int b = 0; b < 3; b++) { o[4 * b] *= a0; o[4 * b + 1] *= a0; o[4 * b + 2] *= a1; o[4 * b + 3] *= a1; }
#pragma unroll
                for (int g = 0; g < 8; g++) {
                    p[2 * g] = pack_bf16(ex2f(s[4 * g] - x0), ex2f(s[4 * g + 1] - x0));
                    p[2 * g + 1] = pack_bf16(ex2f(s[4 * g + 2] - x1), ex2f(s[4 * g + 3] - x1));
                }
            }
            if constexpr (!FAST) {
                WG_FENCE();
#pragma unroll
                for (int k = 0; k < 4; k++) { wg_rs_n24_tb1_d(o, p[4 * k], p[4 * k + 1], p[4 * k + 2], p[4 * k + 3], dv); dv += 96; }
            }
            WG_COMMIT();
            WG_WAIT(0);
            fence_regs(o);
        }
        if ((threadIdx.x & 31) == 0) mbar_arrive(sb + BAR_EMPTY_KV + slot * 8);
        slot = slot == 2 ? 0 : slot + 1;
        count_wait(sb + OFF_PUB, seen, min(pass * 8 + c + 2, 16));
    }
}

__device__ __forceinline__ void gemm_pass(uint32_t sb, int pass, float (&a)[40], float (&b)[40]) {
    zero_regs(a); zero_regs(b);
    const uint32_t n0 = (__shfl_sync(~0u, pass, 0) - 1) * 10;
    uint32_t slot = n0 % 3, phase = (n0 / 3) & 1;
    const bool lead = (threadIdx.x & 31) == 0;
#pragma unroll 1
    for (int c = 0; c < 10; c++) {
        mbar_wait(sb + BAR_FULL_G + slot * 8, phase);
        const uint32_t st = sb + OFF_STAGE + slot * STAGE_BYTES;
        const uint64_t dx = desc(st, 16, SW128 | 64), dw = desc(st + 16384, 2048, SW32 | 16);
        WG_FENCE();
#pragma unroll
        for (int k = 0; k < 4; k++) {
            wg_ss_n80_ta0_tb1_d(a, dx + 2 * k, dw + 32 * k);
            wg_ss_n80_ta0_tb1_d(b, dx + 512 + 2 * k, dw + 32 * k);
        }
        WG_COMMIT();
        WG_WAIT(0);
        if (lead) mbar_arrive(sb + BAR_EMPTY_G + slot * 8);
        if (++slot == 3) { slot = 0; phase ^= 1; }
    }
    fence_regs(a); fence_regs(b);
}

template <bool SPLIT> __device__ __forceinline__ void gemm_half(uint32_t sb, uint32_t n0_, float (&a)[40]) {
    zero_regs(a);
    const uint32_t n0 = __shfl_sync(~0u, n0_, 0);
    const bool lead = (threadIdx.x & 31) == 0;
#pragma unroll 1
    for (uint32_t c = 0; c < 10; c++) {
        const uint32_t n = n0 + c;
        if (SPLIT && (n == 4 || n == 7)) mbar_wait(sb + BAR_WQ + (n == 4 ? 0 : 8), 0);
        mbar_wait(sb + BAR_FULL_X + (n & 3) * 8, (n >> 2) & 1);
        const uint64_t dx = desc(sb + OFF_XA + (n & 3) * 8192, 16, SW128 | 64), dw = desc(sb + OFF_WA + c * 10240 + (SPLIT ? 8192 : 0), 2048, SW32 | 16);
        const uint64_t dv = desc(sb + OFF_WA + c * 10240, 8192, SW128 | 64);
        WG_FENCE();
#pragma unroll
        for (int k = 0; k < 4; k++) {
            if constexpr (SPLIT) {
                wg_ss_n64_ta0_tb1_d(*reinterpret_cast<float(*)[32]>(&a[0]), dx + 2 * k, dv + 128 * k);
                wg_ss_n16_ta0_tb1_d(*reinterpret_cast<float(*)[8]>(&a[32]), dx + 2 * k, dw + 32 * k);
            } else {
                wg_ss_n80_ta0_tb1_d(a, dx + 2 * k, dw + 32 * k);
            }
        }
        WG_COMMIT();
        WG_WAIT(1);
        if (lead && c) mbar_arrive(sb + BAR_EMPTY_X + ((n - 1) & 3) * 8);
    }
    WG_WAIT(0);
    if (lead) mbar_arrive(sb + BAR_EMPTY_X + ((n0 + 9) & 3) * 8);
    fence_regs(a);
}

__device__ __forceinline__ void mma16816(float (&d)[4], uint32_t a0, uint32_t a1, uint32_t a2, uint32_t a3, uint32_t b0, uint32_t b1) {
    asm volatile("mma.sync.aligned.m16n8k16.row.col.f32.bf16.bf16.f32 {%0, %1, %2, %3}, {%4, %5, %6, %7}, {%8, %9}, {%0, %1, %2, %3};"
                 : "+f"(d[0]), "+f"(d[1]), "+f"(d[2]), "+f"(d[3]) : "r"(a0), "r"(a1), "r"(a2), "r"(a3), "r"(b0), "r"(b1));
}

__device__ __forceinline__ void store_tile(uint32_t stage, __nv_bfloat16* dst, int lane, const float (&a)[40]) {
    stage_tile<0>(stage + (lane & 15) * 160 + (lane >> 4) * 16, 16, a);
    __syncwarp();
#pragma unroll
    for (int u = 0; u < 5; u++) {
        const int x = lane + 32 * u, row = (x * 205) >> 11;
        const uint4 v = lds128(stage + x * 16);
        *reinterpret_cast<uint4*>(dst + row * (1280 - 80) + x * 8) = v;
    }
    __syncwarp();
}

__device__ __forceinline__ void linear_out(uint32_t sb, int half, uint32_t dst, int q) {
    float d[44]; zero_regs(d);
    const uint64_t da = desc(sb + OFF_PK + half * 10240, 128, 80), db = desc(sb + OFF_KVB, 1408, 8);
    WG_FENCE();
#pragma unroll
    for (int k = 0; k < 5; k++) wg_ss_n88_ta0_tb1_d(d, da + 16 * k, db + 176 * k);
    WG_COMMIT();
    WG_WAIT(0);
    fence_regs(d);
    bar_sync(6, 128);
    float r0[4], r1[4];
    const int base = (threadIdx.x & 31) & ~3;
#pragma unroll
    for (int e = 0; e < 4; e++) d[40 + e] = rcpf(d[40 + e] + 1e-6f);
#pragma unroll
    for (int h = 0; h < 4; h++) {
        r0[h] = __shfl_sync(~0u, d[40 + (h & 1)], base + (h >> 1));
        r1[h] = __shfl_sync(~0u, d[42 + (h & 1)], base + (h >> 1));
    }
    uint32_t r[20];
#pragma unroll
    for (int b = 0; b < 10; b++) {
        const int hl = (8 * b) / 20, hh = (8 * b + 6) / 20;
        const bool up = hl != hh && q >= 2;
        const float s0 = up ? r0[hh] : r0[hl], s1 = up ? r1[hh] : r1[hl];
        r[2 * b] = pack_bf16(d[4 * b] * s0, d[4 * b + 1] * s0);
        r[2 * b + 1] = pack_bf16(d[4 * b + 2] * s1, d[4 * b + 3] * s1);
    }
#pragma unroll
    for (int k = 0; k < 5; k++) stsm4(dst + 32 * k, r[4 * k], r[4 * k + 1], r[4 * k + 2], r[4 * k + 3]);
}

__global__ void __launch_bounds__(NTHR, 1) fused_kernel(const __grid_constant__ Params P) {
    extern __shared__ __align__(1024) uint8_t smem[];
    const uint32_t sb = (uint32_t)__cvta_generic_to_shared(smem);
    const int tid = threadIdx.x, lane = tid & 31;
    const int wg = __shfl_sync(~0u, tid >> 7, 0), warp = __shfl_sync(~0u, (tid >> 5) & 3, 0);
    const int cta = blockIdx.x, i = cta >> 3, j = cta & 7;
    const int q = lane & 3, r0 = 16 * warp + (lane >> 2);
    if (wg == 4 || wg == 0) TS(wg == 4 ? 0 : 16);

    const uint32_t tag = *(volatile uint32_t*)&g_epoch + 1;

    if (cta >= NCTA) {
        if (tid < 64 && elect_one()) {
            const int jj = 2 * (cta - NCTA) + warp;
            const uint32_t buf = sb + warp * 102400, bar = sb + OFF_BAR + warp * 80;
#pragma unroll 1
            for (int s = 0; s < 10; s++) mbar_init(bar + s * 8, 1);
            asm volatile("fence.mbarrier_init.release.cluster;" ::: "memory");
            int lp = 0, lc = 0;
#pragma unroll 1
            for (int n = -8; n < 40; n++) {
                if (n >= 0) {
                    const int part = n / 10, c = n - 10 * part;
                    mbar_wait(bar + c * 8, part & 1);
                    bulk_store(g_wt + ((part * 8 + jj) * 10 + c) * 10240, buf + c * 10240, 10240);
                    bulk_commit();
                    if (c == 9) { bulk_wait(); st_flag(g_flag_w + part * 8 + jj, tag); }
                    else asm volatile("cp.async.bulk.wait_group.read 2;" ::: "memory");
                }
                if (lp < 4) {
                    mbar_expect(bar + lc * 8, 10240);
                    tma3d(buf + lc * 10240, lp < 2 ? &P.wqkv : lp == 2 ? &P.wob : &P.woa, 64 * lc, 5 * jj + (lp == 0 ? 80 : 0), bar + lc * 8);
                    if (++lc == 10) { lc = 0; lp++; }
                }
            }
        }
        return;
    }
    if (tid == 640) {
        mbar_init(sb + BAR_KVIN, 1);
        asm volatile("fence.mbarrier_init.release.cluster;" ::: "memory");
        mbar_expect(sb + BAR_KVIN, 51200 + 20480);
        tma3d(sb + OFF_X16, &P.xa16, 16 * cta, 0, sb + BAR_KVIN);
#pragma unroll
        for (int u = 0; u < 4; u++) {
            const int v = (u + cta) & 3;
            bulk1d(sb + OFF_WRAW + v * 12800, P.in[2 + (v >> 1)] + (v & 1) * 12800, 12800, sb + BAR_KVIN);
        }
    } else if (tid == 672) {
#pragma unroll
        for (int s = 0; s < 3; s++) {
            mbar_init(sb + BAR_FULL_G + s * 8, 2);
            mbar_init(sb + BAR_EMPTY_G + s * 8, 4);
            mbar_init(sb + BAR_FULL_KV + s * 8, 1);
            mbar_init(sb + BAR_EMPTY_KV + s * 8, 16);
        }
        mbar_init(sb + BAR_OA, 16);
        mbar_init(sb + BAR_OA + 8, 16);
        asm volatile("fence.mbarrier_init.release.cluster;" ::: "memory");
    } else if (tid == 704) {
        prefetch_map(&P.xa);
        prefetch_map(&P.wq64);
        prefetch_map(&P.wq16);
        prefetch_l2(P.in[1] + cta * 6400, 6400);
        mbar_init(sb + BAR_WA, 1);
        mbar_init(sb + BAR_PART, 4);
        mbar_init(sb + BAR_KVB, 1);
        mbar_init(sb + BAR_OB, 4);
        sts32(sb + OFF_PUB, 0);
        sts128(sb + OFF_STAT + 16, 0x357F357Fu, 0u, 0u, 0u);
        asm volatile("fence.mbarrier_init.release.cluster;" ::: "memory");
    } else if (tid == 736) {
#pragma unroll
        for (int s = 0; s < 4; s++) { mbar_init(sb + BAR_FULL_X + s * 8, 1); mbar_init(sb + BAR_EMPTY_X + s * 8, 4); }
#pragma unroll
        for (int s = 0; s < 4; s++) sts128(sb + OFF_QUEUE + s * 16, 0u, 0u, 0u, 0u);
        mbar_init(sb + BAR_A0, 1);
        mbar_init(sb + BAR_Q, 4);
        mbar_init(sb + BAR_Q + 8, 4);
        mbar_init(sb + BAR_C0, 16);
        for (int s = 0; s < 2; s++) mbar_init(sb + BAR_WQ + s * 8, 1);
        asm volatile("fence.mbarrier_init.release.cluster;" ::: "memory");
    }
    __syncthreads();

    if (wg == 5) {
        asm volatile("setmaxnreg.dec.sync.aligned.u32 32;");
        if (warp == 0) {
            if (elect_one()) {
#pragma unroll 1
                for (int n = 0; n < 20; n++) {
                    const uint32_t s = n & 3, bar = sb + BAR_FULL_X + s * 8;
                    if (n >= 4) mbar_wait(sb + BAR_EMPTY_X + s * 8, ((n >> 2) - 1) & 1);
                    mbar_expect(bar, n < 4 ? 18432 : 8192);
                    tma2d(sb + OFF_XA + s * 8192, &P.xa, n < 10 ? 64 * n : 64 * n - 640, 128 * i + (n < 10 ? 0 : 64), bar);
                    if (n < 4) {
                        tma2d(sb + OFF_WA + n * 10240, &P.wq64, 80 * j, 64 * n, bar);
                        tma2d(sb + OFF_WA + n * 10240 + 8192, &P.wq16, 80 * j + 64, 64 * n, bar);
                    }
                    if (n == 3) {
                        mbar_expect(sb + BAR_WQ, 30720);
                        mbar_expect(sb + BAR_WQ + 8, 30720);
#pragma unroll 1
                        for (int c = 4; c < 10; c++) {
                            tma2d(sb + OFF_WA + c * 10240, &P.wq64, 80 * j, 64 * c, sb + BAR_WQ + (c < 7 ? 0 : 8));
                            tma2d(sb + OFF_WA + c * 10240 + 8192, &P.wq16, 80 * j + 64, 64 * c, sb + BAR_WQ + (c < 7 ? 0 : 8));
                        }
                    }
                }
                Ring r{0, 0};
#pragma unroll 1
                for (int pass = 1; pass < 5; pass++) {
                    const CUtensorMap* m = pass <= 3 ? &P.xb : &P.ob;
                    if (pass == 4) {
                        mbar_wait(sb + BAR_OB, 0);
                        tma2d_store(&P.ob_st, 80 * j, 128 * i, sb + OFF_PK);
                        bulk_commit();
                        bulk_wait();
                        st_flag(g_flag_b2 + cta, tag);
                        poll8(g_flag_b2 + i * 8, tag);
                    }
#pragma unroll 1
                    for (int c = 0; c < 10; c++) {
                        if (pass == 3 && c == 3) {
                            mbar_wait(sb + BAR_PART, 0);
                            bulk_add_f32(g_part + j * 1920, sb + OFF_PST, 7680);
                            bulk_commit();
                        }
                        mbar_wait(sb + BAR_EMPTY_G + r.slot * 8, r.phase);
                        mbar_expect(sb + BAR_FULL_G + r.slot * 8, 16384);
                        tma2d(sb + OFF_STAGE + r.slot * STAGE_BYTES, m, 64 * c, 128 * i, sb + BAR_FULL_G + r.slot * 8);
                        next_stage(r);
                        if (pass == 3 && c == 3) {
                            bulk_wait();
                            st_flag(g_flag_b1 + j * 16 + i, tag);
                        }
                    }
                }
                {
                    poll8(g_flag_a + i * 8, tag);
                    mbar_arrive(sb + BAR_A0);
#pragma unroll 1
                    for (int c = 0; c < 10; c++) {
                        const uint32_t s = c & 3;
                        mbar_wait(sb + BAR_EMPTY_X + s * 8, (c >> 2) & 1);
                        mbar_expect(sb + BAR_FULL_X + s * 8, 8192);
                        tma2d(sb + OFF_XA + s * 8192, &P.oa, 64 * c, 128 * i, sb + BAR_FULL_X + s * 8);
                    }
                }
            }
        } else if (warp == 2) {
            if (elect_one()) {
                Ring r{0, 0};
#pragma unroll 1
                for (int pass = 1; pass < 5; pass++) {
                    const CUtensorMap* m = pass <= 3 ? &P.wqkv : &P.wob;
                    const int col = 5 * j + (pass == 1 ? 40 : pass == 2 ? 80 : 0);
                    const bool pre = pass >= 2 && P.helpers;
                    if (pre) poll1(g_flag_w + (pass - 2) * 8 + j, tag);
#pragma unroll 1
                    for (int c = 0; c < 10; c++) {
                        mbar_wait(sb + BAR_EMPTY_G + r.slot * 8, r.phase);
                        const uint32_t bar = sb + BAR_FULL_G + r.slot * 8;
                        mbar_expect(bar, 10240);
                        const uint32_t dst = sb + OFF_STAGE + r.slot * STAGE_BYTES + 16384;
                        if (pre) bulk1d(dst, g_wt + (((pass - 2) * 8 + j) * 10 + c) * 10240, 10240, bar);
                        else tma3d(dst, m, 64 * c, col, bar);
                        next_stage(r);
                    }
                }
                {
                    if (P.helpers) poll1(g_flag_w + 24 + j, tag);
#pragma unroll 1
                    for (int c = 0; c < 3; c++) { mbar_wait(sb + BAR_EMPTY_G + r.slot * 8, r.phase); next_stage(r); }
                    mbar_expect(sb + BAR_WA, 102400);
                    if (P.helpers) bulk1d(sb + OFF_WA, g_wt + (24 + j) * 102400, 102400, sb + BAR_WA);
                    else {
#pragma unroll 1
                        for (int c = 0; c < 10; c++) tma3d(sb + OFF_WA + c * 10240, &P.woa, 64 * c, 5 * j, sb + BAR_WA);
                    }
                }
            }
        } else if (warp == 3) {
            bar_sync(12, 96);
            if (elect_one()) {
                st_flag(g_flag_kv + cta, tag);
                prefetch_l2(P.in[5] + cta * 20480, 20480);
#pragma unroll 1
                for (int u = 0; u < 5; u++) prefetch_l2(P.in[6] + (cta * 5 + u) * 3840 + 1280, 1280);
            }
            __syncwarp();
            {
                if (elect_one()) {
                    poll8(g_flag_b1 + j * 16, tag);
                    poll8(g_flag_b1 + j * 16 + 8, tag);
                    mbar_expect(sb + BAR_KVB, 7680);
                    bulk1d(sb + OFF_PST, g_part + j * 1920, 7680, sb + BAR_KVB);
                }
            }
            if (elect_one()) {
                mbar_wait(sb + BAR_OA, 0);
                tma2d_store(&P.oa_st, 80 * j, 128 * i, sb + OFF_Q);
                bulk_commit();
                bulk_wait();
                st_flag(g_flag_a + cta, tag);
            }
        } else if (warp == 1) {
            uint32_t sk, spin = 0;
            bar_sync(12, 96);
            __nanosleep(1000);
#pragma unroll 1
            while (true) {
                const uint4 f = ld_relaxed128(g_stat + 4 * lane);
                const uint32_t t = tag << 16;
                sk = max(max(f.x ^ t, f.y ^ t), max(f.z ^ t, f.w ^ t));
                sk = __reduce_max_sync(~0u, sk);
                if (sk < 0x10000u || ++spin > (1u << 17)) break;
            }
            if (lane == 0) {
                sts32(sb + OFF_STAT, sk << 16);
            }
            mbar_wait(sb + BAR_C0, 0);
            if (lane == 0) {
                mbar_arrive(sb + BAR_FULL_KV);
                asm volatile("st.release.cta.shared::cta.u32 [%0], %1;" :: "r"(sb + OFF_PUB), "r"(1) : "memory");
            }
            __syncwarp();
            __nanosleep(300);
            const uint32_t t2 = (tag & 0xFFFFu) * 0x10001u;
#pragma unroll 1
            for (spin = 0; spin < (1u << 17); spin++) {
                const uint4 f = ld_acquire128(g_flag_kv + 8 * (lane & 15));
                if (__all_sync(~0u, f.x == t2 && f.y == t2 && f.z == t2 && f.w == t2)) break;
            }
            if (elect_one()) {
                fence_async();
                const uint32_t rot = i >> 1;
#pragma unroll 1
                for (int n = 1; n < 3; n++) {
                    mbar_expect(sb + BAR_FULL_KV + n * 8, RING_BYTES);
                    bulk1d(sb + OFF_RING + n * RING_BYTES, g_kv + ((n + rot) & 7) * RING_BYTES, RING_BYTES, sb + BAR_FULL_KV + n * 8);
                }
                Ring r{1, 0};
#pragma unroll 1
                for (int n = 1; n < 16; n++) {
                    if (n >= 3) {
                        mbar_wait(sb + BAR_EMPTY_KV + r.slot * 8, r.phase ^ 1);
                        mbar_expect(sb + BAR_FULL_KV + r.slot * 8, RING_BYTES);
                        bulk1d(sb + OFF_RING + r.slot * RING_BYTES, g_kv + ((n + rot) & 7) * RING_BYTES, RING_BYTES, sb + BAR_FULL_KV + r.slot * 8);
                    }
                    mbar_wait(sb + BAR_FULL_KV + r.slot * 8, r.phase);
                    asm volatile("st.release.cta.shared::cta.u32 [%0], %1;" :: "r"(sb + OFF_PUB), "r"(n + 1) : "memory");
                    next_stage(r);
                }
            }
        }
    } else if (wg < 4) {
        if (tid < 30) reinterpret_cast<uint4*>(g_part + j * 1920 + i * 120)[tid] = make_uint4(0u, 0u, 0u, 0u);
        if (wg < 2) {
            const uint32_t kw = 4 * wg + warp, g = lane >> 2;
            const uint32_t w0 = sb + OFF_WRAW + (80 * kw + 4 * q) * 40;
            const uint32_t wa[3] = {w0 + g * 4, w0 + g * 4 + 25608, w0 + 32 + (g & 1) * 4 + (g & 2) * 12784};
            float d[3][2][4];
#pragma unroll
            for (int e = 0; e < 24; e++) (&d[0][0][0])[e] = 0.f;
            mbar_wait(sb + BAR_KVIN, 0);
            if (wg == 0) TS(13);
            uint2 x[2][2];
            uint32_t u[2][12];
#pragma unroll
            for (int s = 0; s < 6; s++) {
                if (s < 5) {
                    const uint32_t st = 5 * kw + s;
                    const uint32_t xa = sb + OFF_X16 + (st >> 2) * 2048 + g * 128 + (((2 * (st & 3) + (q >> 1)) ^ g) << 4) + (q & 1) * 8;
                    x[s & 1][0] = lds64(xa); x[s & 1][1] = lds64(xa + 1024);
#pragma unroll
                    for (int e = 0; e < 12; e++) u[s & 1][e] = lds32(wa[e >> 2] + s * 640 + (e & 3) * 40);
                }
                if (s > 0) {
                    const int p = (s - 1) & 1;
#pragma unroll
                    for (int t = 0; t < 3; t++) {
                        const uint32_t a0 = __byte_perm(u[p][4 * t], u[p][4 * t + 1], 0x5410), a1 = __byte_perm(u[p][4 * t], u[p][4 * t + 1], 0x7632);
                        const uint32_t a2 = __byte_perm(u[p][4 * t + 2], u[p][4 * t + 3], 0x5410), a3 = __byte_perm(u[p][4 * t + 2], u[p][4 * t + 3], 0x7632);
                        mma16816(d[t][0], a0, a1, a2, a3, x[p][0].x, x[p][0].y);
                        mma16816(d[t][1], a0, a1, a2, a3, x[p][1].x, x[p][1].y);
                    }
                }
            }
            bar_arrive(2, 384);
#pragma unroll
            for (int t = 0; t < 3; t++) {
                const uint32_t pr = t == 0 ? g : t == 1 ? 12 + g : 8 + g;
                if (t < 2 || g < 4) {
#pragma unroll
                    for (int h = 0; h < 2; h++) {
                        const uint32_t a = sb + OFF_KVP + kw * 2560 + ((8 * h + 2 * q) * 20 + pr) * 8;
                        sts64(a, __float_as_uint(d[t][h][0]), __float_as_uint(d[t][h][2]));
                        sts64(a + 160, __float_as_uint(d[t][h][1]), __float_as_uint(d[t][h][3]));
                    }
                }
            }
            if (wg == 0) TS(14);
        }
        bar_sync(1, 512);
        if (wg < 3) {
            const uint32_t ch = 4 * wg + warp, grp = ch >= 6, c6 = ch - 6 * grp, isv = c6 >= 3, c3 = c6 - 3 * isv;
            const uint32_t key = 8 * grp + (lane >> 2);
            const bool mu = (MUFU_MASK >> ((2 * cta + grp) & 7)) & 1;
            uint32_t word;
            if (c3 == 2 && q >= 2) {
                word = isv ? (q == 2 ? 0x00003F80u : 0u) : mu ? 0u : q == 2 ? 0x3F00433Fu : 0x00003B4Au;
            } else {
                const uint32_t a = sb + OFF_KVP + (key * 20 + 10 * isv + 4 * c3 + q) * 8;
                float s0 = 0.f, s1 = 0.f;
#pragma unroll
                for (int u = 0; u < 8; u++) { const uint2 v = lds64(a + u * 2560); s0 += __uint_as_float(v.x); s1 += __uint_as_float(v.y); }
                const float sc = (isv || mu) ? 1.f : 0.5f;
                word = pack_bf16(s0 * sc, s1 * sc);
            }
            st_relaxed64(g_kt + cta * 384 + tid, ((unsigned long long)tag << 32) | word);
            reinterpret_cast<uint32_t*>(g_kv + cta * 1536)[tid] = word;
            if (c3 == 2 && q >= 2) word = 0;
            if (isv) {
                const uint32_t mx = __reduce_max_sync(~0u, max(word & 0x7FFFu, (word >> 16) & 0x7FFFu));
                if (lane == 0) sts32(sb + OFF_KST + 192 + (3 * grp + c3) * 4, mx);
            } else {
                float n2 = fmaf(bf_lo(word), bf_lo(word), bf_hi(word) * bf_hi(word));
                n2 += __shfl_xor_sync(~0u, n2, 1);
                n2 += __shfl_xor_sync(~0u, n2, 2);
                if (q == 0) sts32(sb + OFF_KST + (c3 * 16 + key) * 4, __float_as_uint(mu ? n2 : 4.f * n2));
            }
            if (wg | warp) bar_arrive(3, 384);
            else {
                bar_sync(3, 384);
                TS(15);
                const uint32_t a = sb + OFF_KST + (lane & 15) * 4;
                const float n2 = __uint_as_float(lds32(a)) + __uint_as_float(lds32(a + 64)) + __uint_as_float(lds32(a + 128));
                const uint32_t sk = __reduce_max_sync(~0u, min(((__float_as_uint(n2) & 0x7FFFFFFFu) + 0xFFFFu) >> 16, 0x7FFFu));
                const uint32_t sv = __reduce_max_sync(~0u, lds32(sb + OFF_KST + 192 + min(lane, 5) * 4));
                if (lane == 0) {
                    const bool vok = sv == 0 || (sv >= ((127 - 40) << 7) && sv <= ((127 + 40) << 7));
                    st_relaxed(g_stat + cta, (tag << 16) | (vok ? sk : 0x7FFFu));
                }
                __syncwarp();
                bar_arrive(12, 96);
                TS(17);
            }
        }
        {
            const unsigned long long* src = g_kt + (i >> 1) * 6144 + tid * 2;
            uint4 v[6];
#pragma unroll
            for (int u = 0; u < 6; u++) v[u] = make_uint4(0u, ~tag, 0u, 0u);
            __nanosleep(700);
#pragma unroll 1
            for (uint32_t spin = 0; spin < (1u << 16); spin++) {
#pragma unroll
                for (int u = 0; u < 6; u++) if (v[u].y != tag) v[u] = ld_relaxed2x64(src + u * 1024);
                bool ok = true;
#pragma unroll
                for (int u = 0; u < 6; u++) { if (v[u].w != tag) v[u].y = ~tag; ok = ok && v[u].y == tag; }
                if (__all_sync(~0u, ok)) break;
            }
#pragma unroll
            for (int u = 0; u < 6; u++) sts64(sb + OFF_RING + tid * 8 + u * 4096, v[u].x, v[u].z);
            fence_async_smem();
            __syncwarp();
            if (lane == 0) mbar_arrive(sb + BAR_C0);
            if (wg == 0) TS(7);
        }
        uint32_t slot = 0;
        const uint4 cz = lds128(sb + OFF_STAT + 16);
#pragma unroll 1
        for (int pass = 0; pass < 2; pass++) {
            uint32_t qf[6];
            mbar_wait(sb + BAR_Q + pass * 8, 0);
            const uint32_t qa = sb + OFF_Q + pass * 10240 + r0 * 160 + wg * 40 + q * 4;
            qf[0] = lds32(qa); qf[1] = lds32(qa + 8 * 160);
            qf[2] = lds32(qa + 16); qf[3] = lds32(qa + 8 * 160 + 16);
            qf[4] = q < 2 ? lds32(qa + 32) : 0u; qf[5] = q < 2 ? lds32(qa + 8 * 160 + 32) : 0u;
            if (pass == 0) { count_wait(sb + OFF_PUB, 0, 1); if (wg == 0) { TS(19); TC(26); } }
            float n0 = 0.f, n1 = 0.f;
#pragma unroll
            for (int e = 0; e < 3; e++) {
                n0 = fmaf(bf_lo(qf[2 * e]), bf_lo(qf[2 * e]), fmaf(bf_hi(qf[2 * e]), bf_hi(qf[2 * e]), n0));
                n1 = fmaf(bf_lo(qf[2 * e + 1]), bf_lo(qf[2 * e + 1]), fmaf(bf_hi(qf[2 * e + 1]), bf_hi(qf[2 * e + 1]), n1));
            }
            n0 += __shfl_xor_sync(~0u, n0, 1); n0 += __shfl_xor_sync(~0u, n0, 2);
            n1 += __shfl_xor_sync(~0u, n1, 1); n1 += __shfl_xor_sync(~0u, n1, 2);
            const float k2 = __uint_as_float(lds32(sb + OFF_STAT));
            const uint32_t bad = !(n0 * k2 <= 4000.f && n1 * k2 <= 4000.f);
            uint32_t anybad;
            asm volatile("{\n.reg .pred p, r;\nsetp.ne.u32 p, %1, 0;\nbar.red.or.pred r, %2, 128, p;\nselp.u32 %0, 1, 0, r;\n}" : "=r"(anybad) : "r"(bad), "r"(8 + wg) : "memory");
            float o[12];
#pragma unroll
            for (int k = 0; k < 12; k++) o[k] = 0.f;
            fence_regs(o);
            if (!__shfl_sync(~0u, anybad, 0)) {
                if (q >= 2) qf[4] = qf[5] = q == 2 ? 0x3F803F80u : 0x00003F80u;
                attend<true>(sb, slot, pass, qf, o, cz.x, cz.y, cz.z);
            } else {
                attend<false>(sb, slot, pass, qf, o, cz.x, cz.y, cz.z);
            }
            const float i0 = rcpf(__shfl_sync(~0u, o[8], (lane & ~3) | 2)), i1 = rcpf(__shfl_sync(~0u, o[10], (lane & ~3) | 2));
            const uint32_t ot = opaque_tid(), ol = ot & 31, oq = ot & 3;
            uint8_t* const gx = g_ox + opaque_cta() * 10240;
#pragma unroll
            for (int b = 0; b < 3; b++) {
                if (b < 2 || oq < 2) {
                    const uint32_t v0 = pack_bf16(o[4 * b] * i0, o[4 * b + 1] * i0), v1 = pack_bf16(o[4 * b + 2] * i1, o[4 * b + 3] * i1);
                    const uint32_t col = 20 * (ot >> 7) + 8 * b + 2 * oq;
                    const uint32_t x = (col >> 4) * 2048 + (ot & 96) * 16 + (col & 8) * 16 + (ol >> 2) * 16 + (col & 7) * 2;
                    st_relaxed(gx + x, pass ? v0 : ~0u);
                    st_relaxed(gx + x + 256, pass ? v1 : ~0u);
                    const uint32_t dst = sb + OFF_Q + (pass ? 10240 + x : (((ot & 96) >> 1) + (ol >> 2)) * 160 + col * 2);
                    sts32(dst, v0);
                    sts32(dst + (pass ? 256 : 8 * 160), v1);
                }
            }
            fence_async_smem();
            __syncwarp();
            if (lane == 0) mbar_arrive(sb + BAR_OA + pass * 8);
            if (wg == 0) { TS(20 + pass); TC(27 + pass); }
        }
        TS(22 + wg);
        {
            const uint32_t ot = opaque_tid(), oc = opaque_cta();
            const int lane = ot & 31, i = oc >> 3, j = oc & 7;
            if (wg != 0) {
                const int u = 4 * (3 - wg) + warp;
                uint4 v[12];
                const uint8_t* src[3];
                uint32_t entry = u + 1;
#pragma unroll
                for (int t = 0; t < 3; t++) {
                    const int s = min(3 * u + t, 34), h = (s * 37) >> 8;
                    const int g = 5 * ((j + 1 + s - 7 * h) & 7) + 4 - h;
                    src[t] = g_ox + (i * 40 + g) * 2048 + lane * 16;
                    entry |= g << (8 * t + 8);
                }
#pragma unroll
                for (int k = 0; k < 12; k++) v[k] = make_uint4(k >= 8 && u == 11 ? 0u : ~0u, 0u, 0u, 0u);
                const uint8_t* const probe = (lane < 8 ? src[0] : lane < 16 ? src[1] : src[2]) - lane * 16 + (lane & 6) * 256 + (lane & 1) * 128 + 368;
                uint32_t wait = u == 11 ? 0xFFFFu : 0xFFFFFFu;
                mbar_wait(sb + BAR_A0, 0);
#pragma unroll 1
                for (uint32_t spin = 0; spin < (1u << 16); spin++) {
                    uint4 p = make_uint4(0u, 0u, 0u, 0u);
                    if (mbar_test(sb + BAR_OA + 8, 0)) wait = 0;
                    if ((wait >> lane) & 1) p = ld_relaxed128(probe);
#pragma unroll
                    for (int k = 0; k < 12; k++) if (!((wait >> (2 * (k & 12))) & 0xFF) && v[k].x == ~0u) v[k] = ld_relaxed128(src[k >> 2] + (k & 3) * 512);
                    wait = __ballot_sync(~0u, p.x == ~0u || p.w == ~0u);
                    bool ok = true;
#pragma unroll
                    for (int k = 0; k < 12; k++) {
                        if (v[k].y == ~0u || v[k].z == ~0u || v[k].w == ~0u) v[k].x = ~0u;
                        ok = ok && v[k].x != ~0u;
                    }
                    if (__all_sync(~0u, ok)) break;
                }
                mbar_wait(sb + BAR_OA + 8, 0);
#pragma unroll
                for (int k = 0; k < 12; k++) sts128(sb + OFF_RING + u * 6144 + k * 512 + lane * 16, v[k].x, v[k].y, v[k].z, v[k].w);
                fence_async_smem();
                __syncwarp();
                if (lane == 0) {
                    uint32_t n;
                    asm volatile("atom.relaxed.cta.shared::cta.add.u32 %0, [%1], 1;" : "=r"(n) : "r"(sb + OFF_QUEUE + 48) : "memory");
                    asm volatile("st.release.cta.shared::cta.u32 [%0], %1;" :: "r"(sb + OFF_QUEUE + n * 4), "r"(entry) : "memory");
                }
            } else {
                float a[40];
                mbar_wait(sb + BAR_WA, 0);
                mbar_wait(sb + BAR_OA + 8, 0);
                const uint64_t dw = desc(sb + OFF_WA, 2048, SW32 | 16);
                {
                    const uint64_t da = desc(sb + OFF_Q + 10240, 128, 16);
                    WG_FENCE();
#pragma unroll
                    for (int t = 0; t < 5; t++) {
                        const uint32_t g = 5 * j + t;
                        if (t == 0) wg_ss_n80_ta0_tb1_initd(a, da, dw + (g >> 2) * 640 + (g & 3) * 32);
                        else wg_ss_n80_ta0_tb1_d(a, da + 128 * t, dw + (g >> 2) * 640 + (g & 3) * 32);
                    }
                    WG_COMMIT();
                }
#pragma unroll 1
                for (int n = 0; n < 12; n++) {
                    const uint32_t e = __shfl_sync(~0u, queue_wait(sb + OFF_QUEUE + n * 4), 0);
                    const uint64_t da = desc(sb + OFF_RING - 6144 + (e & 15) * 6144, 128, 16);
                    WG_FENCE();
#pragma unroll
                    for (int t = 0; t < 3; t++) {
                        const uint32_t g = (e >> (8 * t + 8)) & 63;
                        wg_ss_n80_ta0_tb1_d(a, da + 128 * t, dw + (g >> 2) * 640 + (g & 3) * 32);
                    }
                    WG_COMMIT();
                }
                WG_WAIT(0);
                fence_regs(a);
                bar_sync(8, 128);
                store_tile(sb + OFF_Q + 10240 + warp * 2560, P.out + (128 * i + 64 + 16 * warp) * 1280 + 80 * j, lane, a);
                TS(11);
            }
        }
    } else {
        asm volatile("setmaxnreg.inc.sync.aligned.u32 128;");
        const uint32_t mrow = 16 * warp + (lane & 15), mcol = lane >> 4;
        const uint32_t xrow = mrow * 160 + mcol * 16, xgrp = (mrow & 7) * 16 + mcol * 128;
        bar_sync(2, 384);
#pragma unroll 1
        for (int half = 0; half < 2; half++) {
            float a[40];
            gemm_half<true>(sb, 10 * half, a);
            if (!half) TS(1);
            if (half && lane == 0) { mbar_arrive(sb + BAR_EMPTY_G); mbar_arrive(sb + BAR_EMPTY_G + 8); mbar_arrive(sb + BAR_EMPTY_G + 16); }
            stage_tile<1>(sb + OFF_Q + half * 10240 + xrow, 16, a);
            __syncwarp();
            if (lane == 0) mbar_arrive(sb + BAR_Q + half * 8);
            if (half) TS(2);
        }
#pragma unroll 1
        for (int pass = 1; pass < 5; pass++) {
        if (pass == 4) {
        mbar_wait(sb + BAR_KVB, 0);
        if (tid < 592) {
            const int m = tid - 512, h = m / 20;
            const uint32_t x0 = sb + OFF_KVB + (m >> 3) * 1408 + (m & 7) * 16;
#pragma unroll
            for (int e = 0; e < 5; e++) {
                const uint4 v = lds128(sb + OFF_PST + m * 96 + e * 16);
                const int n = 20 * h + 4 * e;
                sts64(x0 + (n >> 3) * 128 + (n & 4) * 2, pack_bf16(__uint_as_float(v.x), __uint_as_float(v.y)), pack_bf16(__uint_as_float(v.z), __uint_as_float(v.w)));
            }
            sts16(x0 + 1280 + h * 2, (uint16_t)pack_bf16(__uint_as_float(lds32(sb + OFF_PST + m * 96 + 80)), 0.f));
        }
        fence_async_smem();
        bar_sync(6, 128);
#pragma unroll 1
        for (int half = 0; half < 2; half++) linear_out(sb, half, sb + OFF_PK + half * 10240 + xrow, q);
        fence_async_smem();
        __syncwarp();
        if (lane == 0) mbar_arrive(sb + BAR_OB);
        }
        float a[40], b[40];
        gemm_pass(sb, pass, a, b);
        if (pass == 1 || pass == 3) {
        TS(pass == 1 ? 3 : 6);
        stage_tile<2>(sb + OFF_PK + (mrow >> 3) * 1280 + xgrp, 128, a);
        stage_tile<2>(sb + OFF_PK + (8 + (mrow >> 3)) * 1280 + xgrp, 128, b);
        } else if (pass == 2) {
        TS(4);
        stage_tile<0>(sb + OFF_V + 128 + (mrow >> 3) * 1536 + xgrp, 128, a);
        stage_tile<0>(sb + OFF_V + 128 + (8 + (mrow >> 3)) * 1536 + xgrp, 128, b);
        {
            const uint32_t x = sb + OFF_V + ((tid - 512) >> 3) * 1536 + (tid & 7) * 16;
            sts128(x, 0x3F80u, 0u, 0u, 0u);
            sts128(x + 11 * 128, 0x3F80u, 0u, 0u, 0u);
        }
        fence_async_smem();
        bar_sync(6, 128);
        {
            float d1[36], d2[16]; zero_regs(d1); zero_regs(d2);
            const uint64_t da = desc(sb + OFF_PK, 1280, 8), db = desc(sb + OFF_V, 1536, 8);
            WG_FENCE();
#pragma unroll
            for (int k = 0; k < 8; k++) {
                wg_ss_n72_ta1_tb1_d(d1, da + 160 * k, db + 192 * k);
                wg_ss_n32_ta1_tb1_d(d2, da + 16 + 160 * k, db + 64 + 192 * k);
            }
            WG_COMMIT();
            WG_WAIT(0);
            fence_regs(d1); fence_regs(d2);
            bar_sync(6, 128);
#pragma unroll
            for (int u = 0; u < 7; u++) if (u < 6 || tid < 624) sts128(sb + OFF_KVB + (tid - 512 + 128 * u) * 16, 0u, 0u, 0u, 0u);
            const uint32_t part = sb + OFF_PST;
#pragma unroll
            for (int hh = 0; hh < 2; hh++) {
                const int m = r0 + 8 * hh;
                if (m < 60) {
                    const int h20 = (m / 20) * 20;
                    if (q == 0) sts128(part + m * 96 + 80, __float_as_uint(d1[2 * hh]), 0u, 0u, 0u);
#pragma unroll
                    for (int k = 1; k < 9; k++) {
                        const int e = 8 * (k - 1) + 2 * q - h20;
                        if (e >= 0 && e < 20) sts64(part + m * 96 + e * 4, __float_as_uint(d1[4 * k + 2 * hh]), __float_as_uint(d1[4 * k + 2 * hh + 1]));
                    }
                }
                if (m >= 44) {
                    if (q == 0) sts128(part + (m + 16) * 96 + 80, __float_as_uint(d2[12 + 2 * hh]), 0u, 0u, 0u);
#pragma unroll
                    for (int k = 0; k < 3; k++) {
                        const int e = 8 * k + 2 * q - 4;
                        if (e >= 0) sts64(part + (m + 16) * 96 + e * 4, __float_as_uint(d2[4 * k + 2 * hh]), __float_as_uint(d2[4 * k + 2 * hh + 1]));
                    }
                }
            }
            fence_async_smem();
            __syncwarp();
            if (lane == 0) mbar_arrive(sb + BAR_PART);
        }
        } else {
        __nv_bfloat16* out = P.out + (128 * i + 16 * warp) * 1280 + 80 * j + 640;
        mbar_wait(sb + BAR_A0, 0);
        store_tile(sb + OFF_Q + warp * 2560, out, lane, a);
        store_tile(sb + OFF_Q + warp * 2560, out + 64 * 1280, lane, b);
        TS(9);
        }
        }
        {
            mbar_wait(sb + BAR_WA, 0);
            float a[40];
            gemm_half<false>(sb, 20, a);
            store_tile(sb + OFF_Q + warp * 2560, P.out + (128 * i + 16 * warp) * 1280 + 80 * j, lane, a);
            TS(12);
        }
        if (cta == 0 && tid == 512) *(volatile uint32_t*)&g_epoch = tag;
    }
}

typedef CUresult (*EncodeFn)(CUtensorMap*, CUtensorMapDataType, cuuint32_t, void*, const cuuint64_t*, const cuuint64_t*,
                             const cuuint32_t*, const cuuint32_t*, CUtensorMapInterleave, CUtensorMapSwizzle,
                             CUtensorMapL2promotion, CUtensorMapFloatOOBfill);

void make_map(EncodeFn enc, CUtensorMap* m, const void* p, uint32_t box_cols, uint32_t box_rows, uint64_t rows = 2048) {
    cuuint64_t dims[2] = {640, rows}, strides[1] = {1280};
    cuuint32_t box[2] = {box_cols, box_rows}, es[2] = {1, 1};
    enc(m, CU_TENSOR_MAP_DATA_TYPE_BFLOAT16, 2, const_cast<void*>(p), dims, strides, box, es, CU_TENSOR_MAP_INTERLEAVE_NONE,
        box_cols == 64 ? CU_TENSOR_MAP_SWIZZLE_128B : box_cols == 16 ? CU_TENSOR_MAP_SWIZZLE_32B : CU_TENSOR_MAP_SWIZZLE_NONE, CU_TENSOR_MAP_L2_PROMOTION_L2_128B, CU_TENSOR_MAP_FLOAT_OOB_FILL_NONE);
}
void make_x16map(EncodeFn enc, CUtensorMap* m, const void* p) {
    cuuint64_t dims[3] = {64, 2048, 10}, strides[2] = {1280, 128};
    cuuint32_t box[3] = {64, 16, 10}, es[3] = {1, 1, 1};
    enc(m, CU_TENSOR_MAP_DATA_TYPE_BFLOAT16, 3, const_cast<void*>(p), dims, strides, box, es, CU_TENSOR_MAP_INTERLEAVE_NONE,
        CU_TENSOR_MAP_SWIZZLE_128B, CU_TENSOR_MAP_L2_PROMOTION_L2_128B, CU_TENSOR_MAP_FLOAT_OOB_FILL_NONE);
}
void make_wmap(EncodeFn enc, CUtensorMap* m, const void* p, uint64_t cols) {
    cuuint64_t dims[3] = {16, 640, cols / 16}, strides[2] = {cols * 2, 32};
    cuuint32_t box[3] = {16, 64, 5}, es[3] = {1, 1, 1};
    enc(m, CU_TENSOR_MAP_DATA_TYPE_BFLOAT16, 3, const_cast<void*>(p), dims, strides, box, es, CU_TENSOR_MAP_INTERLEAVE_NONE,
        CU_TENSOR_MAP_SWIZZLE_32B, CU_TENSOR_MAP_L2_PROMOTION_L2_128B, CU_TENSOR_MAP_FLOAT_OOB_FILL_NONE);
}

}

extern "C" void kernel_launch(void* const* d_in, const int* in_sizes, int n_in, void* d_out, int out_size) {
    static EncodeFn enc = nullptr;
    static void *oa = nullptr, *ob = nullptr;
    static int sms = 0;
    if (!enc) {
        void* fn = nullptr;
        cudaDriverEntryPointQueryResult qr;
        cudaGetDriverEntryPoint("cuTensorMapEncodeTiled", &fn, cudaEnableDefault, &qr);
        enc = (EncodeFn)fn;
        int dev = 0;
        cudaGetDevice(&dev);
        cudaDeviceGetAttribute(&sms, cudaDevAttrMultiProcessorCount, dev);
        cudaGetSymbolAddress(&oa, g_oa);
        cudaGetSymbolAddress(&ob, g_ob);
        cudaFuncSetAttribute(fused_kernel, cudaFuncAttributeMaxDynamicSharedMemorySize, SMEM_BYTES);
    }
    Params P;
    make_map(enc, &P.xa, d_in[0], 64, 64);
    make_x16map(enc, &P.xa16, d_in[0]);
    make_map(enc, &P.wq64, d_in[1], 64, 64, 640);
    make_map(enc, &P.wq16, d_in[1], 16, 64, 640);
    make_map(enc, &P.xb, d_in[5], 64, 128);
    make_wmap(enc, &P.wqkv, d_in[6], 1920);
    make_wmap(enc, &P.woa, d_in[4], 640);
    make_wmap(enc, &P.wob, d_in[7], 640);
    make_map(enc, &P.oa, oa, 64, 64);
    make_map(enc, &P.ob, ob, 64, 128);
    make_map(enc, &P.oa_st, oa, 80, 64);
    make_map(enc, &P.ob_st, ob, 80, 128);
    for (int k = 0; k < 8; k++) P.in[k] = (const uint8_t*)d_in[k];
    P.out = (__nv_bfloat16*)d_out;
    P.helpers = sms >= NCTA + 4;
    fused_kernel<<<P.helpers ? NCTA + 4 : NCTA, NTHR, SMEM_BYTES, cudaStreamPerThread>>>(P);
}
```

```cpp
#include <cuda_runtime.h>
#include <cuda_bf16.h>
#include <cuda.h>
#include <stdint.h>

namespace {

constexpr int NCTA = 128;
constexpr int NTHR = 768;

constexpr uint32_t OFF_STAGE = 0;
constexpr uint32_t STAGE_BYTES = 26624;
constexpr uint32_t OFF_PK = 79872;
constexpr uint32_t OFF_V = 100352;
constexpr uint32_t OFF_KVB = OFF_V;
constexpr uint32_t OFF_PST = OFF_V + 14336;
constexpr uint32_t OFF_WA = 0;
constexpr uint32_t OFF_XA = 102400;
constexpr uint32_t OFF_RING = 135168;
constexpr uint32_t RING_BYTES = 24576;
constexpr uint32_t OFF_WRAW = OFF_RING;
constexpr uint32_t OFF_KVP = OFF_RING + 51200;
constexpr uint32_t OFF_Q = 208896;
constexpr uint32_t OFF_X16 = OFF_Q;
constexpr uint32_t OFF_MISC = 229376;
constexpr uint32_t OFF_BAR = OFF_MISC;
constexpr uint32_t BAR_FULL_G = OFF_BAR, BAR_EMPTY_G = OFF_BAR + 24, BAR_FULL_KV = OFF_BAR + 48, BAR_EMPTY_KV = OFF_BAR + 72;
constexpr uint32_t BAR_OA = OFF_BAR + 96, BAR_WA = OFF_BAR + 112, BAR_FULL_X = OFF_BAR + 120, BAR_EMPTY_X = OFF_BAR + 152, BAR_A0 = OFF_BAR + 184;
constexpr uint32_t OFF_QUEUE = OFF_BAR + 192;
constexpr uint32_t BAR_PART = OFF_BAR + 264, BAR_KVB = OFF_BAR + 272, BAR_OB = OFF_BAR + 280, BAR_KVIN = OFF_BAR + 288;
constexpr uint32_t OFF_PUB = OFF_BAR + 296;
constexpr uint32_t OFF_STAT = OFF_BAR + 304;
constexpr uint32_t BAR_Q = OFF_BAR + 336, BAR_C0 = OFF_BAR + 352, BAR_WQ = OFF_BAR + 360;
constexpr uint32_t OFF_KST = OFF_MISC + 384;
constexpr uint32_t OFF_TS = OFF_KST + 256;
constexpr uint32_t SMEM_BYTES = OFF_TS + 256;

#define MUFU_MASK 0x52

constexpr float LOG2E = 1.4426950408889634f;
constexpr float QSCALE = 0.22360679774997896f * LOG2E;

struct Params {
    CUtensorMap xa, xa16, wq64, wq16, xb, wqkv, woa, wob, oa, ob, oa_st, ob_st;
    const uint8_t* in[8];
    __nv_bfloat16* out;
    int helpers;
};

}

__device__ __align__(1024) uint8_t g_kv[256 * 768];
__device__ __align__(1024) __nv_bfloat16 g_oa[2048 * 640];
__device__ __align__(1024) __nv_bfloat16 g_ob[2048 * 640];
__device__ __align__(1024) uint8_t g_ox[16 * 40 * 2048];
__device__ __align__(128) float g_part[8 * 1920];
__device__ __align__(1024) unsigned long long g_kt[16 * 384];
__device__ __align__(128) uint32_t g_stat[128];
__device__ __align__(128) uint16_t g_flag_kv[128];
__device__ __align__(128) uint16_t g_flag_b1[128];
__device__ __align__(128) uint16_t g_flag_b2[128];
__device__ __align__(128) uint16_t g_flag_a[128];
__device__ __align__(128) uint16_t g_flag_w[32];
__device__ __align__(1024) uint8_t g_wt[320 * 10240];
__device__ uint32_t g_epoch;
#define TS(k)
#define TC(k)

namespace {

__device__ __forceinline__ void wg_rs_n24_tb1_d(float (&d)[12], uint32_t a0, uint32_t a1, uint32_t a2, uint32_t a3, uint64_t db) {
    asm volatile("{\n.reg .pred p;\nsetp.ne.b32 p, 1, 0;\n"
        "wgmma.mma_async.sync.aligned.m64n24k16.f32.bf16.bf16 {%0, %1, %2, %3, %4, %5, %6, %7, %8, %9, %10, %11}, {%12, %13, %14, %15}, %16, p, 1, 1, 1;\n}\n"
        : "+f"(d[0]), "+f"(d[1]), "+f"(d[2]), "+f"(d[3]), "+f"(d[4]), "+f"(d[5]), "+f"(d[6]), "+f"(d[7]), "+f"(d[8]), "+f"(d[9]), "+f"(d[10]), "+f"(d[11])
        : "r"(a0), "r"(a1), "r"(a2), "r"(a3), "l"(db));
}
__device__ __forceinline__ void wg_rs_n64_tb0_d(float (&d)[32], uint32_t a0, uint32_t a1, uint32_t a2, uint32_t a3, uint64_t db) {
    asm volatile("{\n.reg .pred p;\nsetp.ne.b32 p, 1, 0;\n"
        "wgmma.mma_async.sync.aligned.m64n64k16.f32.bf16.bf16 {%0, %1, %2, %3, %4, %5, %6, %7, %8, %9, %10, %11, %12, %13, %14, %15, %16, %17, %18, %19, %20, %21, %22, %23, %24, %25, %26, %27, %28, %29, %30, %31}, {%32, %33, %34, %35}, %36, p, 1, 1, 0;\n}\n"
        : "+f"(d[0]), "+f"(d[1]), "+f"(d[2]), "+f"(d[3]), "+f"(d[4]), "+f"(d[5]), "+f"(d[6]), "+f"(d[7]), "+f"(d[8]), "+f"(d[9]), "+f"(d[10]), "+f"(d[11]), "+f"(d[12]), "+f"(d[13]), "+f"(d[14]), "+f"(d[15]), "+f"(d[16]), "+f"(d[17]), "+f"(d[18]), "+f"(d[19]), "+f"(d[20]), "+f"(d[21]), "+f"(d[22]), "+f"(d[23]), "+f"(d[24]), "+f"(d[25]), "+f"(d[26]), "+f"(d[27]), "+f"(d[28]), "+f"(d[29]), "+f"(d[30]), "+f"(d[31])
        : "r"(a0), "r"(a1), "r"(a2), "r"(a3), "l"(db));
}
__device__ __forceinline__ void wg_rs_n64_tb0_initd(float (&d)[32], uint32_t a0, uint32_t a1, uint32_t a2, uint32_t a3, uint64_t db) {
    asm volatile("{\n.reg .pred p;\nsetp.ne.b32 p, 0, 0;\n"
        "wgmma.mma_async.sync.aligned.m64n64k16.f32.bf16.bf16 {%0, %1, %2, %3, %4, %5, %6, %7, %8, %9, %10, %11, %12, %13, %14, %15, %16, %17, %18, %19, %20, %21, %22, %23, %24, %25, %26, %27, %28, %29, %30, %31}, {%32, %33, %34, %35}, %36, p, 1, 1, 0;\n}\n"
        : "=f"(d[0]), "=f"(d[1]), "=f"(d[2]), "=f"(d[3]), "=f"(d[4]), "=f"(d[5]), "=f"(d[6]), "=f"(d[7]), "=f"(d[8]), "=f"(d[9]), "=f"(d[10]), "=f"(d[11]), "=f"(d[12]), "=f"(d[13]), "=f"(d[14]), "=f"(d[15]), "=f"(d[16]), "=f"(d[17]), "=f"(d[18]), "=f"(d[19]), "=f"(d[20]), "=f"(d[21]), "=f"(d[22]), "=f"(d[23]), "=f"(d[24]), "=f"(d[25]), "=f"(d[26]), "=f"(d[27]), "=f"(d[28]), "=f"(d[29]), "=f"(d[30]), "=f"(d[31])
        : "r"(a0), "r"(a1), "r"(a2), "r"(a3), "l"(db));
}
__device__ __forceinline__ void wg_ss_n16_ta0_tb1_d(float (&d)[8], uint64_t da, uint64_t db) {
    asm volatile("{\n.reg .pred p;\nsetp.ne.b32 p, 1, 0;\n"
        "wgmma.mma_async.sync.aligned.m64n16k16.f32.bf16.bf16 {%0, %1, %2, %3, %4, %5, %6, %7}, %8, %9, p, 1, 1, 0, 1;\n}\n"
        : "+f"(d[0]), "+f"(d[1]), "+f"(d[2]), "+f"(d[3]), "+f"(d[4]), "+f"(d[5]), "+f"(d[6]), "+f"(d[7])
        : "l"(da), "l"(db));
}
__device__ __forceinline__ void wg_ss_n32_ta1_tb1_d(float (&d)[16], uint64_t da, uint64_t db) {
    asm volatile("{\n.reg .pred p;\nsetp.ne.b32 p, 1, 0;\n"
        "wgmma.mma_async.sync.aligned.m64n32k16.f32.bf16.bf16 {%0, %1, %2, %3, %4, %5, %6, %7, %8, %9, %10, %11, %12, %13, %14, %15}, %16, %17, p, 1, 1, 1, 1;\n}\n"
        : "+f"(d[0]), "+f"(d[1]), "+f"(d[2]), "+f"(d[3]), "+f"(d[4]), "+f"(d[5]), "+f"(d[6]), "+f"(d[7]), "+f"(d[8]), "+f"(d[9]), "+f"(d[10]), "+f"(d[11]), "+f"(d[12]), "+f"(d[13]), "+f"(d[14]), "+f"(d[15])
        : "l"(da), "l"(db));
}
__device__ __forceinline__ void wg_ss_n64_ta0_tb1_d(float (&d)[32], uint64_t da, uint64_t db) {
    asm volatile("{\n.reg .pred p;\nsetp.ne.b32 p, 1, 0;\n"
        "wgmma.mma_async.sync.aligned.m64n64k16.f32.bf16.bf16 {%0, %1, %2, %3, %4, %5, %6, %7, %8, %9, %10, %11, %12, %13, %14, %15, %16, %17, %18, %19, %20, %21, %22, %23, %24, %25, %26, %27, %28, %29, %30, %31}, %32, %33, p, 1, 1, 0, 1;\n}\n"
        : "+f"(d[0]), "+f"(d[1]), "+f"(d[2]), "+f"(d[3]), "+f"(d[4]), "+f"(d[5]), "+f"(d[6]), "+f"(d[7]), "+f"(d[8]), "+f"(d[9]), "+f"(d[10]), "+f"(d[11]), "+f"(d[12]), "+f"(d[13]), "+f"(d[14]), "+f"(d[15]), "+f"(d[16]), "+f"(d[17]), "+f"(d[18]), "+f"(d[19]), "+f"(d[20]), "+f"(d[21]), "+f"(d[22]), "+f"(d[23]), "+f"(d[24]), "+f"(d[25]), "+f"(d[26]), "+f"(d[27]), "+f"(d[28]), "+f"(d[29]), "+f"(d[30]), "+f"(d[31])
        : "l"(da), "l"(db));
}
__device__ __forceinline__ void wg_ss_n72_ta1_tb1_d(float (&d)[36], uint64_t da, uint64_t db) {
    asm volatile("{\n.reg .pred p;\nsetp.ne.b32 p, 1, 0;\n"
        "wgmma.mma_async.sync.aligned.m64n72k16.f32.bf16.bf16 {%0, %1, %2, %3, %4, %5, %6, %7, %8, %9, %10, %11, %12, %13, %14, %15, %16, %17, %18, %19, %20, %21, %22, %23, %24, %25, %26, %27, %28, %29, %30, %31, %32, %33, %34, %35}, %36, %37, p, 1, 1, 1, 1;\n}\n"
        : "+f"(d[0]), "+f"(d[1]), "+f"(d[2]), "+f"(d[3]), "+f"(d[4]), "+f"(d[5]), "+f"(d[6]), "+f"(d[7]), "+f"(d[8]), "+f"(d[9]), "+f"(d[10]), "+f"(d[11]), "+f"(d[12]), "+f"(d[13]), "+f"(d[14]), "+f"(d[15]), "+f"(d[16]), "+f"(d[17]), "+f"(d[18]), "+f"(d[19]), "+f"(d[20]), "+f"(d[21]), "+f"(d[22]), "+f"(d[23]), "+f"(d[24]), "+f"(d[25]), "+f"(d[26]), "+f"(d[27]), "+f"(d[28]), "+f"(d[29]), "+f"(d[30]), "+f"(d[31]), "+f"(d[32]), "+f"(d[33]), "+f"(d[34]), "+f"(d[35])
        : "l"(da), "l"(db));
}
__device__ __forceinline__ void wg_ss_n80_ta0_tb1_d(float (&d)[40], uint64_t da, uint64_t db) {
    asm volatile("{\n.reg .pred p;\nsetp.ne.b32 p, 1, 0;\n"
        "wgmma.mma_async.sync.aligned.m64n80k16.f32.bf16.bf16 {%0, %1, %2, %3, %4, %5, %6, %7, %8, %9, %10, %11, %12, %13, %14, %15, %16, %17, %18, %19, %20, %21, %22, %23, %24, %25, %26, %27, %28, %29, %30, %31, %32, %33, %34, %35, %36, %37, %38, %39}, %40, %41, p, 1, 1, 0, 1;\n}\n"
        : "+f"(d[0]), "+f"(d[1]), "+f"(d[2]), "+f"(d[3]), "+f"(d[4]), "+f"(d[5]), "+f"(d[6]), "+f"(d[7]), "+f"(d[8]), "+f"(d[9]), "+f"(d[10]), "+f"(d[11]), "+f"(d[12]), "+f"(d[13]), "+f"(d[14]), "+f"(d[15]), "+f"(d[16]), "+f"(d[17]), "+f"(d[18]), "+f"(d[19]), "+f"(d[20]), "+f"(d[21]), "+f"(d[22]), "+f"(d[23]), "+f"(d[24]), "+f"(d[25]), "+f"(d[26]), "+f"(d[27]), "+f"(d[28]), "+f"(d[29]), "+f"(d[30]), "+f"(d[31]), "+f"(d[32]), "+f"(d[33]), "+f"(d[34]), "+f"(d[35]), "+f"(d[36]), "+f"(d[37]), "+f"(d[38]), "+f"(d[39])
        : "l"(da), "l"(db));
}
__device__ __forceinline__ void wg_ss_n80_ta0_tb1_initd(float (&d)[40], uint64_t da, uint64_t db) {
    asm volatile("{\n.reg .pred p;\nsetp.ne.b32 p, 0, 0;\n"
        "wgmma.mma_async.sync.aligned.m64n80k16.f32.bf16.bf16 {%0, %1, %2, %3, %4, %5, %6, %7, %8, %9, %10, %11, %12, %13, %14, %15, %16, %17, %18, %19, %20, %21, %22, %23, %24, %25, %26, %27, %28, %29, %30, %31, %32, %33, %34, %35, %36, %37, %38, %39}, %40, %41, p, 1, 1, 0, 1;\n}\n"
        : "=f"(d[0]), "=f"(d[1]), "=f"(d[2]), "=f"(d[3]), "=f"(d[4]), "=f"(d[5]), "=f"(d[6]), "=f"(d[7]), "=f"(d[8]), "=f"(d[9]), "=f"(d[10]), "=f"(d[11]), "=f"(d[12]), "=f"(d[13]), "=f"(d[14]), "=f"(d[15]), "=f"(d[16]), "=f"(d[17]), "=f"(d[18]), "=f"(d[19]), "=f"(d[20]), "=f"(d[21]), "=f"(d[22]), "=f"(d[23]), "=f"(d[24]), "=f"(d[25]), "=f"(d[26]), "=f"(d[27]), "=f"(d[28]), "=f"(d[29]), "=f"(d[30]), "=f"(d[31]), "=f"(d[32]), "=f"(d[33]), "=f"(d[34]), "=f"(d[35]), "=f"(d[36]), "=f"(d[37]), "=f"(d[38]), "=f"(d[39])
        : "l"(da), "l"(db));
}
__device__ __forceinline__ void wg_ss_n88_ta0_tb1_d(float (&d)[44], uint64_t da, uint64_t db) {
    asm volatile("{\n.reg .pred p;\nsetp.ne.b32 p, 1, 0;\n"
        "wgmma.mma_async.sync.aligned.m64n88k16.f32.bf16.bf16 {%0, %1, %2, %3, %4, %5, %6, %7, %8, %9, %10, %11, %12, %13, %14, %15, %16, %17, %18, %19, %20, %21, %22, %23, %24, %25, %26, %27, %28, %29, %30, %31, %32, %33, %34, %35, %36, %37, %38, %39, %40, %41, %42, %43}, %44, %45, p, 1, 1, 0, 1;\n}\n"
        : "+f"(d[0]), "+f"(d[1]), "+f"(d[2]), "+f"(d[3]), "+f"(d[4]), "+f"(d[5]), "+f"(d[6]), "+f"(d[7]), "+f"(d[8]), "+f"(d[9]), "+f"(d[10]), "+f"(d[11]), "+f"(d[12]), "+f"(d[13]), "+f"(d[14]), "+f"(d[15]), "+f"(d[16]), "+f"(d[17]), "+f"(d[18]), "+f"(d[19]), "+f"(d[20]), "+f"(d[21]), "+f"(d[22]), "+f"(d[23]), "+f"(d[24]), "+f"(d[25]), "+f"(d[26]), "+f"(d[27]), "+f"(d[28]), "+f"(d[29]), "+f"(d[30]), "+f"(d[31]), "+f"(d[32]), "+f"(d[33]), "+f"(d[34]), "+f"(d[35]), "+f"(d[36]), "+f"(d[37]), "+f"(d[38]), "+f"(d[39]), "+f"(d[40]), "+f"(d[41]), "+f"(d[42]), "+f"(d[43])
        : "l"(da), "l"(db));
}

#define WG_FENCE() asm volatile("wgmma.fence.sync.aligned;" ::: "memory")
#define WG_COMMIT() asm volatile("wgmma.commit_group.sync.aligned;" ::: "memory")
#define WG_WAIT(n) asm volatile("wgmma.wait_group.sync.aligned %0;" :: "n"(n) : "memory")
template <int NR> __device__ __forceinline__ void fence_regs(float (&d)[NR]) {
#pragma unroll
    for (int i = 0; i < NR; i++) asm volatile("" : "+f"(d[i]) :: "memory");
}
template <int NR> __device__ __forceinline__ void zero_regs(float (&d)[NR]) {
#pragma unroll
    for (int i = 0; i < NR; i++) asm volatile("mov.b32 %0, 0;" : "=f"(d[i]) :: "memory");
}
constexpr uint32_t SW128 = 1u << 30, SW32 = 3u << 30;
__device__ __forceinline__ constexpr uint32_t dlo(uint32_t lbo) { return (lbo >> 4) << 16; }

__device__ __forceinline__ void bar_sync(int id, int n) { asm volatile("bar.sync %0, %1;" :: "r"(id), "r"(n) : "memory"); }
__device__ __forceinline__ void bar_arrive(int id, int n) { asm volatile("bar.arrive %0, %1;" :: "r"(id), "r"(n) : "memory"); }
__device__ __forceinline__ void mbar_init(uint32_t bar, uint32_t cnt) { asm volatile("mbarrier.init.shared::cta.b64 [%0], %1;" :: "r"(bar), "r"(cnt) : "memory"); }
__device__ __forceinline__ void mbar_arrive(uint32_t bar) { asm volatile("mbarrier.arrive.shared::cta.b64 _, [%0];" :: "r"(bar) : "memory"); }
__device__ __forceinline__ void mbar_expect(uint32_t bar, uint32_t bytes) { asm volatile("mbarrier.arrive.expect_tx.shared::cta.b64 _, [%0], %1;" :: "r"(bar), "r"(bytes) : "memory"); }
__device__ __forceinline__ void mbar_wait(uint32_t bar, uint32_t parity) {
    asm volatile("{\n.reg .pred p;\n.reg .u32 n;\nmov.u32 n, 0;\n"
                 "MW_LOOP:\nmbarrier.try_wait.parity.shared::cta.b64 p, [%0], %1;\n@p bra.uni MW_DONE;\n"
                 "add.u32 n, n, 1;\nsetp.lt.u32 p, n, 32768;\n@p bra.uni MW_LOOP;\nMW_DONE:\n}"
                 :: "r"(bar), "r"(parity) : "memory");
}
__device__ __forceinline__ bool mbar_test(uint32_t bar, uint32_t parity) {
    uint32_t r;
    asm volatile("{\n.reg .pred p;\nmbarrier.test_wait.parity.shared::cta.b64 p, [%1], %2;\nselp.u32 %0, 1, 0, p;\n}" : "=r"(r) : "r"(bar), "r"(parity) : "memory");
    return r;
}
__device__ __forceinline__ void count_wait(uint32_t addr, uint32_t seen, uint32_t need) {
    asm volatile("{\n.reg .pred p;\n.reg .u32 n, v;\nmov.u32 n, 0;\nmov.u32 v, %1;\n"
                 "CW_LOOP:\nsetp.ge.u32 p, v, %2;\n@p bra.uni CW_DONE;\nld.volatile.shared.u32 v, [%0];\n"
                 "add.u32 n, n, 1;\nsetp.lt.u32 p, n, 0x400000;\n@p bra.uni CW_LOOP;\nCW_DONE:\n}"
                 :: "r"(addr), "r"(seen), "r"(need) : "memory");
}
__device__ __forceinline__ uint32_t queue_wait(uint32_t addr) {
    uint32_t v;
    asm volatile("{\n.reg .pred p;\n.reg .u32 n;\nmov.u32 n, 0;\n"
                 "QW_LOOP:\nld.acquire.cta.shared::cta.u32 %0, [%1];\nsetp.ne.u32 p, %0, 0;\n@p bra.uni QW_DONE;\n"
                 "add.u32 n, n, 1;\nsetp.lt.u32 p, n, 0x400000;\n@p bra.uni QW_LOOP;\nmov.u32 %0, 1;\nQW_DONE:\n}"
                 : "=r"(v) : "r"(addr) : "memory");
    return v;
}
__device__ __forceinline__ void tma2d(uint32_t dst, const CUtensorMap* m, int x, int y, uint32_t bar) {
    asm volatile("cp.async.bulk.tensor.2d.shared::cluster.global.mbarrier::complete_tx::bytes [%0], [%1, {%2, %3}], [%4];"
                 :: "r"(dst), "l"(m), "r"(x), "r"(y), "r"(bar) : "memory");
}
__device__ __forceinline__ void bulk1d(uint32_t dst, const void* src, uint32_t bytes, uint32_t bar) {
    asm volatile("cp.async.bulk.shared::cluster.global.mbarrier::complete_tx::bytes [%0], [%1], %2, [%3];"
                 :: "r"(dst), "l"(src), "r"(bytes), "r"(bar) : "memory");
}
__device__ __forceinline__ void tma3d(uint32_t dst, const CUtensorMap* m, int y, int z, uint32_t bar) {
    asm volatile("cp.async.bulk.tensor.3d.shared::cluster.global.mbarrier::complete_tx::bytes [%0], [%1, {0, %2, %3}], [%4];"
                 :: "r"(dst), "l"(m), "r"(y), "r"(z), "r"(bar) : "memory");
}
__device__ __forceinline__ void tma2d_store(const CUtensorMap* m, int x, int y, uint32_t src) {
    asm volatile("cp.async.bulk.tensor.2d.global.shared::cta.bulk_group [%0, {%1, %2}], [%3];" :: "l"(m), "r"(x), "r"(y), "r"(src) : "memory");
}
__device__ __forceinline__ void bulk_store(void* dst, uint32_t src, uint32_t bytes) {
    asm volatile("cp.async.bulk.global.shared::cta.bulk_group [%0], [%1], %2;" :: "l"(dst), "r"(src), "r"(bytes) : "memory");
}
__device__ __forceinline__ void bulk_add_f32(void* dst, uint32_t src, uint32_t bytes) {
    asm volatile("cp.reduce.async.bulk.global.shared::cta.bulk_group.add.f32 [%0], [%1], %2;" :: "l"(dst), "r"(src), "r"(bytes) : "memory");
}
__device__ __forceinline__ void bulk_commit() { asm volatile("cp.async.bulk.commit_group;" ::: "memory"); }
__device__ __forceinline__ void bulk_wait() {
    asm volatile("cp.async.bulk.wait_group 0;\nfence.proxy.async.global;" ::: "memory");
}
__device__ __forceinline__ void prefetch_l2(const void* p, uint32_t bytes) { asm volatile("cp.async.bulk.prefetch.L2.global [%0], %1;" :: "l"(p), "r"(bytes) : "memory"); }
__device__ __forceinline__ void prefetch_map(const CUtensorMap* m) { asm volatile("prefetch.tensormap [%0];" :: "l"(m) : "memory"); }
__device__ __forceinline__ uint32_t opaque_tid() { uint32_t t; asm volatile("mov.u32 %0, %tid.x;" : "=r"(t) :: "memory"); return t; }
__device__ __forceinline__ uint32_t opaque_cta() { uint32_t t; asm volatile("mov.u32 %0, %ctaid.x;" : "=r"(t) :: "memory"); return t; }
__device__ __forceinline__ bool elect_one() {
    uint32_t p;
    asm volatile("{\n.reg .pred p;\nelect.sync _|p, 0xffffffff;\nselp.u32 %0, 1, 0, p;\n}" : "=r"(p));
    return p;
}
__device__ __forceinline__ void fence_async() { asm volatile("fence.proxy.async.global;" ::: "memory"); }
__device__ __forceinline__ void fence_async_smem() { asm volatile("fence.proxy.async.shared::cta;" ::: "memory"); }
__device__ __forceinline__ void st_flag(uint16_t* p, uint32_t v) { asm volatile("st.release.gpu.global.u16 [%0], %1;" :: "l"(p), "h"((uint16_t)v) : "memory"); }
__device__ __forceinline__ void st_relaxed(void* p, uint32_t v) { asm volatile("st.relaxed.gpu.global.u32 [%0], %1;" :: "l"(p), "r"(v) : "memory"); }
__device__ __forceinline__ void st_relaxed64(void* p, unsigned long long v) { asm volatile("st.relaxed.gpu.global.u64 [%0], %1;" :: "l"(p), "l"(v) : "memory"); }
__device__ __forceinline__ uint4 ld_relaxed2x64(const void* p) {
    uint4 v;
    asm volatile("{\n.reg .b64 a, b;\nld.relaxed.gpu.global.v2.u64 {a, b}, [%4];\nmov.b64 {%0, %1}, a;\nmov.b64 {%2, %3}, b;\n}" : "=r"(v.x), "=r"(v.y), "=r"(v.z), "=r"(v.w) : "l"(p) : "memory");
    return v;
}
__device__ __forceinline__ uint4 ld_relaxed128(const void* p) { uint4 v; asm volatile("ld.relaxed.gpu.global.v4.u32 {%0, %1, %2, %3}, [%4];" : "=r"(v.x), "=r"(v.y), "=r"(v.z), "=r"(v.w) : "l"(p) : "memory"); return v; }
__device__ __forceinline__ uint4 ld_acquire128(const void* p) { uint4 v; asm volatile("ld.acquire.gpu.global.v4.u32 {%0, %1, %2, %3}, [%4];" : "=r"(v.x), "=r"(v.y), "=r"(v.z), "=r"(v.w) : "l"(p) : "memory"); return v; }
__device__ __forceinline__ void poll1(const uint16_t* p, uint32_t tag) {
#pragma unroll 1
    for (uint32_t spin = 0; spin < (1u << 17); spin++) {
        uint16_t v;
        asm volatile("ld.acquire.gpu.global.u16 %0, [%1];" : "=h"(v) : "l"(p) : "memory");
        if (v == (uint16_t)tag) break;
    }
    fence_async();
}
__device__ __forceinline__ void poll8(const uint16_t* p, uint32_t tag) {
    const uint32_t t2 = (tag & 0xFFFFu) * 0x10001u;
#pragma unroll 1
    for (uint32_t spin = 0; spin < (1u << 17); spin++) {
        const uint4 a = ld_acquire128(p);
        if (a.x == t2 && a.y == t2 && a.z == t2 && a.w == t2) break;
    }
    fence_async();
}
__device__ __forceinline__ uint32_t lds32(uint32_t a) { uint32_t v; asm volatile("ld.shared.u32 %0, [%1];" : "=r"(v) : "r"(a) : "memory"); return v; }
__device__ __forceinline__ void sts32(uint32_t a, uint32_t v) { asm volatile("st.shared.u32 [%0], %1;" :: "r"(a), "r"(v) : "memory"); }
__device__ __forceinline__ void sts16(uint32_t a, uint16_t v) { asm volatile("st.shared.u16 [%0], %1;" :: "r"(a), "h"(v) : "memory"); }
__device__ __forceinline__ void sts64(uint32_t a, uint32_t x, uint32_t y) { asm volatile("st.shared.v2.u32 [%0], {%1, %2};" :: "r"(a), "r"(x), "r"(y) : "memory"); }
__device__ __forceinline__ void sts128(uint32_t a, uint32_t x, uint32_t y, uint32_t z, uint32_t w) { asm volatile("st.shared.v4.u32 [%0], {%1, %2, %3, %4};" :: "r"(a), "r"(x), "r"(y), "r"(z), "r"(w) : "memory"); }
__device__ __forceinline__ uint2 lds64(uint32_t a) { uint2 v; asm volatile("ld.shared.v2.u32 {%0, %1}, [%2];" : "=r"(v.x), "=r"(v.y) : "r"(a) : "memory"); return v; }
__device__ __forceinline__ uint4 lds128(uint32_t a) { uint4 v; asm volatile("ld.shared.v4.u32 {%0, %1, %2, %3}, [%4];" : "=r"(v.x), "=r"(v.y), "=r"(v.z), "=r"(v.w) : "r"(a) : "memory"); return v; }
__device__ __forceinline__ float ex2f(float x) { float y; asm("ex2.approx.ftz.f32 %0, %1;" : "=f"(y) : "f"(x)); return y; }
__device__ __forceinline__ float rcpf(float x) { float y; asm("rcp.approx.ftz.f32 %0, %1;" : "=f"(y) : "f"(x)); return y; }
__device__ __forceinline__ void stsm4(uint32_t a, uint32_t x, uint32_t y, uint32_t z, uint32_t w) {
    asm volatile("stmatrix.sync.aligned.m8n8.x4.shared.b16 [%0], {%1, %2, %3, %4};" :: "r"(a), "r"(x), "r"(y), "r"(z), "r"(w) : "memory");
}
__device__ __forceinline__ uint32_t pack_bf16(float lo, float hi) { uint32_t r; asm("cvt.rn.bf16x2.f32 %0, %1, %2;" : "=r"(r) : "f"(hi), "f"(lo)); return r; }
__device__ __forceinline__ float bf_lo(uint32_t v) { return __uint_as_float(v << 16); }
__device__ __forceinline__ float bf_hi(uint32_t v) { return __uint_as_float(v & 0xFFFF0000u); }
__device__ __forceinline__ uint32_t phi2(float t0, float t1) {
    uint32_t r;
    asm("{\n.reg .b32 one, eps, p, e;\nmov.b32 one, 0x3F803F80;\nmov.b32 eps, 0x35863586;\n"
        "add.rn.bf16x2 p, %1, one;\nmin.bf16x2 e, %2, one;\nmax.NaN.bf16x2 p, p, e;\nadd.rn.bf16x2 %0, p, eps;\n}"
        : "=r"(r) : "r"(pack_bf16(t0, t1)), "r"(pack_bf16(ex2f(t0 * LOG2E), ex2f(t1 * LOG2E))));
    return r;
}
template <int MODE> __device__ __forceinline__ void stage_tile(uint32_t x, uint32_t step, const float (&a)[40]) {
#pragma unroll
    for (int k = 0; k < 5; k++) {
        uint32_t r[4];
#pragma unroll
        for (int e = 0; e < 4; e++) {
            const float t0 = a[8 * k + 2 * e], t1 = a[8 * k + 2 * e + 1];
            r[e] = MODE == 0 ? pack_bf16(t0, t1) : MODE == 1 ? pack_bf16(t0 * QSCALE, t1 * QSCALE) : phi2(t0, t1);
        }
        stsm4(x + 2 * k * step, r[0], r[1], r[2], r[3]);
    }
}

__device__ __forceinline__ uint32_t exp2_pair(float t0, float t1, uint32_t ca) {
    uint32_t y, u, g;
    asm("prmt.b32 %0, %1, %2, 0x6521;" : "=r"(y) : "r"(__float_as_uint(t0)), "r"(__float_as_uint(t1)));
    u = y & 0x007F007Fu;
    asm("{.reg .b32 c; mov.b32 c, 0xF963F963; fma.rn.f16x2 %0, %1, c, %2;}" : "=r"(g) : "r"(u), "r"(ca));
    asm("mul.rn.f16x2 %0, %1, %2;" : "=r"(g) : "r"(g), "r"(u));
    return y - g;
}

__device__ __forceinline__ uint64_t desc(uint32_t addr, uint32_t lbo, uint32_t hi) { return ((uint64_t)hi << 32) | ((addr >> 4) + dlo(lbo)); }
template <int J> __device__ __forceinline__ void exp_steps(const float (&s)[32], uint32_t (&p)[16], float (&o)[12], uint64_t& dv, uint32_t ca) {
    if constexpr (J < 4) {
#pragma unroll
        for (int g = 2 * J; g < 2 * J + 2; g++) {
            if ((MUFU_MASK >> g) & 1) {
                p[2 * g] = pack_bf16(ex2f(s[4 * g]), ex2f(s[4 * g + 1]));
                p[2 * g + 1] = pack_bf16(ex2f(s[4 * g + 2]), ex2f(s[4 * g + 3]));
            } else {
                p[2 * g] = exp2_pair(s[4 * g], s[4 * g + 1], ca);
                p[2 * g + 1] = exp2_pair(s[4 * g + 2], s[4 * g + 3], ca);
            }
        }
        WG_FENCE();
        wg_rs_n24_tb1_d(o, p[4 * J], p[4 * J + 1], p[4 * J + 2], p[4 * J + 3], dv);
        dv += 96;
        exp_steps<J + 1>(s, p, o, dv, ca);
    }
}

struct Ring { uint32_t slot, phase; };
__device__ __forceinline__ void next_stage(Ring& r) { if (++r.slot == 3) { r.slot = 0; r.phase ^= 1; } }

template <bool FAST>
__device__ __forceinline__ void attend(uint32_t sb, uint32_t& slot, int pass, const uint32_t (&q)[6], float (&o)[12], uint32_t ca, uint32_t z0, uint32_t z1) {
    float m0 = -INFINITY, m1 = -INFINITY;
    constexpr int UNR = FAST ? 4 : 1;
#pragma unroll 1
    for (int c = 0; c < 8; c++) {
        const uint32_t base = sb + OFF_RING + slot * RING_BYTES;
        uint64_t dk = desc(base, 128, 768 >> 4), dv = desc(base + 384, 768, 128 >> 4);
        uint32_t seen;
#pragma unroll UNR
        for (int b = 0; b < 4; b++) {
            float s[32];
            uint32_t p[16];
            WG_FENCE();
            wg_rs_n64_tb0_initd(s, q[0], q[1], q[2], q[3], dk);
            dk += 16;
            wg_rs_n64_tb0_d(s, q[4], q[5], z0, z1, dk);
            dk += 368;
            WG_COMMIT();
            if (UNR < 4 || b == 3) seen = lds32(sb + OFF_PUB);
            WG_WAIT(0);
            fence_regs(s);
            if constexpr (FAST) {
                exp_steps<0>(s, p, o, dv, ca);
            } else {
                fence_regs(o);
                float x0 = m0, x1 = m1;
#pragma unroll
                for (int g = 0; g < 8; g++) {
                    if (!((MUFU_MASK >> g) & 1)) {
#pragma unroll
                        for (int e = 0; e < 4; e++) s[4 * g + e] *= 2.f;
                    }
                    x0 = fmaxf(x0, fmaxf(s[4 * g], s[4 * g + 1]));
                    x1 = fmaxf(x1, fmaxf(s[4 * g + 2], s[4 * g + 3]));
                }
                x0 = fmaxf(x0, __shfl_xor_sync(~0u, x0, 1)); x0 = fmaxf(x0, __shfl_xor_sync(~0u, x0, 2));
                x1 = fmaxf(x1, __shfl_xor_sync(~0u, x1, 1)); x1 = fmaxf(x1, __shfl_xor_sync(~0u, x1, 2));
                const float a0 = ex2f(m0 - x0), a1 = ex2f(m1 - x1);
                m0 = x0; m1 = x1;
#pragma unroll
                for (int b = 0; b < 3; b++) { o[4 * b] *= a0; o[4 * b + 1] *= a0; o[4 * b + 2] *= a1; o[4 * b + 3] *= a1; }
#pragma unroll
                for (int g = 0; g < 8; g++) {
                    p[2 * g] = pack_bf16(ex2f(s[4 * g] - x0), ex2f(s[4 * g + 1] - x0));
                    p[2 * g + 1] = pack_bf16(ex2f(s[4 * g + 2] - x1), ex2f(s[4 * g + 3] - x1));
                }
            }
            if constexpr (!FAST) {
                WG_FENCE();
#pragma unroll
                for (int k = 0; k < 4; k++) { wg_rs_n24_tb1_d(o, p[4 * k], p[4 * k + 1], p[4 * k + 2], p[4 * k + 3], dv); dv += 96; }
            }
            WG_COMMIT();
            WG_WAIT(0);
            fence_regs(o);
        }
        if ((threadIdx.x & 31) == 0) mbar_arrive(sb + BAR_EMPTY_KV + slot * 8);
        slot = slot == 2 ? 0 : slot + 1;
        count_wait(sb + OFF_PUB, seen, min(pass * 8 + c + 2, 16));
    }
}

__device__ __forceinline__ void gemm_pass(uint32_t sb, int pass, float (&a)[40], float (&b)[40]) {
    zero_regs(a); zero_regs(b);
    const uint32_t n0 = (__shfl_sync(~0u, pass, 0) - 1) * 10;
    uint32_t slot = n0 % 3, phase = (n0 / 3) & 1;
    const bool lead = (threadIdx.x & 31) == 0;
#pragma unroll 1
    for (int c = 0; c < 10; c++) {
        mbar_wait(sb + BAR_FULL_G + slot * 8, phase);
        const uint32_t st = sb + OFF_STAGE + slot * STAGE_BYTES;
        const uint64_t dx = desc(st, 16, SW128 | 64), dw = desc(st + 16384, 2048, SW32 | 16);
        WG_FENCE();
#pragma unroll
        for (int k = 0; k < 4; k++) {
            wg_ss_n80_ta0_tb1_d(a, dx + 2 * k, dw + 32 * k);
            wg_ss_n80_ta0_tb1_d(b, dx + 512 + 2 * k, dw + 32 * k);
        }
        WG_COMMIT();
        WG_WAIT(0);
        if (lead) mbar_arrive(sb + BAR_EMPTY_G + slot * 8);
        if (++slot == 3) { slot = 0; phase ^= 1; }
    }
    fence_regs(a); fence_regs(b);
}

template <bool SPLIT> __device__ __forceinline__ void gemm_half(uint32_t sb, uint32_t n0_, float (&a)[40]) {
    zero_regs(a);
    const uint32_t n0 = __shfl_sync(~0u, n0_, 0);
    const bool lead = (threadIdx.x & 31) == 0;
#pragma unroll 1
    for (uint32_t c = 0; c < 10; c++) {
        const uint32_t n = n0 + c;
        if (SPLIT && (n == 4 || n == 7)) mbar_wait(sb + BAR_WQ + (n == 4 ? 0 : 8), 0);
        mbar_wait(sb + BAR_FULL_X + (n & 3) * 8, (n >> 2) & 1);
        const uint64_t dx = desc(sb + OFF_XA + (n & 3) * 8192, 16, SW128 | 64), dw = desc(sb + OFF_WA + c * 10240 + (SPLIT ? 8192 : 0), 2048, SW32 | 16);
        const uint64_t dv = desc(sb + OFF_WA + c * 10240, 8192, SW128 | 64);
        WG_FENCE();
#pragma unroll
        for (int k = 0; k < 4; k++) {
            if constexpr (SPLIT) {
                wg_ss_n64_ta0_tb1_d(*reinterpret_cast<float(*)[32]>(&a[0]), dx + 2 * k, dv + 128 * k);
                wg_ss_n16_ta0_tb1_d(*reinterpret_cast<float(*)[8]>(&a[32]), dx + 2 * k, dw + 32 * k);
            } else {
                wg_ss_n80_ta0_tb1_d(a, dx + 2 * k, dw + 32 * k);
            }
        }
        WG_COMMIT();
        WG_WAIT(1);
        if (lead && c) mbar_arrive(sb + BAR_EMPTY_X + ((n - 1) & 3) * 8);
    }
    WG_WAIT(0);
    if (lead) mbar_arrive(sb + BAR_EMPTY_X + ((n0 + 9) & 3) * 8);
    fence_regs(a);
}

__device__ __forceinline__ void mma16816(float (&d)[4], uint32_t a0, uint32_t a1, uint32_t a2, uint32_t a3, uint32_t b0, uint32_t b1) {
    asm volatile("mma.sync.aligned.m16n8k16.row.col.f32.bf16.bf16.f32 {%0, %1, %2, %3}, {%4, %5, %6, %7}, {%8, %9}, {%0, %1, %2, %3};"
                 : "+f"(d[0]), "+f"(d[1]), "+f"(d[2]), "+f"(d[3]) : "r"(a0), "r"(a1), "r"(a2), "r"(a3), "r"(b0), "r"(b1));
}

__device__ __forceinline__ void store_tile(uint32_t stage, __nv_bfloat16* dst, int lane, const float (&a)[40]) {
    stage_tile<0>(stage + (lane & 15) * 160 + (lane >> 4) * 16, 16, a);
    __syncwarp();
#pragma unroll
    for (int u = 0; u < 5; u++) {
        const int x = lane + 32 * u, row = (x * 205) >> 11;
        const uint4 v = lds128(stage + x * 16);
        *reinterpret_cast<uint4*>(dst + row * (1280 - 80) + x * 8) = v;
    }
    __syncwarp();
}

__device__ __forceinline__ void linear_out(uint32_t sb, int half, uint32_t dst, int q) {
    float d[44]; zero_regs(d);
    const uint64_t da = desc(sb + OFF_PK + half * 10240, 128, 80), db = desc(sb + OFF_KVB, 1408, 8);
    WG_FENCE();
#pragma unroll
    for (int k = 0; k < 5; k++) wg_ss_n88_ta0_tb1_d(d, da + 16 * k, db + 176 * k);
    WG_COMMIT();
    WG_WAIT(0);
    fence_regs(d);
    bar_sync(6, 128);
    float r0[4], r1[4];
    const int base = (threadIdx.x & 31) & ~3;
#pragma unroll
    for (int e = 0; e < 4; e++) d[40 + e] = rcpf(d[40 + e] + 1e-6f);
#pragma unroll
    for (int h = 0; h < 4; h++) {
        r0[h] = __shfl_sync(~0u, d[40 + (h & 1)], base + (h >> 1));
        r1[h] = __shfl_sync(~0u, d[42 + (h & 1)], base + (h >> 1));
    }
    uint32_t r[20];
#pragma unroll
    for (int b = 0; b < 10; b++) {
        const int hl = (8 * b) / 20, hh = (8 * b + 6) / 20;
        const bool up = hl != hh && q >= 2;
        const float s0 = up ? r0[hh] : r0[hl], s1 = up ? r1[hh] : r1[hl];
        r[2 * b] = pack_bf16(d[4 * b] * s0, d[4 * b + 1] * s0);
        r[2 * b + 1] = pack_bf16(d[4 * b + 2] * s1, d[4 * b + 3] * s1);
    }
#pragma unroll
    for (int k = 0; k < 5; k++) stsm4(dst + 32 * k, r[4 * k], r[4 * k + 1], r[4 * k + 2], r[4 * k + 3]);
}

__global__ void __launch_bounds__(NTHR, 1) fused_kernel(const __grid_constant__ Params P) {
    extern __shared__ __align__(1024) uint8_t smem[];
    const uint32_t sb = (uint32_t)__cvta_generic_to_shared(smem);
    const int tid = threadIdx.x, lane = tid & 31;
    const int wg = __shfl_sync(~0u, tid >> 7, 0), warp = __shfl_sync(~0u, (tid >> 5) & 3, 0);
    const int cta = blockIdx.x, i = cta >> 3, j = cta & 7;
    const int q = lane & 3, r0 = 16 * warp + (lane >> 2);
    if (wg == 4 || wg == 0) TS(wg == 4 ? 0 : 16);

    const uint32_t tag = *(volatile uint32_t*)&g_epoch + 1;

    if (cta >= NCTA) {
        if (tid < 64 && elect_one()) {
            const int jj = 2 * (cta - NCTA) + warp;
            const uint32_t buf = sb + warp * 102400, bar = sb + OFF_BAR + warp * 80;
#pragma unroll 1
            for (int s = 0; s < 10; s++) mbar_init(bar + s * 8, 1);
            asm volatile("fence.mbarrier_init.release.cluster;" ::: "memory");
            int lp = 0, lc = 0;
#pragma unroll 1
            for (int n = -8; n < 40; n++) {
                if (n >= 0) {
                    const int part = n / 10, c = n - 10 * part;
                    mbar_wait(bar + c * 8, part & 1);
                    bulk_store(g_wt + ((part * 8 + jj) * 10 + c) * 10240, buf + c * 10240, 10240);
                    bulk_commit();
                    if (c == 9) { bulk_wait(); st_flag(g_flag_w + part * 8 + jj, tag); }
                    else asm volatile("cp.async.bulk.wait_group.read 2;" ::: "memory");
                }
                if (lp < 4) {
                    mbar_expect(bar + lc * 8, 10240);
                    tma3d(buf + lc * 10240, lp < 2 ? &P.wqkv : lp == 2 ? &P.wob : &P.woa, 64 * lc, 5 * jj + (lp == 0 ? 80 : 0), bar + lc * 8);
                    if (++lc == 10) { lc = 0; lp++; }
                }
            }
        }
        return;
    }
    if (tid == 640) {
        mbar_init(sb + BAR_KVIN, 1);
        asm volatile("fence.mbarrier_init.release.cluster;" ::: "memory");
        mbar_expect(sb + BAR_KVIN, 51200 + 20480);
        tma3d(sb + OFF_X16, &P.xa16, 16 * cta, 0, sb + BAR_KVIN);
#pragma unroll
        for (int u = 0; u < 4; u++) {
            const int v = (u + cta) & 3;
            bulk1d(sb + OFF_WRAW + v * 12800, P.in[2 + (v >> 1)] + (v & 1) * 12800, 12800, sb + BAR_KVIN);
        }
    } else if (tid == 672) {
#pragma unroll
        for (int s = 0; s < 3; s++) {
            mbar_init(sb + BAR_FULL_G + s * 8, 2);
            mbar_init(sb + BAR_EMPTY_G + s * 8, 4);
            mbar_init(sb + BAR_FULL_KV + s * 8, 1);
            mbar_init(sb + BAR_EMPTY_KV + s * 8, 16);
        }
        mbar_init(sb + BAR_OA, 16);
        mbar_init(sb + BAR_OA + 8, 16);
        asm volatile("fence.mbarrier_init.release.cluster;" ::: "memory");
    } else if (tid == 704) {
        prefetch_map(&P.xa);
        prefetch_map(&P.wq64);
        prefetch_map(&P.wq16);
        prefetch_l2(P.in[1] + cta * 6400, 6400);
        mbar_init(sb + BAR_WA, 1);
        mbar_init(sb + BAR_PART, 4);
        mbar_init(sb + BAR_KVB, 1);
        mbar_init(sb + BAR_OB, 4);
        sts32(sb + OFF_PUB, 0);
        sts128(sb + OFF_STAT + 16, 0x357F357Fu, 0u, 0u, 0u);
        asm volatile("fence.mbarrier_init.release.cluster;" ::: "memory");
    } else if (tid == 736) {
#pragma unroll
        for (int s = 0; s < 4; s++) { mbar_init(sb + BAR_FULL_X + s * 8, 1); mbar_init(sb + BAR_EMPTY_X + s * 8, 4); }
#pragma unroll
        for (int s = 0; s < 4; s++) sts128(sb + OFF_QUEUE + s * 16, 0u, 0u, 0u, 0u);
        mbar_init(sb + BAR_A0, 1);
        mbar_init(sb + BAR_Q, 4);
        mbar_init(sb + BAR_Q + 8, 4);
        mbar_init(sb + BAR_C0, 16);
        for (int s = 0; s < 2; s++) mbar_init(sb + BAR_WQ + s * 8, 1);
        asm volatile("fence.mbarrier_init.release.cluster;" ::: "memory");
    }
    __syncthreads();

    if (wg == 5) {
        asm volatile("setmaxnreg.dec.sync.aligned.u32 32;");
        if (warp == 0) {
            if (elect_one()) {
#pragma unroll 1
                for (int n = 0; n < 20; n++) {
                    const uint32_t s = n & 3, bar = sb + BAR_FULL_X + s * 8;
                    if (n >= 4) mbar_wait(sb + BAR_EMPTY_X + s * 8, ((n >> 2) - 1) & 1);
                    mbar_expect(bar, n < 4 ? 18432 : 8192);
                    tma2d(sb + OFF_XA + s * 8192, &P.xa, n < 10 ? 64 * n : 64 * n - 640, 128 * i + (n < 10 ? 0 : 64), bar);
                    if (n < 4) {
                        tma2d(sb + OFF_WA + n * 10240, &P.wq64, 80 * j, 64 * n, bar);
                        tma2d(sb + OFF_WA + n * 10240 + 8192, &P.wq16, 80 * j + 64, 64 * n, bar);
                    }
                    if (n == 3) {
                        mbar_expect(sb + BAR_WQ, 30720);
                        mbar_expect(sb + BAR_WQ + 8, 30720);
#pragma unroll 1
                        for (int c = 4; c < 10; c++) {
                            tma2d(sb + OFF_WA + c * 10240, &P.wq64, 80 * j, 64 * c, sb + BAR_WQ + (c < 7 ? 0 : 8));
                            tma2d(sb + OFF_WA + c * 10240 + 8192, &P.wq16, 80 * j + 64, 64 * c, sb + BAR_WQ + (c < 7 ? 0 : 8));
                        }
                    }
                }
                Ring r{0, 0};
#pragma unroll 1
                for (int pass = 1; pass < 5; pass++) {
                    const CUtensorMap* m = pass <= 3 ? &P.xb : &P.ob;
                    if (pass == 4) {
                        mbar_wait(sb + BAR_OB, 0);
                        tma2d_store(&P.ob_st, 80 * j, 128 * i, sb + OFF_PK);
                        bulk_commit();
                        bulk_wait();
                        st_flag(g_flag_b2 + cta, tag);
                        poll8(g_flag_b2 + i * 8, tag);
                    }
#pragma unroll 1
                    for (int c = 0; c < 10; c++) {
                        if (pass == 3 && c == 3) {
                            mbar_wait(sb + BAR_PART, 0);
                            bulk_add_f32(g_part + j * 1920, sb + OFF_PST, 7680);
                            bulk_commit();
                        }
                        mbar_wait(sb + BAR_EMPTY_G + r.slot * 8, r.phase);
                        mbar_expect(sb + BAR_FULL_G + r.slot * 8, 16384);
                        tma2d(sb + OFF_STAGE + r.slot * STAGE_BYTES, m, 64 * c, 128 * i, sb + BAR_FULL_G + r.slot * 8);
                        next_stage(r);
                        if (pass == 3 && c == 3) {
                            bulk_wait();
                            st_flag(g_flag_b1 + j * 16 + i, tag);
                        }
                    }
                }
                {
                    poll8(g_flag_a + i * 8, tag);
                    mbar_arrive(sb + BAR_A0);
#pragma unroll 1
                    for (int c = 0; c < 10; c++) {
                        const uint32_t s = c & 3;
                        mbar_wait(sb + BAR_EMPTY_X + s * 8, (c >> 2) & 1);
                        mbar_expect(sb + BAR_FULL_X + s * 8, 8192);
                        tma2d(sb + OFF_XA + s * 8192, &P.oa, 64 * c, 128 * i, sb + BAR_FULL_X + s * 8);
                    }
                }
            }
        } else if (warp == 2) {
            if (elect_one()) {
                Ring r{0, 0};
#pragma unroll 1
                for (int pass = 1; pass < 5; pass++) {
                    const CUtensorMap* m = pass <= 3 ? &P.wqkv : &P.wob;
                    const int col = 5 * j + (pass == 1 ? 40 : pass == 2 ? 80 : 0);
                    const bool pre = pass >= 2 && P.helpers;
                    if (pre) poll1(g_flag_w + (pass - 2) * 8 + j, tag);
#pragma unroll 1
                    for (int c = 0; c < 10; c++) {
                        mbar_wait(sb + BAR_EMPTY_G + r.slot * 8, r.phase);
                        const uint32_t bar = sb + BAR_FULL_G + r.slot * 8;
                        mbar_expect(bar, 10240);
                        const uint32_t dst = sb + OFF_STAGE + r.slot * STAGE_BYTES + 16384;
                        if (pre) bulk1d(dst, g_wt + (((pass - 2) * 8 + j) * 10 + c) * 10240, 10240, bar);
                        else tma3d(dst, m, 64 * c, col, bar);
                        next_stage(r);
                    }
                }
                {
                    if (P.helpers) poll1(g_flag_w + 24 + j, tag);
#pragma unroll 1
                    for (int c = 0; c < 3; c++) { mbar_wait(sb + BAR_EMPTY_G + r.slot * 8, r.phase); next_stage(r); }
                    mbar_expect(sb + BAR_WA, 102400);
                    if (P.helpers) bulk1d(sb + OFF_WA, g_wt + (24 + j) * 102400, 102400, sb + BAR_WA);
                    else {
#pragma unroll 1
                        for (int c = 0; c < 10; c++) tma3d(sb + OFF_WA + c * 10240, &P.woa, 64 * c, 5 * j, sb + BAR_WA);
                    }
                }
            }
        } else if (warp == 3) {
            bar_sync(12, 96);
            if (elect_one()) {
                st_flag(g_flag_kv + cta, tag);
                prefetch_l2(P.in[5] + cta * 20480, 20480);
#pragma unroll 1
                for (int u = 0; u < 5; u++) prefetch_l2(P.in[6] + (cta * 5 + u) * 3840 + 1280, 1280);
            }
            __syncwarp();
            {
                if (elect_one()) {
                    poll8(g_flag_b1 + j * 16, tag);
                    poll8(g_flag_b1 + j * 16 + 8, tag);
                    mbar_expect(sb + BAR_KVB, 7680);
                    bulk1d(sb + OFF_PST, g_part + j * 1920, 7680, sb + BAR_KVB);
                }
            }
            if (elect_one()) {
                mbar_wait(sb + BAR_OA, 0);
                tma2d_store(&P.oa_st, 80 * j, 128 * i, sb + OFF_Q);
                bulk_commit();
                bulk_wait();
                st_flag(g_flag_a + cta, tag);
            }
        } else if (warp == 1) {
            uint32_t sk, spin = 0;
            bar_sync(12, 96);
            __nanosleep(800);
#pragma unroll 1
            while (true) {
                const uint4 f = ld_relaxed128(g_stat + 4 * lane);
                const uint32_t t = tag << 16;
                sk = max(max(f.x ^ t, f.y ^ t), max(f.z ^ t, f.w ^ t));
                sk = __reduce_max_sync(~0u, sk);
                if (sk < 0x10000u || ++spin > (1u << 17)) break;
            }
            if (lane == 0) {
                sts32(sb + OFF_STAT, sk << 16);
            }
            mbar_wait(sb + BAR_C0, 0);
            if (lane == 0) {
                mbar_arrive(sb + BAR_FULL_KV);
                asm volatile("st.release.cta.shared::cta.u32 [%0], %1;" :: "r"(sb + OFF_PUB), "r"(1) : "memory");
            }
            __syncwarp();
            __nanosleep(300);
            const uint32_t t2 = (tag & 0xFFFFu) * 0x10001u;
#pragma unroll 1
            for (spin = 0; spin < (1u << 17); spin++) {
                const uint4 f = ld_acquire128(g_flag_kv + 8 * (lane & 15));
                if (__all_sync(~0u, f.x == t2 && f.y == t2 && f.z == t2 && f.w == t2)) break;
            }
            if (elect_one()) {
                fence_async();
#pragma unroll 1
                for (int n = 1; n < 3; n++) {
                    mbar_expect(sb + BAR_FULL_KV + n * 8, RING_BYTES);
                    bulk1d(sb + OFF_RING + n * RING_BYTES, g_kv + n * RING_BYTES, RING_BYTES, sb + BAR_FULL_KV + n * 8);
                }
                Ring r{1, 0};
#pragma unroll 1
                for (int n = 1; n < 16; n++) {
                    if (n >= 3) {
                        mbar_wait(sb + BAR_EMPTY_KV + r.slot * 8, r.phase ^ 1);
                        mbar_expect(sb + BAR_FULL_KV + r.slot * 8, RING_BYTES);
                        bulk1d(sb + OFF_RING + r.slot * RING_BYTES, g_kv + (n & 7) * RING_BYTES, RING_BYTES, sb + BAR_FULL_KV + r.slot * 8);
                    }
                    mbar_wait(sb + BAR_FULL_KV + r.slot * 8, r.phase);
                    asm volatile("st.release.cta.shared::cta.u32 [%0], %1;" :: "r"(sb + OFF_PUB), "r"(n + 1) : "memory");
                    next_stage(r);
                }
            }
        }
    } else if (wg < 4) {
        if (tid < 30) reinterpret_cast<uint4*>(g_part + j * 1920 + i * 120)[tid] = make_uint4(0u, 0u, 0u, 0u);
        if (wg < 2) {
            const uint32_t kw = 4 * wg + warp, g = lane >> 2;
            const uint32_t w0 = sb + OFF_WRAW + (80 * kw + 4 * q) * 40;
            const uint32_t wa[3] = {w0 + g * 4, w0 + g * 4 + 25608, w0 + 32 + (g & 1) * 4 + (g & 2) * 12784};
            float d[3][2][4];
#pragma unroll
            for (int e = 0; e < 24; e++) (&d[0][0][0])[e] = 0.f;
            mbar_wait(sb + BAR_KVIN, 0);
            if (wg == 0) TS(13);
            uint2 x[2][2];
            uint32_t u[2][12];
#pragma unroll
            for (int s = 0; s < 6; s++) {
                if (s < 5) {
                    const uint32_t st = 5 * kw + s;
                    const uint32_t xa = sb + OFF_X16 + (st >> 2) * 2048 + g * 128 + (((2 * (st & 3) + (q >> 1)) ^ g) << 4) + (q & 1) * 8;
                    x[s & 1][0] = lds64(xa); x[s & 1][1] = lds64(xa + 1024);
#pragma unroll
                    for (int e = 0; e < 12; e++) u[s & 1][e] = lds32(wa[e >> 2] + s * 640 + (e & 3) * 40);
                }
                if (s > 0) {
                    const int p = (s - 1) & 1;
#pragma unroll
                    for (int t = 0; t < 3; t++) {
                        const uint32_t a0 = __byte_perm(u[p][4 * t], u[p][4 * t + 1], 0x5410), a1 = __byte_perm(u[p][4 * t], u[p][4 * t + 1], 0x7632);
                        const uint32_t a2 = __byte_perm(u[p][4 * t + 2], u[p][4 * t + 3], 0x5410), a3 = __byte_perm(u[p][4 * t + 2], u[p][4 * t + 3], 0x7632);
                        mma16816(d[t][0], a0, a1, a2, a3, x[p][0].x, x[p][0].y);
                        mma16816(d[t][1], a0, a1, a2, a3, x[p][1].x, x[p][1].y);
                    }
                }
            }
            bar_arrive(2, 384);
#pragma unroll
            for (int t = 0; t < 3; t++) {
                const uint32_t pr = t == 0 ? g : t == 1 ? 12 + g : 8 + g;
                if (t < 2 || g < 4) {
#pragma unroll
                    for (int h = 0; h < 2; h++) {
                        const uint32_t a = sb + OFF_KVP + kw * 2560 + ((8 * h + 2 * q) * 20 + pr) * 8;
                        sts64(a, __float_as_uint(d[t][h][0]), __float_as_uint(d[t][h][2]));
                        sts64(a + 160, __float_as_uint(d[t][h][1]), __float_as_uint(d[t][h][3]));
                    }
                }
            }
            if (wg == 0) TS(14);
        }
        bar_sync(1, 512);
        if (wg < 3) {
            const uint32_t ch = 4 * wg + warp, grp = ch >= 6, c6 = ch - 6 * grp, isv = c6 >= 3, c3 = c6 - 3 * isv;
            const uint32_t key = 8 * grp + (lane >> 2);
            const bool mu = (MUFU_MASK >> ((2 * cta + grp) & 7)) & 1;
            uint32_t word;
            if (c3 == 2 && q >= 2) {
                word = isv ? (q == 2 ? 0x00003F80u : 0u) : mu ? 0u : q == 2 ? 0x3F00433Fu : 0x00003B4Au;
            } else {
                const uint32_t a = sb + OFF_KVP + (key * 20 + 10 * isv + 4 * c3 + q) * 8;
                float s0 = 0.f, s1 = 0.f;
#pragma unroll
                for (int u = 0; u < 8; u++) { const uint2 v = lds64(a + u * 2560); s0 += __uint_as_float(v.x); s1 += __uint_as_float(v.y); }
                const float sc = (isv || mu) ? 1.f : 0.5f;
                word = pack_bf16(s0 * sc, s1 * sc);
            }
            if (cta < 16) st_relaxed64(g_kt + cta * 384 + tid, ((unsigned long long)tag << 32) | word);
            reinterpret_cast<uint32_t*>(g_kv + cta * 1536)[tid] = word;
            if (c3 == 2 && q >= 2) word = 0;
            if (isv) {
                const uint32_t mx = __reduce_max_sync(~0u, max(word & 0x7FFFu, (word >> 16) & 0x7FFFu));
                if (lane == 0) sts32(sb + OFF_KST + 192 + (3 * grp + c3) * 4, mx);
            } else {
                float n2 = fmaf(bf_lo(word), bf_lo(word), bf_hi(word) * bf_hi(word));
                n2 += __shfl_xor_sync(~0u, n2, 1);
                n2 += __shfl_xor_sync(~0u, n2, 2);
                if (q == 0) sts32(sb + OFF_KST + (c3 * 16 + key) * 4, __float_as_uint(mu ? n2 : 4.f * n2));
            }
            if (wg | warp) bar_arrive(3, 384);
            else {
                bar_sync(3, 384);
                TS(15);
                const uint32_t a = sb + OFF_KST + (lane & 15) * 4;
                const float n2 = __uint_as_float(lds32(a)) + __uint_as_float(lds32(a + 64)) + __uint_as_float(lds32(a + 128));
                const uint32_t sk = __reduce_max_sync(~0u, min(((__float_as_uint(n2) & 0x7FFFFFFFu) + 0xFFFFu) >> 16, 0x7FFFu));
                const uint32_t sv = __reduce_max_sync(~0u, lds32(sb + OFF_KST + 192 + min(lane, 5) * 4));
                if (lane == 0) {
                    const bool vok = sv == 0 || (sv >= ((127 - 40) << 7) && sv <= ((127 + 40) << 7));
                    st_relaxed(g_stat + cta, (tag << 16) | (vok ? sk : 0x7FFFu));
                }
                __syncwarp();
                bar_arrive(12, 96);
                TS(17);
            }
        }
        {
            const unsigned long long* src = g_kt + tid * 2;
            uint4 v[6];
#pragma unroll
            for (int u = 0; u < 6; u++) v[u] = make_uint4(0u, ~tag, 0u, 0u);
            __nanosleep(400);
#pragma unroll 1
            for (uint32_t spin = 0; spin < (1u << 16); spin++) {
#pragma unroll
                for (int u = 0; u < 6; u++) if (v[u].y != tag) v[u] = ld_relaxed2x64(src + u * 1024);
                bool ok = true;
#pragma unroll
                for (int u = 0; u < 6; u++) { if (v[u].w != tag) v[u].y = ~tag; ok = ok && v[u].y == tag; }
                if (__all_sync(~0u, ok)) break;
            }
#pragma unroll
            for (int u = 0; u < 6; u++) sts64(sb + OFF_RING + tid * 8 + u * 4096, v[u].x, v[u].z);
            fence_async_smem();
            __syncwarp();
            if (lane == 0) mbar_arrive(sb + BAR_C0);
            if (wg == 0) TS(7);
        }
        uint32_t slot = 0;
        const uint4 cz = lds128(sb + OFF_STAT + 16);
#pragma unroll 1
        for (int pass = 0; pass < 2; pass++) {
            uint32_t qf[6];
            mbar_wait(sb + BAR_Q + pass * 8, 0);
            const uint32_t qa = sb + OFF_Q + pass * 10240 + r0 * 160 + wg * 40 + q * 4;
            qf[0] = lds32(qa); qf[1] = lds32(qa + 8 * 160);
            qf[2] = lds32(qa + 16); qf[3] = lds32(qa + 8 * 160 + 16);
            qf[4] = q < 2 ? lds32(qa + 32) : 0u; qf[5] = q < 2 ? lds32(qa + 8 * 160 + 32) : 0u;
            if (pass == 0) { count_wait(sb + OFF_PUB, 0, 1); if (wg == 0) { TS(19); TC(26); } }
            float n0 = 0.f, n1 = 0.f;
#pragma unroll
            for (int e = 0; e < 3; e++) {
                n0 = fmaf(bf_lo(qf[2 * e]), bf_lo(qf[2 * e]), fmaf(bf_hi(qf[2 * e]), bf_hi(qf[2 * e]), n0));
                n1 = fmaf(bf_lo(qf[2 * e + 1]), bf_lo(qf[2 * e + 1]), fmaf(bf_hi(qf[2 * e + 1]), bf_hi(qf[2 * e + 1]), n1));
            }
            n0 += __shfl_xor_sync(~0u, n0, 1); n0 += __shfl_xor_sync(~0u, n0, 2);
            n1 += __shfl_xor_sync(~0u, n1, 1); n1 += __shfl_xor_sync(~0u, n1, 2);
            const float k2 = __uint_as_float(lds32(sb + OFF_STAT));
            const uint32_t bad = !(n0 * k2 <= 4000.f && n1 * k2 <= 4000.f);
            uint32_t anybad;
            asm volatile("{\n.reg .pred p, r;\nsetp.ne.u32 p, %1, 0;\nbar.red.or.pred r, %2, 128, p;\nselp.u32 %0, 1, 0, r;\n}" : "=r"(anybad) : "r"(bad), "r"(8 + wg) : "memory");
            float o[12];
#pragma unroll
            for (int k = 0; k < 12; k++) o[k] = 0.f;
            fence_regs(o);
            if (!__shfl_sync(~0u, anybad, 0)) {
                if (q >= 2) qf[4] = qf[5] = q == 2 ? 0x3F803F80u : 0x00003F80u;
                attend<true>(sb, slot, pass, qf, o, cz.x, cz.y, cz.z);
            } else {
                attend<false>(sb, slot, pass, qf, o, cz.x, cz.y, cz.z);
            }
            const float i0 = rcpf(__shfl_sync(~0u, o[8], (lane & ~3) | 2)), i1 = rcpf(__shfl_sync(~0u, o[10], (lane & ~3) | 2));
            const uint32_t ot = opaque_tid(), ol = ot & 31, oq = ot & 3;
            uint8_t* const gx = g_ox + opaque_cta() * 10240;
#pragma unroll
            for (int b = 0; b < 3; b++) {
                if (b < 2 || oq < 2) {
                    const uint32_t v0 = pack_bf16(o[4 * b] * i0, o[4 * b + 1] * i0), v1 = pack_bf16(o[4 * b + 2] * i1, o[4 * b + 3] * i1);
                    const uint32_t col = 20 * (ot >> 7) + 8 * b + 2 * oq;
                    const uint32_t x = (col >> 4) * 2048 + (ot & 96) * 16 + (col & 8) * 16 + (ol >> 2) * 16 + (col & 7) * 2;
                    st_relaxed(gx + x, pass ? v0 : ~0u);
                    st_relaxed(gx + x + 256, pass ? v1 : ~0u);
                    const uint32_t dst = sb + OFF_Q + (pass ? 10240 + x : (((ot & 96) >> 1) + (ol >> 2)) * 160 + col * 2);
                    sts32(dst, v0);
                    sts32(dst + (pass ? 256 : 8 * 160), v1);
                }
            }
            fence_async_smem();
            __syncwarp();
            if (lane == 0) mbar_arrive(sb + BAR_OA + pass * 8);
            if (wg == 0) { TS(20 + pass); TC(27 + pass); }
        }
        TS(22 + wg);
        {
            const uint32_t ot = opaque_tid(), oc = opaque_cta();
            const int lane = ot & 31, i = oc >> 3, j = oc & 7;
            if (wg != 0) {
                const int u = 4 * (3 - wg) + warp;
                uint4 v[12];
                const uint8_t* src[3];
                uint32_t entry = u + 1;
#pragma unroll
                for (int t = 0; t < 3; t++) {
                    const int s = min(3 * u + t, 34), h = (s * 37) >> 8;
                    const int g = 5 * ((j + 1 + s - 7 * h) & 7) + 4 - h;
                    src[t] = g_ox + (i * 40 + g) * 2048 + lane * 16;
                    entry |= g << (8 * t + 8);
                }
#pragma unroll
                for (int k = 0; k < 12; k++) v[k] = make_uint4(k >= 8 && u == 11 ? 0u : ~0u, 0u, 0u, 0u);
                const uint8_t* const probe = (lane < 8 ? src[0] : lane < 16 ? src[1] : src[2]) - lane * 16 + (lane & 6) * 256 + (lane & 1) * 128 + 368;
                uint32_t wait = u == 11 ? 0xFFFFu : 0xFFFFFFu;
                mbar_wait(sb + BAR_A0, 0);
#pragma unroll 1
                for (uint32_t spin = 0; spin < (1u << 16); spin++) {
                    uint4 p = make_uint4(0u, 0u, 0u, 0u);
                    if (mbar_test(sb + BAR_OA + 8, 0)) wait = 0;
                    if ((wait >> lane) & 1) p = ld_relaxed128(probe);
#pragma unroll
                    for (int k = 0; k < 12; k++) if (!((wait >> (2 * (k & 12))) & 0xFF) && v[k].x == ~0u) v[k] = ld_relaxed128(src[k >> 2] + (k & 3) * 512);
                    wait = __ballot_sync(~0u, p.x == ~0u || p.w == ~0u);
                    bool ok = true;
#pragma unroll
                    for (int k = 0; k < 12; k++) {
                        if (v[k].y == ~0u || v[k].z == ~0u || v[k].w == ~0u) v[k].x = ~0u;
                        ok = ok && v[k].x != ~0u;
                    }
                    if (__all_sync(~0u, ok)) break;
                }
                mbar_wait(sb + BAR_OA + 8, 0);
#pragma unroll
                for (int k = 0; k < 12; k++) sts128(sb + OFF_RING + u * 6144 + k * 512 + lane * 16, v[k].x, v[k].y, v[k].z, v[k].w);
                fence_async_smem();
                __syncwarp();
                if (lane == 0) {
                    uint32_t n;
                    asm volatile("atom.relaxed.cta.shared::cta.add.u32 %0, [%1], 1;" : "=r"(n) : "r"(sb + OFF_QUEUE + 48) : "memory");
                    asm volatile("st.release.cta.shared::cta.u32 [%0], %1;" :: "r"(sb + OFF_QUEUE + n * 4), "r"(entry) : "memory");
                }
            } else {
                float a[40];
                mbar_wait(sb + BAR_WA, 0);
                mbar_wait(sb + BAR_OA + 8, 0);
                const uint64_t dw = desc(sb + OFF_WA, 2048, SW32 | 16);
                {
                    const uint64_t da = desc(sb + OFF_Q + 10240, 128, 16);
                    WG_FENCE();
#pragma unroll
                    for (int t = 0; t < 5; t++) {
                        const uint32_t g = 5 * j + t;
                        if (t == 0) wg_ss_n80_ta0_tb1_initd(a, da, dw + (g >> 2) * 640 + (g & 3) * 32);
                        else wg_ss_n80_ta0_tb1_d(a, da + 128 * t, dw + (g >> 2) * 640 + (g & 3) * 32);
                    }
                    WG_COMMIT();
                }
#pragma unroll 1
                for (int n = 0; n < 12; n++) {
                    const uint32_t e = __shfl_sync(~0u, queue_wait(sb + OFF_QUEUE + n * 4), 0);
                    const uint64_t da = desc(sb + OFF_RING - 6144 + (e & 15) * 6144, 128, 16);
                    WG_FENCE();
#pragma unroll
                    for (int t = 0; t < 3; t++) {
                        const uint32_t g = (e >> (8 * t + 8)) & 63;
                        wg_ss_n80_ta0_tb1_d(a, da + 128 * t, dw + (g >> 2) * 640 + (g & 3) * 32);
                    }
                    WG_COMMIT();
                }
                WG_WAIT(0);
                fence_regs(a);
                bar_sync(8, 128);
                store_tile(sb + OFF_Q + 10240 + warp * 2560, P.out + (128 * i + 64 + 16 * warp) * 1280 + 80 * j, lane, a);
                TS(11);
            }
        }
    } else {
        asm volatile("setmaxnreg.inc.sync.aligned.u32 128;");
        const uint32_t mrow = 16 * warp + (lane & 15), mcol = lane >> 4;
        const uint32_t xrow = mrow * 160 + mcol * 16, xgrp = (mrow & 7) * 16 + mcol * 128;
        bar_sync(2, 384);
#pragma unroll 1
        for (int half = 0; half < 2; half++) {
            float a[40];
            gemm_half<true>(sb, 10 * half, a);
            if (!half) TS(1);
            if (half && lane == 0) { mbar_arrive(sb + BAR_EMPTY_G); mbar_arrive(sb + BAR_EMPTY_G + 8); mbar_arrive(sb + BAR_EMPTY_G + 16); }
            stage_tile<1>(sb + OFF_Q + half * 10240 + xrow, 16, a);
            __syncwarp();
            if (lane == 0) mbar_arrive(sb + BAR_Q + half * 8);
            if (half) TS(2);
        }
#pragma unroll 1
        for (int pass = 1; pass < 5; pass++) {
        if (pass == 4) {
        mbar_wait(sb + BAR_KVB, 0);
        if (tid < 592) {
            const int m = tid - 512, h = m / 20;
            const uint32_t x0 = sb + OFF_KVB + (m >> 3) * 1408 + (m & 7) * 16;
#pragma unroll
            for (int e = 0; e < 5; e++) {
                const uint4 v = lds128(sb + OFF_PST + m * 96 + e * 16);
                const int n = 20 * h + 4 * e;
                sts64(x0 + (n >> 3) * 128 + (n & 4) * 2, pack_bf16(__uint_as_float(v.x), __uint_as_float(v.y)), pack_bf16(__uint_as_float(v.z), __uint_as_float(v.w)));
            }
            sts16(x0 + 1280 + h * 2, (uint16_t)pack_bf16(__uint_as_float(lds32(sb + OFF_PST + m * 96 + 80)), 0.f));
        }
        fence_async_smem();
        bar_sync(6, 128);
#pragma unroll 1
        for (int half = 0; half < 2; half++) linear_out(sb, half, sb + OFF_PK + half * 10240 + xrow, q);
        fence_async_smem();
        __syncwarp();
        if (lane == 0) mbar_arrive(sb + BAR_OB);
        }
        float a[40], b[40];
        gemm_pass(sb, pass, a, b);
        if (pass == 1 || pass == 3) {
        TS(pass == 1 ? 3 : 6);
        stage_tile<2>(sb + OFF_PK + (mrow >> 3) * 1280 + xgrp, 128, a);
        stage_tile<2>(sb + OFF_PK + (8 + (mrow >> 3)) * 1280 + xgrp, 128, b);
        } else if (pass == 2) {
        TS(4);
        stage_tile<0>(sb + OFF_V + 128 + (mrow >> 3) * 1536 + xgrp, 128, a);
        stage_tile<0>(sb + OFF_V + 128 + (8 + (mrow >> 3)) * 1536 + xgrp, 128, b);
        {
            const uint32_t x = sb + OFF_V + ((tid - 512) >> 3) * 1536 + (tid & 7) * 16;
            sts128(x, 0x3F80u, 0u, 0u, 0u);
            sts128(x + 11 * 128, 0x3F80u, 0u, 0u, 0u);
        }
        fence_async_smem();
        bar_sync(6, 128);
        {
            float d1[36], d2[16]; zero_regs(d1); zero_regs(d2);
            const uint64_t da = desc(sb + OFF_PK, 1280, 8), db = desc(sb + OFF_V, 1536, 8);
            WG_FENCE();
#pragma unroll
            for (int k = 0; k < 8; k++) {
                wg_ss_n72_ta1_tb1_d(d1, da + 160 * k, db + 192 * k);
                wg_ss_n32_ta1_tb1_d(d2, da + 16 + 160 * k, db + 64 + 192 * k);
            }
            WG_COMMIT();
            WG_WAIT(0);
            fence_regs(d1); fence_regs(d2);
            bar_sync(6, 128);
#pragma unroll
            for (int u = 0; u < 7; u++) if (u < 6 || tid < 624) sts128(sb + OFF_KVB + (tid - 512 + 128 * u) * 16, 0u, 0u, 0u, 0u);
            const uint32_t part = sb + OFF_PST;
#pragma unroll
            for (int hh = 0; hh < 2; hh++) {
                const int m = r0 + 8 * hh;
                if (m < 60) {
                    const int h20 = (m / 20) * 20;
                    if (q == 0) sts128(part + m * 96 + 80, __float_as_uint(d1[2 * hh]), 0u, 0u, 0u);
#pragma unroll
                    for (int k = 1; k < 9; k++) {
                        const int e = 8 * (k - 1) + 2 * q - h20;
                        if (e >= 0 && e < 20) sts64(part + m * 96 + e * 4, __float_as_uint(d1[4 * k + 2 * hh]), __float_as_uint(d1[4 * k + 2 * hh + 1]));
                    }
                }
                if (m >= 44) {
                    if (q == 0) sts128(part + (m + 16) * 96 + 80, __float_as_uint(d2[12 + 2 * hh]), 0u, 0u, 0u);
#pragma unroll
                    for (int k = 0; k < 3; k++) {
                        const int e = 8 * k + 2 * q - 4;
                        if (e >= 0) sts64(part + (m + 16) * 96 + e * 4, __float_as_uint(d2[4 * k + 2 * hh]), __float_as_uint(d2[4 * k + 2 * hh + 1]));
                    }
                }
            }
            fence_async_smem();
            __syncwarp();
            if (lane == 0) mbar_arrive(sb + BAR_PART);
        }
        } else {
        __nv_bfloat16* out = P.out + (128 * i + 16 * warp) * 1280 + 80 * j + 640;
        mbar_wait(sb + BAR_A0, 0);
        store_tile(sb + OFF_Q + warp * 2560, out, lane, a);
        store_tile(sb + OFF_Q + warp * 2560, out + 64 * 1280, lane, b);
        TS(9);
        }
        }
        {
            mbar_wait(sb + BAR_WA, 0);
            float a[40];
            gemm_half<false>(sb, 20, a);
            store_tile(sb + OFF_Q + warp * 2560, P.out + (128 * i + 16 * warp) * 1280 + 80 * j, lane, a);
            TS(12);
        }
        if (cta == 0 && tid == 512) *(volatile uint32_t*)&g_epoch = tag;
    }
}

typedef CUresult (*EncodeFn)(CUtensorMap*, CUtensorMapDataType, cuuint32_t, void*, const cuuint64_t*, const cuuint64_t*,
                             const cuuint32_t*, const cuuint32_t*, CUtensorMapInterleave, CUtensorMapSwizzle,
                             CUtensorMapL2promotion, CUtensorMapFloatOOBfill);

void make_map(EncodeFn enc, CUtensorMap* m, const void* p, uint32_t box_cols, uint32_t box_rows, uint64_t rows = 2048) {
    cuuint64_t dims[2] = {640, rows}, strides[1] = {1280};
    cuuint32_t box[2] = {box_cols, box_rows}, es[2] = {1, 1};
    enc(m, CU_TENSOR_MAP_DATA_TYPE_BFLOAT16, 2, const_cast<void*>(p), dims, strides, box, es, CU_TENSOR_MAP_INTERLEAVE_NONE,
        box_cols == 64 ? CU_TENSOR_MAP_SWIZZLE_128B : box_cols == 16 ? CU_TENSOR_MAP_SWIZZLE_32B : CU_TENSOR_MAP_SWIZZLE_NONE, CU_TENSOR_MAP_L2_PROMOTION_L2_128B, CU_TENSOR_MAP_FLOAT_OOB_FILL_NONE);
}
void make_x16map(EncodeFn enc, CUtensorMap* m, const void* p) {
    cuuint64_t dims[3] = {64, 2048, 10}, strides[2] = {1280, 128};
    cuuint32_t box[3] = {64, 16, 10}, es[3] = {1, 1, 1};
    enc(m, CU_TENSOR_MAP_DATA_TYPE_BFLOAT16, 3, const_cast<void*>(p), dims, strides, box, es, CU_TENSOR_MAP_INTERLEAVE_NONE,
        CU_TENSOR_MAP_SWIZZLE_128B, CU_TENSOR_MAP_L2_PROMOTION_L2_128B, CU_TENSOR_MAP_FLOAT_OOB_FILL_NONE);
}
void make_wmap(EncodeFn enc, CUtensorMap* m, const void* p, uint64_t cols) {
    cuuint64_t dims[3] = {16, 640, cols / 16}, strides[2] = {cols * 2, 32};
    cuuint32_t box[3] = {16, 64, 5}, es[3] = {1, 1, 1};
    enc(m, CU_TENSOR_MAP_DATA_TYPE_BFLOAT16, 3, const_cast<void*>(p), dims, strides, box, es, CU_TENSOR_MAP_INTERLEAVE_NONE,
        CU_TENSOR_MAP_SWIZZLE_32B, CU_TENSOR_MAP_L2_PROMOTION_L2_128B, CU_TENSOR_MAP_FLOAT_OOB_FILL_NONE);
}

}

extern "C" void kernel_launch(void* const* d_in, const int* in_sizes, int n_in, void* d_out, int out_size) {
    static EncodeFn enc = nullptr;
    static void *oa = nullptr, *ob = nullptr;
    static int sms = 0;
    if (!enc) {
        void* fn = nullptr;
        cudaDriverEntryPointQueryResult qr;
        cudaGetDriverEntryPoint("cuTensorMapEncodeTiled", &fn, cudaEnableDefault, &qr);
        enc = (EncodeFn)fn;
        int dev = 0;
        cudaGetDevice(&dev);
        cudaDeviceGetAttribute(&sms, cudaDevAttrMultiProcessorCount, dev);
        cudaGetSymbolAddress(&oa, g_oa);
        cudaGetSymbolAddress(&ob, g_ob);
        cudaFuncSetAttribute(fused_kernel, cudaFuncAttributeMaxDynamicSharedMemorySize, SMEM_BYTES);
    }
    Params P;
    make_map(enc, &P.xa, d_in[0], 64, 64);
    make_x16map(enc, &P.xa16, d_in[0]);
    make_map(enc, &P.wq64, d_in[1], 64, 64, 640);
    make_map(enc, &P.wq16, d_in[1], 16, 64, 640);
    make_map(enc, &P.xb, d_in[5], 64, 128);
    make_wmap(enc, &P.wqkv, d_in[6], 1920);
    make_wmap(enc, &P.woa, d_in[4], 640);
    make_wmap(enc, &P.wob, d_in[7], 640);
    make_map(enc, &P.oa, oa, 64, 64);
    make_map(enc, &P.ob, ob, 64, 128);
    make_map(enc, &P.oa_st, oa, 80, 64);
    make_map(enc, &P.ob_st, ob, 80, 128);
    for (int k = 0; k < 8; k++) P.in[k] = (const uint8_t*)d_in[k];
    P.out = (__nv_bfloat16*)d_out;
    P.helpers = sms >= NCTA + 4;
    fused_kernel<<<P.helpers ? NCTA + 4 : NCTA, NTHR, SMEM_BYTES, cudaStreamPerThread>>>(P);
}
```

```cpp
#include <cuda_runtime.h>
#include <cuda_bf16.h>
#include <cuda.h>
#include <stdint.h>

namespace {

constexpr int NCTA = 128;
constexpr int NTHR = 768;

constexpr uint32_t OFF_STAGE = 0;
constexpr uint32_t STAGE_BYTES = 26624;
constexpr uint32_t OFF_PK = 79872;
constexpr uint32_t OFF_V = 100352;
constexpr uint32_t OFF_KVB = OFF_V;
constexpr uint32_t OFF_PST = OFF_V + 14336;
constexpr uint32_t OFF_WA = 0;
constexpr uint32_t OFF_XA = 102400;
constexpr uint32_t OFF_RING = 135168;
constexpr uint32_t RING_BYTES = 24576;
constexpr uint32_t OFF_WRAW = OFF_RING;
constexpr uint32_t OFF_KVP = OFF_RING + 51200;
constexpr uint32_t OFF_Q = 208896;
constexpr uint32_t OFF_X16 = OFF_Q;
constexpr uint32_t OFF_MISC = 229376;
constexpr uint32_t OFF_BAR = OFF_MISC;
constexpr uint32_t BAR_FULL_G = OFF_BAR, BAR_EMPTY_G = OFF_BAR + 24, BAR_FULL_KV = OFF_BAR + 48, BAR_EMPTY_KV = OFF_BAR + 72;
constexpr uint32_t BAR_OA = OFF_BAR + 96, BAR_WA = OFF_BAR + 112, BAR_FULL_X = OFF_BAR + 120, BAR_EMPTY_X = OFF_BAR + 152, BAR_A0 = OFF_BAR + 184;
constexpr uint32_t OFF_QUEUE = OFF_BAR + 192;
constexpr uint32_t BAR_PART = OFF_BAR + 264, BAR_KVB = OFF_BAR + 272, BAR_OB = OFF_BAR + 280, BAR_KVIN = OFF_BAR + 288;
constexpr uint32_t OFF_PUB = OFF_BAR + 296;
constexpr uint32_t OFF_STAT = OFF_BAR + 304;
constexpr uint32_t BAR_Q = OFF_BAR + 336, BAR_C0 = OFF_BAR + 352, BAR_WQ = OFF_BAR + 360;
constexpr uint32_t OFF_KST = OFF_MISC + 384;
constexpr uint32_t OFF_TS = OFF_KST + 256;
constexpr uint32_t SMEM_BYTES = OFF_TS + 256;

#define MUFU_MASK 0x52

constexpr float LOG2E = 1.4426950408889634f;
constexpr float QSCALE = 0.22360679774997896f * LOG2E;

struct Params {
    CUtensorMap xa, xa16, wq64, wq16, xb, wqkv, woa, wob, oa, ob, oa_st, ob_st;
    const uint8_t* in[8];
    __nv_bfloat16* out;
    int helpers;
};

}

__device__ __align__(1024) uint8_t g_kv[256 * 768];
__device__ __align__(1024) __nv_bfloat16 g_oa[2048 * 640];
__device__ __align__(1024) __nv_bfloat16 g_ob[2048 * 640];
__device__ __align__(1024) uint8_t g_ox[16 * 40 * 2048];
__device__ __align__(128) float g_part[8 * 1920];
__device__ __align__(1024) unsigned long long g_kt[16 * 384];
__device__ __align__(128) uint32_t g_stat[128];
__device__ __align__(128) uint16_t g_flag_kv[128];
__device__ __align__(128) uint16_t g_flag_b1[128];
__device__ __align__(128) uint16_t g_flag_b2[128];
__device__ __align__(128) uint16_t g_flag_a[128];
__device__ __align__(128) uint16_t g_flag_w[32];
__device__ __align__(1024) uint8_t g_wt[320 * 10240];
__device__ uint32_t g_epoch;

namespace {

__device__ __forceinline__ void wg_rs_n24_tb1_d(float (&d)[12], uint32_t a0, uint32_t a1, uint32_t a2, uint32_t a3, uint64_t db) {
    asm volatile("{\n.reg .pred p;\nsetp.ne.b32 p, 1, 0;\n"
        "wgmma.mma_async.sync.aligned.m64n24k16.f32.bf16.bf16 {%0, %1, %2, %3, %4, %5, %6, %7, %8, %9, %10, %11}, {%12, %13, %14, %15}, %16, p, 1, 1, 1;\n}\n"
        : "+f"(d[0]), "+f"(d[1]), "+f"(d[2]), "+f"(d[3]), "+f"(d[4]), "+f"(d[5]), "+f"(d[6]), "+f"(d[7]), "+f"(d[8]), "+f"(d[9]), "+f"(d[10]), "+f"(d[11])
        : "r"(a0), "r"(a1), "r"(a2), "r"(a3), "l"(db));
}
__device__ __forceinline__ void wg_rs_n64_tb0_d(float (&d)[32], uint32_t a0, uint32_t a1, uint32_t a2, uint32_t a3, uint64_t db) {
    asm volatile("{\n.reg .pred p;\nsetp.ne.b32 p, 1, 0;\n"
        "wgmma.mma_async.sync.aligned.m64n64k16.f32.bf16.bf16 {%0, %1, %2, %3, %4, %5, %6, %7, %8, %9, %10, %11, %12, %13, %14, %15, %16, %17, %18, %19, %20, %21, %22, %23, %24, %25, %26, %27, %28, %29, %30, %31}, {%32, %33, %34, %35}, %36, p, 1, 1, 0;\n}\n"
        : "+f"(d[0]), "+f"(d[1]), "+f"(d[2]), "+f"(d[3]), "+f"(d[4]), "+f"(d[5]), "+f"(d[6]), "+f"(d[7]), "+f"(d[8]), "+f"(d[9]), "+f"(d[10]), "+f"(d[11]), "+f"(d[12]), "+f"(d[13]), "+f"(d[14]), "+f"(d[15]), "+f"(d[16]), "+f"(d[17]), "+f"(d[18]), "+f"(d[19]), "+f"(d[20]), "+f"(d[21]), "+f"(d[22]), "+f"(d[23]), "+f"(d[24]), "+f"(d[25]), "+f"(d[26]), "+f"(d[27]), "+f"(d[28]), "+f"(d[29]), "+f"(d[30]), "+f"(d[31])
        : "r"(a0), "r"(a1), "r"(a2), "r"(a3), "l"(db));
}
__device__ __forceinline__ void wg_rs_n64_tb0_initd(float (&d)[32], uint32_t a0, uint32_t a1, uint32_t a2, uint32_t a3, uint64_t db) {
    asm volatile("{\n.reg .pred p;\nsetp.ne.b32 p, 0, 0;\n"
        "wgmma.mma_async.sync.aligned.m64n64k16.f32.bf16.bf16 {%0, %1, %2, %3, %4, %5, %6, %7, %8, %9, %10, %11, %12, %13, %14, %15, %16, %17, %18, %19, %20, %21, %22, %23, %24, %25, %26, %27, %28, %29, %30, %31}, {%32, %33, %34, %35}, %36, p, 1, 1, 0;\n}\n"
        : "=f"(d[0]), "=f"(d[1]), "=f"(d[2]), "=f"(d[3]), "=f"(d[4]), "=f"(d[5]), "=f"(d[6]), "=f"(d[7]), "=f"(d[8]), "=f"(d[9]), "=f"(d[10]), "=f"(d[11]), "=f"(d[12]), "=f"(d[13]), "=f"(d[14]), "=f"(d[15]), "=f"(d[16]), "=f"(d[17]), "=f"(d[18]), "=f"(d[19]), "=f"(d[20]), "=f"(d[21]), "=f"(d[22]), "=f"(d[23]), "=f"(d[24]), "=f"(d[25]), "=f"(d[26]), "=f"(d[27]), "=f"(d[28]), "=f"(d[29]), "=f"(d[30]), "=f"(d[31])
        : "r"(a0), "r"(a1), "r"(a2), "r"(a3), "l"(db));
}
__device__ __forceinline__ void wg_ss_n16_ta0_tb1_d(float (&d)[8], uint64_t da, uint64_t db) {
    asm volatile("{\n.reg .pred p;\nsetp.ne.b32 p, 1, 0;\n"
        "wgmma.mma_async.sync.aligned.m64n16k16.f32.bf16.bf16 {%0, %1, %2, %3, %4, %5, %6, %7}, %8, %9, p, 1, 1, 0, 1;\n}\n"
        : "+f"(d[0]), "+f"(d[1]), "+f"(d[2]), "+f"(d[3]), "+f"(d[4]), "+f"(d[5]), "+f"(d[6]), "+f"(d[7])
        : "l"(da), "l"(db));
}
__device__ __forceinline__ void wg_ss_n32_ta1_tb1_d(float (&d)[16], uint64_t da, uint64_t db) {
    asm volatile("{\n.reg .pred p;\nsetp.ne.b32 p, 1, 0;\n"
        "wgmma.mma_async.sync.aligned.m64n32k16.f32.bf16.bf16 {%0, %1, %2, %3, %4, %5, %6, %7, %8, %9, %10, %11, %12, %13, %14, %15}, %16, %17, p, 1, 1, 1, 1;\n}\n"
        : "+f"(d[0]), "+f"(d[1]), "+f"(d[2]), "+f"(d[3]), "+f"(d[4]), "+f"(d[5]), "+f"(d[6]), "+f"(d[7]), "+f"(d[8]), "+f"(d[9]), "+f"(d[10]), "+f"(d[11]), "+f"(d[12]), "+f"(d[13]), "+f"(d[14]), "+f"(d[15])
        : "l"(da), "l"(db));
}
__device__ __forceinline__ void wg_ss_n64_ta0_tb1_d(float (&d)[32], uint64_t da, uint64_t db) {
    asm volatile("{\n.reg .pred p;\nsetp.ne.b32 p, 1, 0;\n"
        "wgmma.mma_async.sync.aligned.m64n64k16.f32.bf16.bf16 {%0, %1, %2, %3, %4, %5, %6, %7, %8, %9, %10, %11, %12, %13, %14, %15, %16, %17, %18, %19, %20, %21, %22, %23, %24, %25, %26, %27, %28, %29, %30, %31}, %32, %33, p, 1, 1, 0, 1;\n}\n"
        : "+f"(d[0]), "+f"(d[1]), "+f"(d[2]), "+f"(d[3]), "+f"(d[4]), "+f"(d[5]), "+f"(d[6]), "+f"(d[7]), "+f"(d[8]), "+f"(d[9]), "+f"(d[10]), "+f"(d[11]), "+f"(d[12]), "+f"(d[13]), "+f"(d[14]), "+f"(d[15]), "+f"(d[16]), "+f"(d[17]), "+f"(d[18]), "+f"(d[19]), "+f"(d[20]), "+f"(d[21]), "+f"(d[22]), "+f"(d[23]), "+f"(d[24]), "+f"(d[25]), "+f"(d[26]), "+f"(d[27]), "+f"(d[28]), "+f"(d[29]), "+f"(d[30]), "+f"(d[31])
        : "l"(da), "l"(db));
}
__device__ __forceinline__ void wg_ss_n72_ta1_tb1_d(float (&d)[36], uint64_t da, uint64_t db) {
    asm volatile("{\n.reg .pred p;\nsetp.ne.b32 p, 1, 0;\n"
        "wgmma.mma_async.sync.aligned.m64n72k16.f32.bf16.bf16 {%0, %1, %2, %3, %4, %5, %6, %7, %8, %9, %10, %11, %12, %13, %14, %15, %16, %17, %18, %19, %20, %21, %22, %23, %24, %25, %26, %27, %28, %29, %30, %31, %32, %33, %34, %35}, %36, %37, p, 1, 1, 1, 1;\n}\n"
        : "+f"(d[0]), "+f"(d[1]), "+f"(d[2]), "+f"(d[3]), "+f"(d[4]), "+f"(d[5]), "+f"(d[6]), "+f"(d[7]), "+f"(d[8]), "+f"(d[9]), "+f"(d[10]), "+f"(d[11]), "+f"(d[12]), "+f"(d[13]), "+f"(d[14]), "+f"(d[15]), "+f"(d[16]), "+f"(d[17]), "+f"(d[18]), "+f"(d[19]), "+f"(d[20]), "+f"(d[21]), "+f"(d[22]), "+f"(d[23]), "+f"(d[24]), "+f"(d[25]), "+f"(d[26]), "+f"(d[27]), "+f"(d[28]), "+f"(d[29]), "+f"(d[30]), "+f"(d[31]), "+f"(d[32]), "+f"(d[33]), "+f"(d[34]), "+f"(d[35])
        : "l"(da), "l"(db));
}
__device__ __forceinline__ void wg_ss_n80_ta0_tb1_d(float (&d)[40], uint64_t da, uint64_t db) {
    asm volatile("{\n.reg .pred p;\nsetp.ne.b32 p, 1, 0;\n"
        "wgmma.mma_async.sync.aligned.m64n80k16.f32.bf16.bf16 {%0, %1, %2, %3, %4, %5, %6, %7, %8, %9, %10, %11, %12, %13, %14, %15, %16, %17, %18, %19, %20, %21, %22, %23, %24, %25, %26, %27, %28, %29, %30, %31, %32, %33, %34, %35, %36, %37, %38, %39}, %40, %41, p, 1, 1, 0, 1;\n}\n"
        : "+f"(d[0]), "+f"(d[1]), "+f"(d[2]), "+f"(d[3]), "+f"(d[4]), "+f"(d[5]), "+f"(d[6]), "+f"(d[7]), "+f"(d[8]), "+f"(d[9]), "+f"(d[10]), "+f"(d[11]), "+f"(d[12]), "+f"(d[13]), "+f"(d[14]), "+f"(d[15]), "+f"(d[16]), "+f"(d[17]), "+f"(d[18]), "+f"(d[19]), "+f"(d[20]), "+f"(d[21]), "+f"(d[22]), "+f"(d[23]), "+f"(d[24]), "+f"(d[25]), "+f"(d[26]), "+f"(d[27]), "+f"(d[28]), "+f"(d[29]), "+f"(d[30]), "+f"(d[31]), "+f"(d[32]), "+f"(d[33]), "+f"(d[34]), "+f"(d[35]), "+f"(d[36]), "+f"(d[37]), "+f"(d[38]), "+f"(d[39])
        : "l"(da), "l"(db));
}
__device__ __forceinline__ void wg_ss_n80_ta0_tb1_initd(float (&d)[40], uint64_t da, uint64_t db) {
    asm volatile("{\n.reg .pred p;\nsetp.ne.b32 p, 0, 0;\n"
        "wgmma.mma_async.sync.aligned.m64n80k16.f32.bf16.bf16 {%0, %1, %2, %3, %4, %5, %6, %7, %8, %9, %10, %11, %12, %13, %14, %15, %16, %17, %18, %19, %20, %21, %22, %23, %24, %25, %26, %27, %28, %29, %30, %31, %32, %33, %34, %35, %36, %37, %38, %39}, %40, %41, p, 1, 1, 0, 1;\n}\n"
        : "=f"(d[0]), "=f"(d[1]), "=f"(d[2]), "=f"(d[3]), "=f"(d[4]), "=f"(d[5]), "=f"(d[6]), "=f"(d[7]), "=f"(d[8]), "=f"(d[9]), "=f"(d[10]), "=f"(d[11]), "=f"(d[12]), "=f"(d[13]), "=f"(d[14]), "=f"(d[15]), "=f"(d[16]), "=f"(d[17]), "=f"(d[18]), "=f"(d[19]), "=f"(d[20]), "=f"(d[21]), "=f"(d[22]), "=f"(d[23]), "=f"(d[24]), "=f"(d[25]), "=f"(d[26]), "=f"(d[27]), "=f"(d[28]), "=f"(d[29]), "=f"(d[30]), "=f"(d[31]), "=f"(d[32]), "=f"(d[33]), "=f"(d[34]), "=f"(d[35]), "=f"(d[36]), "=f"(d[37]), "=f"(d[38]), "=f"(d[39])
        : "l"(da), "l"(db));
}
__device__ __forceinline__ void wg_ss_n88_ta0_tb1_d(float (&d)[44], uint64_t da, uint64_t db) {
    asm volatile("{\n.reg .pred p;\nsetp.ne.b32 p, 1, 0;\n"
        "wgmma.mma_async.sync.aligned.m64n88k16.f32.bf16.bf16 {%0, %1, %2, %3, %4, %5, %6, %7, %8, %9, %10, %11, %12, %13, %14, %15, %16, %17, %18, %19, %20, %21, %22, %23, %24, %25, %26, %27, %28, %29, %30, %31, %32, %33, %34, %35, %36, %37, %38, %39, %40, %41, %42, %43}, %44, %45, p, 1, 1, 0, 1;\n}\n"
        : "+f"(d[0]), "+f"(d[1]), "+f"(d[2]), "+f"(d[3]), "+f"(d[4]), "+f"(d[5]), "+f"(d[6]), "+f"(d[7]), "+f"(d[8]), "+f"(d[9]), "+f"(d[10]), "+f"(d[11]), "+f"(d[12]), "+f"(d[13]), "+f"(d[14]), "+f"(d[15]), "+f"(d[16]), "+f"(d[17]), "+f"(d[18]), "+f"(d[19]), "+f"(d[20]), "+f"(d[21]), "+f"(d[22]), "+f"(d[23]), "+f"(d[24]), "+f"(d[25]), "+f"(d[26]), "+f"(d[27]), "+f"(d[28]), "+f"(d[29]), "+f"(d[30]), "+f"(d[31]), "+f"(d[32]), "+f"(d[33]), "+f"(d[34]), "+f"(d[35]), "+f"(d[36]), "+f"(d[37]), "+f"(d[38]), "+f"(d[39]), "+f"(d[40]), "+f"(d[41]), "+f"(d[42]), "+f"(d[43])
        : "l"(da), "l"(db));
}

#define WG_FENCE() asm volatile("wgmma.fence.sync.aligned;" ::: "memory")
#define WG_COMMIT() asm volatile("wgmma.commit_group.sync.aligned;" ::: "memory")
#define WG_WAIT(n) asm volatile("wgmma.wait_group.sync.aligned %0;" :: "n"(n) : "memory")
template <int NR> __device__ __forceinline__ void fence_regs(float (&d)[NR]) {
#pragma unroll
    for (int i = 0; i < NR; i++) asm volatile("" : "+f"(d[i]) :: "memory");
}
template <int NR> __device__ __forceinline__ void zero_regs(float (&d)[NR]) {
#pragma unroll
    for (int i = 0; i < NR; i++) asm volatile("mov.b32 %0, 0;" : "=f"(d[i]) :: "memory");
}
constexpr uint32_t SW128 = 1u << 30, SW32 = 3u << 30;
__device__ __forceinline__ constexpr uint32_t dlo(uint32_t lbo) { return (lbo >> 4) << 16; }

__device__ __forceinline__ void bar_sync(int id, int n) { asm volatile("bar.sync %0, %1;" :: "r"(id), "r"(n) : "memory"); }
__device__ __forceinline__ void bar_arrive(int id, int n) { asm volatile("bar.arrive %0, %1;" :: "r"(id), "r"(n) : "memory"); }
__device__ __forceinline__ void mbar_init(uint32_t bar, uint32_t cnt) { asm volatile("mbarrier.init.shared::cta.b64 [%0], %1;" :: "r"(bar), "r"(cnt) : "memory"); }
__device__ __forceinline__ void mbar_arrive(uint32_t bar) { asm volatile("mbarrier.arrive.shared::cta.b64 _, [%0];" :: "r"(bar) : "memory"); }
__device__ __forceinline__ void mbar_expect(uint32_t bar, uint32_t bytes) { asm volatile("mbarrier.arrive.expect_tx.shared::cta.b64 _, [%0], %1;" :: "r"(bar), "r"(bytes) : "memory"); }
__device__ __forceinline__ void mbar_wait(uint32_t bar, uint32_t parity) {
    asm volatile("{\n.reg .pred p;\n.reg .u32 n;\nmov.u32 n, 0;\n"
                 "MW_LOOP:\nmbarrier.try_wait.parity.shared::cta.b64 p, [%0], %1;\n@p bra.uni MW_DONE;\n"
                 "add.u32 n, n, 1;\nsetp.lt.u32 p, n, 32768;\n@p bra.uni MW_LOOP;\nMW_DONE:\n}"
                 :: "r"(bar), "r"(parity) : "memory");
}
__device__ __forceinline__ bool mbar_test(uint32_t bar, uint32_t parity) {
    uint32_t r;
    asm volatile("{\n.reg .pred p;\nmbarrier.test_wait.parity.shared::cta.b64 p, [%1], %2;\nselp.u32 %0, 1, 0, p;\n}" : "=r"(r) : "r"(bar), "r"(parity) : "memory");
    return r;
}
__device__ __forceinline__ void count_wait(uint32_t addr, uint32_t seen, uint32_t need) {
    asm volatile("{\n.reg .pred p;\n.reg .u32 n, v;\nmov.u32 n, 0;\nmov.u32 v, %1;\n"
                 "CW_LOOP:\nsetp.ge.u32 p, v, %2;\n@p bra.uni CW_DONE;\nld.volatile.shared.u32 v, [%0];\n"
                 "add.u32 n, n, 1;\nsetp.lt.u32 p, n, 0x400000;\n@p bra.uni CW_LOOP;\nCW_DONE:\n}"
                 :: "r"(addr), "r"(seen), "r"(need) : "memory");
}
__device__ __forceinline__ uint32_t queue_wait(uint32_t addr) {
    uint32_t v;
    asm volatile("{\n.reg .pred p;\n.reg .u32 n;\nmov.u32 n, 0;\n"
                 "QW_LOOP:\nld.acquire.cta.shared::cta.u32 %0, [%1];\nsetp.ne.u32 p, %0, 0;\n@p bra.uni QW_DONE;\n"
                 "add.u32 n, n, 1;\nsetp.lt.u32 p, n, 0x400000;\n@p bra.uni QW_LOOP;\nmov.u32 %0, 1;\nQW_DONE:\n}"
                 : "=r"(v) : "r"(addr) : "memory");
    return v;
}
__device__ __forceinline__ void tma2d(uint32_t dst, const CUtensorMap* m, int x, int y, uint32_t bar) {
    asm volatile("cp.async.bulk.tensor.2d.shared::cluster.global.mbarrier::complete_tx::bytes [%0], [%1, {%2, %3}], [%4];"
                 :: "r"(dst), "l"(m), "r"(x), "r"(y), "r"(bar) : "memory");
}
__device__ __forceinline__ void bulk1d(uint32_t dst, const void* src, uint32_t bytes, uint32_t bar) {
    asm volatile("cp.async.bulk.shared::cluster.global.mbarrier::complete_tx::bytes [%0], [%1], %2, [%3];"
                 :: "r"(dst), "l"(src), "r"(bytes), "r"(bar) : "memory");
}
__device__ __forceinline__ void tma3d(uint32_t dst, const CUtensorMap* m, int y, int z, uint32_t bar) {
    asm volatile("cp.async.bulk.tensor.3d.shared::cluster.global.mbarrier::complete_tx::bytes [%0], [%1, {0, %2, %3}], [%4];"
                 :: "r"(dst), "l"(m), "r"(y), "r"(z), "r"(bar) : "memory");
}
__device__ __forceinline__ void tma2d_store(const CUtensorMap* m, int x, int y, uint32_t src) {
    asm volatile("cp.async.bulk.tensor.2d.global.shared::cta.bulk_group [%0, {%1, %2}], [%3];" :: "l"(m), "r"(x), "r"(y), "r"(src) : "memory");
}
__device__ __forceinline__ void bulk_store(void* dst, uint32_t src, uint32_t bytes) {
    asm volatile("cp.async.bulk.global.shared::cta.bulk_group [%0], [%1], %2;" :: "l"(dst), "r"(src), "r"(bytes) : "memory");
}
__device__ __forceinline__ void bulk_add_f32(void* dst, uint32_t src, uint32_t bytes) {
    asm volatile("cp.reduce.async.bulk.global.shared::cta.bulk_group.add.f32 [%0], [%1], %2;" :: "l"(dst), "r"(src), "r"(bytes) : "memory");
}
__device__ __forceinline__ void bulk_commit() { asm volatile("cp.async.bulk.commit_group;" ::: "memory"); }
__device__ __forceinline__ void bulk_wait() {
    asm volatile("cp.async.bulk.wait_group 0;\nfence.proxy.async.global;" ::: "memory");
}
__device__ __forceinline__ void prefetch_l2(const void* p, uint32_t bytes) { asm volatile("cp.async.bulk.prefetch.L2.global [%0], %1;" :: "l"(p), "r"(bytes) : "memory"); }
__device__ __forceinline__ void prefetch_map(const CUtensorMap* m) { asm volatile("prefetch.tensormap [%0];" :: "l"(m) : "memory"); }
__device__ __forceinline__ uint32_t opaque_tid() { uint32_t t; asm volatile("mov.u32 %0, %tid.x;" : "=r"(t) :: "memory"); return t; }
__device__ __forceinline__ uint32_t opaque_cta() { uint32_t t; asm volatile("mov.u32 %0, %ctaid.x;" : "=r"(t) :: "memory"); return t; }
__device__ __forceinline__ bool elect_one() {
    uint32_t p;
    asm volatile("{\n.reg .pred p;\nelect.sync _|p, 0xffffffff;\nselp.u32 %0, 1, 0, p;\n}" : "=r"(p));
    return p;
}
__device__ __forceinline__ void fence_async() { asm volatile("fence.proxy.async.global;" ::: "memory"); }
__device__ __forceinline__ void fence_async_smem() { asm volatile("fence.proxy.async.shared::cta;" ::: "memory"); }
__device__ __forceinline__ void st_flag(uint16_t* p, uint32_t v) { asm volatile("st.release.gpu.global.u16 [%0], %1;" :: "l"(p), "h"((uint16_t)v) : "memory"); }
__device__ __forceinline__ void st_relaxed(void* p, uint32_t v) { asm volatile("st.relaxed.gpu.global.u32 [%0], %1;" :: "l"(p), "r"(v) : "memory"); }
__device__ __forceinline__ void st_relaxed64(void* p, unsigned long long v) { asm volatile("st.relaxed.gpu.global.u64 [%0], %1;" :: "l"(p), "l"(v) : "memory"); }
__device__ __forceinline__ uint4 ld_relaxed2x64(const void* p) {
    uint4 v;
    asm volatile("{\n.reg .b64 a, b;\nld.relaxed.gpu.global.v2.u64 {a, b}, [%4];\nmov.b64 {%0, %1}, a;\nmov.b64 {%2, %3}, b;\n}" : "=r"(v.x), "=r"(v.y), "=r"(v.z), "=r"(v.w) : "l"(p) : "memory");
    return v;
}
__device__ __forceinline__ uint4 ld_relaxed128(const void* p) { uint4 v; asm volatile("ld.relaxed.gpu.global.v4.u32 {%0, %1, %2, %3}, [%4];" : "=r"(v.x), "=r"(v.y), "=r"(v.z), "=r"(v.w) : "l"(p) : "memory"); return v; }
__device__ __forceinline__ uint4 ld_acquire128(const void* p) { uint4 v; asm volatile("ld.acquire.gpu.global.v4.u32 {%0, %1, %2, %3}, [%4];" : "=r"(v.x), "=r"(v.y), "=r"(v.z), "=r"(v.w) : "l"(p) : "memory"); return v; }
__device__ __forceinline__ void poll1(const uint16_t* p, uint32_t tag) {
#pragma unroll 1
    for (uint32_t spin = 0; spin < (1u << 17); spin++) {
        uint16_t v;
        asm volatile("ld.acquire.gpu.global.u16 %0, [%1];" : "=h"(v) : "l"(p) : "memory");
        if (v == (uint16_t)tag) break;
    }
    fence_async();
}
__device__ __forceinline__ void poll8(const uint16_t* p, uint32_t tag) {
    const uint32_t t2 = (tag & 0xFFFFu) * 0x10001u;
#pragma unroll 1
    for (uint32_t spin = 0; spin < (1u << 17); spin++) {
        const uint4 a = ld_acquire128(p);
        if (a.x == t2 && a.y == t2 && a.z == t2 && a.w == t2) break;
    }
    fence_async();
}
__device__ __forceinline__ uint32_t lds32(uint32_t a) { uint32_t v; asm volatile("ld.shared.u32 %0, [%1];" : "=r"(v) : "r"(a) : "memory"); return v; }
__device__ __forceinline__ void sts32(uint32_t a, uint32_t v) { asm volatile("st.shared.u32 [%0], %1;" :: "r"(a), "r"(v) : "memory"); }
__device__ __forceinline__ void sts16(uint32_t a, uint16_t v) { asm volatile("st.shared.u16 [%0], %1;" :: "r"(a), "h"(v) : "memory"); }
__device__ __forceinline__ void sts64(uint32_t a, uint32_t x, uint32_t y) { asm volatile("st.shared.v2.u32 [%0], {%1, %2};" :: "r"(a), "r"(x), "r"(y) : "memory"); }
__device__ __forceinline__ void sts128(uint32_t a, uint32_t x, uint32_t y, uint32_t z, uint32_t w) { asm volatile("st.shared.v4.u32 [%0], {%1, %2, %3, %4};" :: "r"(a), "r"(x), "r"(y), "r"(z), "r"(w) : "memory"); }
__device__ __forceinline__ uint2 lds64(uint32_t a) { uint2 v; asm volatile("ld.shared.v2.u32 {%0, %1}, [%2];" : "=r"(v.x), "=r"(v.y) : "r"(a) : "memory"); return v; }
__device__ __forceinline__ uint4 lds128(uint32_t a) { uint4 v; asm volatile("ld.shared.v4.u32 {%0, %1, %2, %3}, [%4];" : "=r"(v.x), "=r"(v.y), "=r"(v.z), "=r"(v.w) : "r"(a) : "memory"); return v; }
__device__ __forceinline__ float ex2f(float x) { float y; asm("ex2.approx.ftz.f32 %0, %1;" : "=f"(y) : "f"(x)); return y; }
__device__ __forceinline__ float rcpf(float x) { float y; asm("rcp.approx.ftz.f32 %0, %1;" : "=f"(y) : "f"(x)); return y; }
__device__ __forceinline__ void stsm4(uint32_t a, uint32_t x, uint32_t y, uint32_t z, uint32_t w) {
    asm volatile("stmatrix.sync.aligned.m8n8.x4.shared.b16 [%0], {%1, %2, %3, %4};" :: "r"(a), "r"(x), "r"(y), "r"(z), "r"(w) : "memory");
}
__device__ __forceinline__ uint32_t pack_bf16(float lo, float hi) { uint32_t r; asm("cvt.rn.bf16x2.f32 %0, %1, %2;" : "=r"(r) : "f"(hi), "f"(lo)); return r; }
__device__ __forceinline__ float bf_lo(uint32_t v) { return __uint_as_float(v << 16); }
__device__ __forceinline__ float bf_hi(uint32_t v) { return __uint_as_float(v & 0xFFFF0000u); }
__device__ __forceinline__ uint32_t phi2(float t0, float t1) {
    uint32_t r;
    asm("{\n.reg .b32 one, eps, p, e;\nmov.b32 one, 0x3F803F80;\nmov.b32 eps, 0x35863586;\n"
        "add.rn.bf16x2 p, %1, one;\nmin.bf16x2 e, %2, one;\nmax.NaN.bf16x2 p, p, e;\nadd.rn.bf16x2 %0, p, eps;\n}"
        : "=r"(r) : "r"(pack_bf16(t0, t1)), "r"(pack_bf16(ex2f(t0 * LOG2E), ex2f(t1 * LOG2E))));
    return r;
}
template <int MODE> __device__ __forceinline__ void stage_tile(uint32_t x, uint32_t step, const float (&a)[40]) {
#pragma unroll
    for (int k = 0; k < 5; k++) {
        uint32_t r[4];
#pragma unroll
        for (int e = 0; e < 4; e++) {
            const float t0 = a[8 * k + 2 * e], t1 = a[8 * k + 2 * e + 1];
            r[e] = MODE == 0 ? pack_bf16(t0, t1) : MODE == 1 ? pack_bf16(t0 * QSCALE, t1 * QSCALE) : phi2(t0, t1);
        }
        stsm4(x + 2 * k * step, r[0], r[1], r[2], r[3]);
    }
}

__device__ __forceinline__ uint32_t exp2_pair(float t0, float t1, uint32_t ca) {
    uint32_t y, u, g;
    asm("prmt.b32 %0, %1, %2, 0x6521;" : "=r"(y) : "r"(__float_as_uint(t0)), "r"(__float_as_uint(t1)));
    u = y & 0x007F007Fu;
    asm("{.reg .b32 c; mov.b32 c, 0xF963F963; fma.rn.f16x2 %0, %1, c, %2;}" : "=r"(g) : "r"(u), "r"(ca));
    asm("mul.rn.f16x2 %0, %1, %2;" : "=r"(g) : "r"(g), "r"(u));
    return y - g;
}

__device__ __forceinline__ uint64_t desc(uint32_t addr, uint32_t lbo, uint32_t hi) { return ((uint64_t)hi << 32) | ((addr >> 4) + dlo(lbo)); }
template <int J> __device__ __forceinline__ void exp_steps(const float (&s)[32], uint32_t (&p)[16], float (&o)[12], uint64_t& dv, uint32_t ca) {
    if constexpr (J < 4) {
#pragma unroll
        for (int g = 2 * J; g < 2 * J + 2; g++) {
            if ((MUFU_MASK >> g) & 1) {
                p[2 * g] = pack_bf16(ex2f(s[4 * g]), ex2f(s[4 * g + 1]));
                p[2 * g + 1] = pack_bf16(ex2f(s[4 * g + 2]), ex2f(s[4 * g + 3]));
            } else {
                p[2 * g] = exp2_pair(s[4 * g], s[4 * g + 1], ca);
                p[2 * g + 1] = exp2_pair(s[4 * g + 2], s[4 * g + 3], ca);
            }
        }
        WG_FENCE();
        wg_rs_n24_tb1_d(o, p[4 * J], p[4 * J + 1], p[4 * J + 2], p[4 * J + 3], dv);
        dv += 96;
        exp_steps<J + 1>(s, p, o, dv, ca);
    }
}

struct Ring { uint32_t slot, phase; };
__device__ __forceinline__ void next_stage(Ring& r) { if (++r.slot == 3) { r.slot = 0; r.phase ^= 1; } }

template <bool FAST>
__device__ __forceinline__ void attend(uint32_t sb, uint32_t& slot, int pass, const uint32_t (&q)[6], float (&o)[12], uint32_t ca, uint32_t z0, uint32_t z1) {
    float m0 = -INFINITY, m1 = -INFINITY;
    constexpr int UNR = FAST ? 4 : 1;
#pragma unroll 1
    for (int c = 0; c < 8; c++) {
        const uint32_t base = sb + OFF_RING + slot * RING_BYTES;
        uint64_t dk = desc(base, 128, 768 >> 4), dv = desc(base + 384, 768, 128 >> 4);
        uint32_t seen;
#pragma unroll UNR
        for (int b = 0; b < 4; b++) {
            float s[32];
            uint32_t p[16];
            WG_FENCE();
            wg_rs_n64_tb0_initd(s, q[0], q[1], q[2], q[3], dk);
            dk += 16;
            wg_rs_n64_tb0_d(s, q[4], q[5], z0, z1, dk);
            dk += 368;
            WG_COMMIT();
            if (UNR < 4 || b == 3) seen = lds32(sb + OFF_PUB);
            WG_WAIT(0);
            fence_regs(s);
            if constexpr (FAST) {
                exp_steps<0>(s, p, o, dv, ca);
            } else {
                fence_regs(o);
                float x0 = m0, x1 = m1;
#pragma unroll
                for (int g = 0; g < 8; g++) {
                    if (!((MUFU_MASK >> g) & 1)) {
#pragma unroll
                        for (int e = 0; e < 4; e++) s[4 * g + e] *= 2.f;
                    }
                    x0 = fmaxf(x0, fmaxf(s[4 * g], s[4 * g + 1]));
                    x1 = fmaxf(x1, fmaxf(s[4 * g + 2], s[4 * g + 3]));
                }
                x0 = fmaxf(x0, __shfl_xor_sync(~0u, x0, 1)); x0 = fmaxf(x0, __shfl_xor_sync(~0u, x0, 2));
                x1 = fmaxf(x1, __shfl_xor_sync(~0u, x1, 1)); x1 = fmaxf(x1, __shfl_xor_sync(~0u, x1, 2));
                const float a0 = ex2f(m0 - x0), a1 = ex2f(m1 - x1);
                m0 = x0; m1 = x1;
#pragma unroll
                for (int b = 0; b < 3; b++) { o[4 * b] *= a0; o[4 * b + 1] *= a0; o[4 * b + 2] *= a1; o[4 * b + 3] *= a1; }
#pragma unroll
                for (int g = 0; g < 8; g++) {
                    p[2 * g] = pack_bf16(ex2f(s[4 * g] - x0), ex2f(s[4 * g + 1] - x0));
                    p[2 * g + 1] = pack_bf16(ex2f(s[4 * g + 2] - x1), ex2f(s[4 * g + 3] - x1));
                }
            }
            if constexpr (!FAST) {
                WG_FENCE();
#pragma unroll
                for (int k = 0; k < 4; k++) { wg_rs_n24_tb1_d(o, p[4 * k], p[4 * k + 1], p[4 * k + 2], p[4 * k + 3], dv); dv += 96; }
            }
            WG_COMMIT();
            WG_WAIT(0);
            fence_regs(o);
        }
        if ((threadIdx.x & 31) == 0) mbar_arrive(sb + BAR_EMPTY_KV + slot * 8);
        slot = slot == 2 ? 0 : slot + 1;
        count_wait(sb + OFF_PUB, seen, min(pass * 8 + c + 2, 16));
    }
}

__device__ __forceinline__ void gemm_pass(uint32_t sb, int pass, float (&a)[40], float (&b)[40]) {
    zero_regs(a); zero_regs(b);
    const uint32_t n0 = (__shfl_sync(~0u, pass, 0) - 1) * 10;
    uint32_t slot = n0 % 3, phase = (n0 / 3) & 1;
    const bool lead = (threadIdx.x & 31) == 0;
#pragma unroll 1
    for (int c = 0; c < 10; c++) {
        mbar_wait(sb + BAR_FULL_G + slot * 8, phase);
        const uint32_t st = sb + OFF_STAGE + slot * STAGE_BYTES;
        const uint64_t dx = desc(st, 16, SW128 | 64), dw = desc(st + 16384, 2048, SW32 | 16);
        WG_FENCE();
#pragma unroll
        for (int k = 0; k < 4; k++) {
            wg_ss_n80_ta0_tb1_d(a, dx + 2 * k, dw + 32 * k);
            wg_ss_n80_ta0_tb1_d(b, dx + 512 + 2 * k, dw + 32 * k);
        }
        WG_COMMIT();
        WG_WAIT(0);
        if (lead) mbar_arrive(sb + BAR_EMPTY_G + slot * 8);
        if (++slot == 3) { slot = 0; phase ^= 1; }
    }
    fence_regs(a); fence_regs(b);
}

template <bool SPLIT> __device__ __forceinline__ void gemm_half(uint32_t sb, uint32_t n0_, float (&a)[40]) {
    zero_regs(a);
    const uint32_t n0 = __shfl_sync(~0u, n0_, 0);
    const bool lead = (threadIdx.x & 31) == 0;
#pragma unroll 1
    for (uint32_t c = 0; c < 10; c++) {
        const uint32_t n = n0 + c;
        if (SPLIT && (n == 4 || n == 7)) mbar_wait(sb + BAR_WQ + (n == 4 ? 0 : 8), 0);
        mbar_wait(sb + BAR_FULL_X + (n & 3) * 8, (n >> 2) & 1);
        const uint64_t dx = desc(sb + OFF_XA + (n & 3) * 8192, 16, SW128 | 64), dw = desc(sb + OFF_WA + c * 10240 + (SPLIT ? 8192 : 0), 2048, SW32 | 16);
        const uint64_t dv = desc(sb + OFF_WA + c * 10240, 8192, SW128 | 64);
        WG_FENCE();
#pragma unroll
        for (int k = 0; k < 4; k++) {
            if constexpr (SPLIT) {
                wg_ss_n64_ta0_tb1_d(*reinterpret_cast<float(*)[32]>(&a[0]), dx + 2 * k, dv + 128 * k);
                wg_ss_n16_ta0_tb1_d(*reinterpret_cast<float(*)[8]>(&a[32]), dx + 2 * k, dw + 32 * k);
            } else {
                wg_ss_n80_ta0_tb1_d(a, dx + 2 * k, dw + 32 * k);
            }
        }
        WG_COMMIT();
        WG_WAIT(1);
        if (lead && c) mbar_arrive(sb + BAR_EMPTY_X + ((n - 1) & 3) * 8);
    }
    WG_WAIT(0);
    if (lead) mbar_arrive(sb + BAR_EMPTY_X + ((n0 + 9) & 3) * 8);
    fence_regs(a);
}

__device__ __forceinline__ void mma16816(float (&d)[4], uint32_t a0, uint32_t a1, uint32_t a2, uint32_t a3, uint32_t b0, uint32_t b1) {
    asm volatile("mma.sync.aligned.m16n8k16.row.col.f32.bf16.bf16.f32 {%0, %1, %2, %3}, {%4, %5, %6, %7}, {%8, %9}, {%0, %1, %2, %3};"
                 : "+f"(d[0]), "+f"(d[1]), "+f"(d[2]), "+f"(d[3]) : "r"(a0), "r"(a1), "r"(a2), "r"(a3), "r"(b0), "r"(b1));
}

__device__ __forceinline__ void store_tile(uint32_t stage, __nv_bfloat16* dst, int lane, const float (&a)[40]) {
    stage_tile<0>(stage + (lane & 15) * 160 + (lane >> 4) * 16, 16, a);
    __syncwarp();
#pragma unroll
    for (int u = 0; u < 5; u++) {
        const int x = lane + 32 * u, row = (x * 205) >> 11;
        const uint4 v = lds128(stage + x * 16);
        *reinterpret_cast<uint4*>(dst + row * (1280 - 80) + x * 8) = v;
    }
    __syncwarp();
}

__device__ __forceinline__ void linear_out(uint32_t sb, int half, uint32_t dst, int q) {
    float d[44]; zero_regs(d);
    const uint64_t da = desc(sb + OFF_PK + half * 10240, 128, 80), db = desc(sb + OFF_KVB, 1408, 8);
    WG_FENCE();
#pragma unroll
    for (int k = 0; k < 5; k++) wg_ss_n88_ta0_tb1_d(d, da + 16 * k, db + 176 * k);
    WG_COMMIT();
    WG_WAIT(0);
    fence_regs(d);
    bar_sync(6, 128);
    float r0[4], r1[4];
    const int base = (threadIdx.x & 31) & ~3;
#pragma unroll
    for (int e = 0; e < 4; e++) d[40 + e] = rcpf(d[40 + e] + 1e-6f);
#pragma unroll
    for (int h = 0; h < 4; h++) {
        r0[h] = __shfl_sync(~0u, d[40 + (h & 1)], base + (h >> 1));
        r1[h] = __shfl_sync(~0u, d[42 + (h & 1)], base + (h >> 1));
    }
    uint32_t r[20];
#pragma unroll
    for (int b = 0; b < 10; b++) {
        const int hl = (8 * b) / 20, hh = (8 * b + 6) / 20;
        const bool up = hl != hh && q >= 2;
        const float s0 = up ? r0[hh] : r0[hl], s1 = up ? r1[hh] : r1[hl];
        r[2 * b] = pack_bf16(d[4 * b] * s0, d[4 * b + 1] * s0);
        r[2 * b + 1] = pack_bf16(d[4 * b + 2] * s1, d[4 * b + 3] * s1);
    }
#pragma unroll
    for (int k = 0; k < 5; k++) stsm4(dst + 32 * k, r[4 * k], r[4 * k + 1], r[4 * k + 2], r[4 * k + 3]);
}

__global__ void __launch_bounds__(NTHR, 1) fused_kernel(const __grid_constant__ Params P) {
    extern __shared__ __align__(1024) uint8_t smem[];
    const uint32_t sb = (uint32_t)__cvta_generic_to_shared(smem);
    const int tid = threadIdx.x, lane = tid & 31;
    const int wg = __shfl_sync(~0u, tid >> 7, 0), warp = __shfl_sync(~0u, (tid >> 5) & 3, 0);
    const int cta = blockIdx.x, i = cta >> 3, j = cta & 7;
    const int q = lane & 3, r0 = 16 * warp + (lane >> 2);

    const uint32_t tag = *(volatile uint32_t*)&g_epoch + 1;

    if (cta >= NCTA) {
        if (tid < 64 && elect_one()) {
            const int jj = 2 * (cta - NCTA) + warp;
            const uint32_t buf = sb + warp * 102400, bar = sb + OFF_BAR + warp * 80;
#pragma unroll 1
            for (int s = 0; s < 10; s++) mbar_init(bar + s * 8, 1);
            asm volatile("fence.mbarrier_init.release.cluster;" ::: "memory");
            int lp = 0, lc = 0;
#pragma unroll 1
            for (int n = -8; n < 40; n++) {
                if (n >= 0) {
                    const int part = n / 10, c = n - 10 * part;
                    mbar_wait(bar + c * 8, part & 1);
                    bulk_store(g_wt + ((part * 8 + jj) * 10 + c) * 10240, buf + c * 10240, 10240);
                    bulk_commit();
                    if (c == 9) { bulk_wait(); st_flag(g_flag_w + part * 8 + jj, tag); }
                    else asm volatile("cp.async.bulk.wait_group.read 2;" ::: "memory");
                }
                if (lp < 4) {
                    mbar_expect(bar + lc * 8, 10240);
                    tma3d(buf + lc * 10240, lp < 2 ? &P.wqkv : lp == 2 ? &P.wob : &P.woa, 64 * lc, 5 * jj + (lp == 0 ? 80 : 0), bar + lc * 8);
                    if (++lc == 10) { lc = 0; lp++; }
                }
            }
        }
        return;
    }
    if (tid == 640) {
        mbar_init(sb + BAR_KVIN, 1);
        asm volatile("fence.mbarrier_init.release.cluster;" ::: "memory");
        mbar_expect(sb + BAR_KVIN, 51200 + 20480);
        tma3d(sb + OFF_X16, &P.xa16, 16 * cta, 0, sb + BAR_KVIN);
#pragma unroll
        for (int u = 0; u < 4; u++) {
            const int v = (u + cta) & 3;
            bulk1d(sb + OFF_WRAW + v * 12800, P.in[2 + (v >> 1)] + (v & 1) * 12800, 12800, sb + BAR_KVIN);
        }
    } else if (tid == 672) {
#pragma unroll
        for (int s = 0; s < 3; s++) {
            mbar_init(sb + BAR_FULL_G + s * 8, 2);
            mbar_init(sb + BAR_EMPTY_G + s * 8, 4);
            mbar_init(sb + BAR_FULL_KV + s * 8, 1);
            mbar_init(sb + BAR_EMPTY_KV + s * 8, 16);
        }
        mbar_init(sb + BAR_OA, 16);
        mbar_init(sb + BAR_OA + 8, 16);
        asm volatile("fence.mbarrier_init.release.cluster;" ::: "memory");
    } else if (tid == 704) {
        prefetch_map(&P.xa);
        prefetch_map(&P.wq64);
        prefetch_map(&P.wq16);
        prefetch_l2(P.in[1] + cta * 6400, 6400);
        mbar_init(sb + BAR_WA, 1);
        mbar_init(sb + BAR_PART, 4);
        mbar_init(sb + BAR_KVB, 1);
        mbar_init(sb + BAR_OB, 4);
        sts32(sb + OFF_PUB, 0);
        sts128(sb + OFF_STAT + 16, 0x357F357Fu, 0u, 0u, 0u);
        asm volatile("fence.mbarrier_init.release.cluster;" ::: "memory");
    } else if (tid == 736) {
#pragma unroll
        for (int s = 0; s < 4; s++) { mbar_init(sb + BAR_FULL_X + s * 8, 1); mbar_init(sb + BAR_EMPTY_X + s * 8, 4); }
#pragma unroll
        for (int s = 0; s < 4; s++) sts128(sb + OFF_QUEUE + s * 16, 0u, 0u, 0u, 0u);
        mbar_init(sb + BAR_A0, 1);
        mbar_init(sb + BAR_Q, 4);
        mbar_init(sb + BAR_Q + 8, 4);
        mbar_init(sb + BAR_C0, 16);
        for (int s = 0; s < 2; s++) mbar_init(sb + BAR_WQ + s * 8, 1);
        asm volatile("fence.mbarrier_init.release.cluster;" ::: "memory");
    }
    __syncthreads();

    if (wg == 5) {
        asm volatile("setmaxnreg.dec.sync.aligned.u32 32;");
        if (warp == 0) {
            if (elect_one()) {
#pragma unroll 1
                for (int n = 0; n < 20; n++) {
                    const uint32_t s = n & 3, bar = sb + BAR_FULL_X + s * 8;
                    if (n >= 4) mbar_wait(sb + BAR_EMPTY_X + s * 8, ((n >> 2) - 1) & 1);
                    mbar_expect(bar, n < 4 ? 18432 : 8192);
                    tma2d(sb + OFF_XA + s * 8192, &P.xa, n < 10 ? 64 * n : 64 * n - 640, 128 * i + (n < 10 ? 0 : 64), bar);
                    if (n < 4) {
                        tma2d(sb + OFF_WA + n * 10240, &P.wq64, 80 * j, 64 * n, bar);
                        tma2d(sb + OFF_WA + n * 10240 + 8192, &P.wq16, 80 * j + 64, 64 * n, bar);
                    }
                    if (n == 3) {
                        mbar_expect(sb + BAR_WQ, 30720);
                        mbar_expect(sb + BAR_WQ + 8, 30720);
#pragma unroll 1
                        for (int c = 4; c < 10; c++) {
                            tma2d(sb + OFF_WA + c * 10240, &P.wq64, 80 * j, 64 * c, sb + BAR_WQ + (c < 7 ? 0 : 8));
                            tma2d(sb + OFF_WA + c * 10240 + 8192, &P.wq16, 80 * j + 64, 64 * c, sb + BAR_WQ + (c < 7 ? 0 : 8));
                        }
                    }
                }
                Ring r{0, 0};
#pragma unroll 1
                for (int pass = 1; pass < 5; pass++) {
                    const CUtensorMap* m = pass <= 3 ? &P.xb : &P.ob;
                    if (pass == 4) {
                        mbar_wait(sb + BAR_OB, 0);
                        tma2d_store(&P.ob_st, 80 * j, 128 * i, sb + OFF_PK);
                        bulk_commit();
                        bulk_wait();
                        st_flag(g_flag_b2 + cta, tag);
                        poll8(g_flag_b2 + i * 8, tag);
                    }
#pragma unroll 1
                    for (int c = 0; c < 10; c++) {
                        if (pass == 3 && c == 3) {
                            mbar_wait(sb + BAR_PART, 0);
                            bulk_add_f32(g_part + j * 1920, sb + OFF_PST, 7680);
                            bulk_commit();
                        }
                        mbar_wait(sb + BAR_EMPTY_G + r.slot * 8, r.phase);
                        mbar_expect(sb + BAR_FULL_G + r.slot * 8, 16384);
                        tma2d(sb + OFF_STAGE + r.slot * STAGE_BYTES, m, 64 * c, 128 * i, sb + BAR_FULL_G + r.slot * 8);
                        next_stage(r);
                        if (pass == 3 && c == 3) {
                            bulk_wait();
                            st_flag(g_flag_b1 + j * 16 + i, tag);
                        }
                    }
                }
                {
                    poll8(g_flag_a + i * 8, tag);
                    mbar_arrive(sb + BAR_A0);
#pragma unroll 1
                    for (int c = 0; c < 10; c++) {
                        const uint32_t s = c & 3;
                        mbar_wait(sb + BAR_EMPTY_X + s * 8, (c >> 2) & 1);
                        mbar_expect(sb + BAR_FULL_X + s * 8, 8192);
                        tma2d(sb + OFF_XA + s * 8192, &P.oa, 64 * c, 128 * i, sb + BAR_FULL_X + s * 8);
                    }
                }
            }
        } else if (warp == 2) {
            if (elect_one()) {
                Ring r{0, 0};
#pragma unroll 1
                for (int pass = 1; pass < 5; pass++) {
                    const CUtensorMap* m = pass <= 3 ? &P.wqkv : &P.wob;
                    const int col = 5 * j + (pass == 1 ? 40 : pass == 2 ? 80 : 0);
                    const bool pre = pass >= 2 && P.helpers;
                    if (pre) poll1(g_flag_w + (pass - 2) * 8 + j, tag);
#pragma unroll 1
                    for (int c = 0; c < 10; c++) {
                        mbar_wait(sb + BAR_EMPTY_G + r.slot * 8, r.phase);
                        const uint32_t bar = sb + BAR_FULL_G + r.slot * 8;
                        mbar_expect(bar, 10240);
                        const uint32_t dst = sb + OFF_STAGE + r.slot * STAGE_BYTES + 16384;
                        if (pre) bulk1d(dst, g_wt + (((pass - 2) * 8 + j) * 10 + c) * 10240, 10240, bar);
                        else tma3d(dst, m, 64 * c, col, bar);
                        next_stage(r);
                    }
                }
                {
                    if (P.helpers) poll1(g_flag_w + 24 + j, tag);
#pragma unroll 1
                    for (int c = 0; c < 3; c++) { mbar_wait(sb + BAR_EMPTY_G + r.slot * 8, r.phase); next_stage(r); }
                    mbar_expect(sb + BAR_WA, 102400);
                    if (P.helpers) bulk1d(sb + OFF_WA, g_wt + (24 + j) * 102400, 102400, sb + BAR_WA);
                    else {
#pragma unroll 1
                        for (int c = 0; c < 10; c++) tma3d(sb + OFF_WA + c * 10240, &P.woa, 64 * c, 5 * j, sb + BAR_WA);
                    }
                }
            }
        } else if (warp == 3) {
            bar_sync(12, 96);
            if (elect_one()) {
                st_flag(g_flag_kv + cta, tag);
                prefetch_l2(P.in[5] + cta * 20480, 20480);
#pragma unroll 1
                for (int u = 0; u < 5; u++) prefetch_l2(P.in[6] + (cta * 5 + u) * 3840 + 1280, 1280);
            }
            __syncwarp();
            {
                if (elect_one()) {
                    poll8(g_flag_b1 + j * 16, tag);
                    poll8(g_flag_b1 + j * 16 + 8, tag);
                    mbar_expect(sb + BAR_KVB, 7680);
                    bulk1d(sb + OFF_PST, g_part + j * 1920, 7680, sb + BAR_KVB);
                }
            }
            if (elect_one()) {
                mbar_wait(sb + BAR_OA, 0);
                tma2d_store(&P.oa_st, 80 * j, 128 * i, sb + OFF_Q);
                bulk_commit();
                bulk_wait();
                st_flag(g_flag_a + cta, tag);
            }
        } else if (warp == 1) {
            uint32_t sk, spin = 0;
            bar_sync(12, 96);
            __nanosleep(800);
#pragma unroll 1
            while (true) {
                const uint4 f = ld_relaxed128(g_stat + 4 * lane);
                const uint32_t t = tag << 16;
                sk = max(max(f.x ^ t, f.y ^ t), max(f.z ^ t, f.w ^ t));
                sk = __reduce_max_sync(~0u, sk);
                if (sk < 0x10000u || ++spin > (1u << 17)) break;
            }
            if (lane == 0) {
                sts32(sb + OFF_STAT, sk << 16);
            }
            mbar_wait(sb + BAR_C0, 0);
            if (lane == 0) {
                mbar_arrive(sb + BAR_FULL_KV);
                asm volatile("st.release.cta.shared::cta.u32 [%0], %1;" :: "r"(sb + OFF_PUB), "r"(1) : "memory");
            }
            __syncwarp();
            __nanosleep(300);
            const uint32_t t2 = (tag & 0xFFFFu) * 0x10001u;
#pragma unroll 1
            for (spin = 0; spin < (1u << 17); spin++) {
                const uint4 f = ld_acquire128(g_flag_kv + 8 * (lane & 15));
                if (__all_sync(~0u, f.x == t2 && f.y == t2 && f.z == t2 && f.w == t2)) break;
            }
            if (elect_one()) {
                fence_async();
#pragma unroll 1
                for (int n = 1; n < 3; n++) {
                    mbar_expect(sb + BAR_FULL_KV + n * 8, RING_BYTES);
                    bulk1d(sb + OFF_RING + n * RING_BYTES, g_kv + n * RING_BYTES, RING_BYTES, sb + BAR_FULL_KV + n * 8);
                }
                Ring r{1, 0};
#pragma unroll 1
                for (int n = 1; n < 16; n++) {
                    if (n >= 3) {
                        mbar_wait(sb + BAR_EMPTY_KV + r.slot * 8, r.phase ^ 1);
                        mbar_expect(sb + BAR_FULL_KV + r.slot * 8, RING_BYTES);
                        bulk1d(sb + OFF_RING + r.slot * RING_BYTES, g_kv + (n & 7) * RING_BYTES, RING_BYTES, sb + BAR_FULL_KV + r.slot * 8);
                    }
                    mbar_wait(sb + BAR_FULL_KV + r.slot * 8, r.phase);
                    asm volatile("st.release.cta.shared::cta.u32 [%0], %1;" :: "r"(sb + OFF_PUB), "r"(n + 1) : "memory");
                    next_stage(r);
                }
            }
        }
    } else if (wg < 4) {
        if (tid < 30) reinterpret_cast<uint4*>(g_part + j * 1920 + i * 120)[tid] = make_uint4(0u, 0u, 0u, 0u);
        if (wg < 2) {
            const uint32_t kw = 4 * wg + warp, g = lane >> 2;
            const uint32_t w0 = sb + OFF_WRAW + (80 * kw + 4 * q) * 40;
            const uint32_t wa[3] = {w0 + g * 4, w0 + g * 4 + 25608, w0 + 32 + (g & 1) * 4 + (g & 2) * 12784};
            float d[3][2][4];
#pragma unroll
            for (int e = 0; e < 24; e++) (&d[0][0][0])[e] = 0.f;
            mbar_wait(sb + BAR_KVIN, 0);
            uint2 x[2][2];
            uint32_t u[2][12];
#pragma unroll
            for (int s = 0; s < 6; s++) {
                if (s < 5) {
                    const uint32_t st = 5 * kw + s;
                    const uint32_t xa = sb + OFF_X16 + (st >> 2) * 2048 + g * 128 + (((2 * (st & 3) + (q >> 1)) ^ g) << 4) + (q & 1) * 8;
                    x[s & 1][0] = lds64(xa); x[s & 1][1] = lds64(xa + 1024);
#pragma unroll
                    for (int e = 0; e < 12; e++) u[s & 1][e] = lds32(wa[e >> 2] + s * 640 + (e & 3) * 40);
                }
                if (s > 0) {
                    const int p = (s - 1) & 1;
#pragma unroll
                    for (int t = 0; t < 3; t++) {
                        const uint32_t a0 = __byte_perm(u[p][4 * t], u[p][4 * t + 1], 0x5410), a1 = __byte_perm(u[p][4 * t], u[p][4 * t + 1], 0x7632);
                        const uint32_t a2 = __byte_perm(u[p][4 * t + 2], u[p][4 * t + 3], 0x5410), a3 = __byte_perm(u[p][4 * t + 2], u[p][4 * t + 3], 0x7632);
                        mma16816(d[t][0], a0, a1, a2, a3, x[p][0].x, x[p][0].y);
                        mma16816(d[t][1], a0, a1, a2, a3, x[p][1].x, x[p][1].y);
                    }
                }
            }
            bar_arrive(2, 384);
#pragma unroll
            for (int t = 0; t < 3; t++) {
                const uint32_t pr = t == 0 ? g : t == 1 ? 12 + g : 8 + g;
                if (t < 2 || g < 4) {
#pragma unroll
                    for (int h = 0; h < 2; h++) {
                        const uint32_t a = sb + OFF_KVP + kw * 2560 + ((8 * h + 2 * q) * 20 + pr) * 8;
                        sts64(a, __float_as_uint(d[t][h][0]), __float_as_uint(d[t][h][2]));
                        sts64(a + 160, __float_as_uint(d[t][h][1]), __float_as_uint(d[t][h][3]));
                    }
                }
            }
        }
        bar_sync(1, 512);
        if (wg < 3) {
            const uint32_t ch = 4 * wg + warp, grp = ch >= 6, c6 = ch - 6 * grp, isv = c6 >= 3, c3 = c6 - 3 * isv;
            const uint32_t key = 8 * grp + (lane >> 2);
            const bool mu = (MUFU_MASK >> ((2 * cta + grp) & 7)) & 1;
            uint32_t word;
            if (c3 == 2 && q >= 2) {
                word = isv ? (q == 2 ? 0x00003F80u : 0u) : mu ? 0u : q == 2 ? 0x3F00433Fu : 0x00003B4Au;
            } else {
                const uint32_t a = sb + OFF_KVP + (key * 20 + 10 * isv + 4 * c3 + q) * 8;
                float s0 = 0.f, s1 = 0.f;
#pragma unroll
                for (int u = 0; u < 8; u++) { const uint2 v = lds64(a + u * 2560); s0 += __uint_as_float(v.x); s1 += __uint_as_float(v.y); }
                const float sc = (isv || mu) ? 1.f : 0.5f;
                word = pack_bf16(s0 * sc, s1 * sc);
            }
            if (cta < 16) st_relaxed64(g_kt + cta * 384 + tid, ((unsigned long long)tag << 32) | word);
            reinterpret_cast<uint32_t*>(g_kv + cta * 1536)[tid] = word;
            if (c3 == 2 && q >= 2) word = 0;
            if (isv) {
                const uint32_t mx = __reduce_max_sync(~0u, max(word & 0x7FFFu, (word >> 16) & 0x7FFFu));
                if (lane == 0) sts32(sb + OFF_KST + 192 + (3 * grp + c3) * 4, mx);
            } else {
                float n2 = fmaf(bf_lo(word), bf_lo(word), bf_hi(word) * bf_hi(word));
                n2 += __shfl_xor_sync(~0u, n2, 1);
                n2 += __shfl_xor_sync(~0u, n2, 2);
                if (q == 0) sts32(sb + OFF_KST + (c3 * 16 + key) * 4, __float_as_uint(mu ? n2 : 4.f * n2));
            }
            if (wg | warp) bar_arrive(3, 384);
            else {
                bar_sync(3, 384);
                const uint32_t a = sb + OFF_KST + (lane & 15) * 4;
                const float n2 = __uint_as_float(lds32(a)) + __uint_as_float(lds32(a + 64)) + __uint_as_float(lds32(a + 128));
                const uint32_t sk = __reduce_max_sync(~0u, min(((__float_as_uint(n2) & 0x7FFFFFFFu) + 0xFFFFu) >> 16, 0x7FFFu));
                const uint32_t sv = __reduce_max_sync(~0u, lds32(sb + OFF_KST + 192 + min(lane, 5) * 4));
                if (lane == 0) {
                    const bool vok = sv == 0 || (sv >= ((127 - 40) << 7) && sv <= ((127 + 40) << 7));
                    st_relaxed(g_stat + cta, (tag << 16) | (vok ? sk : 0x7FFFu));
                }
                __syncwarp();
                bar_arrive(12, 96);
            }
        }
        {
            const unsigned long long* src = g_kt + tid * 2;
            uint4 v[6];
#pragma unroll
            for (int u = 0; u < 6; u++) v[u] = make_uint4(0u, ~tag, 0u, 0u);
            __nanosleep(400);
#pragma unroll 1
            for (uint32_t spin = 0; spin < (1u << 16); spin++) {
#pragma unroll
                for (int u = 0; u < 6; u++) if (v[u].y != tag) v[u] = ld_relaxed2x64(src + u * 1024);
                bool ok = true;
#pragma unroll
                for (int u = 0; u < 6; u++) { if (v[u].w != tag) v[u].y = ~tag; ok = ok && v[u].y == tag; }
                if (__all_sync(~0u, ok)) break;
            }
#pragma unroll
            for (int u = 0; u < 6; u++) sts64(sb + OFF_RING + tid * 8 + u * 4096, v[u].x, v[u].z);
            fence_async_smem();
            __syncwarp();
            if (lane == 0) mbar_arrive(sb + BAR_C0);
        }
        uint32_t slot = 0;
        const uint4 cz = lds128(sb + OFF_STAT + 16);
#pragma unroll 1
        for (int pass = 0; pass < 2; pass++) {
            uint32_t qf[6];
            mbar_wait(sb + BAR_Q + pass * 8, 0);
            const uint32_t qa = sb + OFF_Q + pass * 10240 + r0 * 160 + wg * 40 + q * 4;
            qf[0] = lds32(qa); qf[1] = lds32(qa + 8 * 160);
            qf[2] = lds32(qa + 16); qf[3] = lds32(qa + 8 * 160 + 16);
            qf[4] = q < 2 ? lds32(qa + 32) : 0u; qf[5] = q < 2 ? lds32(qa + 8 * 160 + 32) : 0u;
            if (pass == 0) { count_wait(sb + OFF_PUB, 0, 1); }
            float n0 = 0.f, n1 = 0.f;
#pragma unroll
            for (int e = 0; e < 3; e++) {
                n0 = fmaf(bf_lo(qf[2 * e]), bf_lo(qf[2 * e]), fmaf(bf_hi(qf[2 * e]), bf_hi(qf[2 * e]), n0));
                n1 = fmaf(bf_lo(qf[2 * e + 1]), bf_lo(qf[2 * e + 1]), fmaf(bf_hi(qf[2 * e + 1]), bf_hi(qf[2 * e + 1]), n1));
            }
            n0 += __shfl_xor_sync(~0u, n0, 1); n0 += __shfl_xor_sync(~0u, n0, 2);
            n1 += __shfl_xor_sync(~0u, n1, 1); n1 += __shfl_xor_sync(~0u, n1, 2);
            const float k2 = __uint_as_float(lds32(sb + OFF_STAT));
            const uint32_t bad = !(n0 * k2 <= 4000.f && n1 * k2 <= 4000.f);
            uint32_t anybad;
            asm volatile("{\n.reg .pred p, r;\nsetp.ne.u32 p, %1, 0;\nbar.red.or.pred r, %2, 128, p;\nselp.u32 %0, 1, 0, r;\n}" : "=r"(anybad) : "r"(bad), "r"(8 + wg) : "memory");
            float o[12];
#pragma unroll
            for (int k = 0; k < 12; k++) o[k] = 0.f;
            fence_regs(o);
            if (!__shfl_sync(~0u, anybad, 0)) {
                if (q >= 2) qf[4] = qf[5] = q == 2 ? 0x3F803F80u : 0x00003F80u;
                attend<true>(sb, slot, pass, qf, o, cz.x, cz.y, cz.z);
            } else {
                attend<false>(sb, slot, pass, qf, o, cz.x, cz.y, cz.z);
            }
            const float i0 = rcpf(__shfl_sync(~0u, o[8], (lane & ~3) | 2)), i1 = rcpf(__shfl_sync(~0u, o[10], (lane & ~3) | 2));
            const uint32_t ot = opaque_tid(), ol = ot & 31, oq = ot & 3;
            uint8_t* const gx = g_ox + opaque_cta() * 10240;
#pragma unroll
            for (int b = 0; b < 3; b++) {
                if (b < 2 || oq < 2) {
                    const uint32_t v0 = pack_bf16(o[4 * b] * i0, o[4 * b + 1] * i0), v1 = pack_bf16(o[4 * b + 2] * i1, o[4 * b + 3] * i1);
                    const uint32_t col = 20 * (ot >> 7) + 8 * b + 2 * oq;
                    const uint32_t x = (col >> 4) * 2048 + (ot & 96) * 16 + (col & 8) * 16 + (ol >> 2) * 16 + (col & 7) * 2;
                    st_relaxed(gx + x, pass ? v0 : ~0u);
                    st_relaxed(gx + x + 256, pass ? v1 : ~0u);
                    const uint32_t dst = sb + OFF_Q + (pass ? 10240 + x : (((ot & 96) >> 1) + (ol >> 2)) * 160 + col * 2);
                    sts32(dst, v0);
                    sts32(dst + (pass ? 256 : 8 * 160), v1);
                }
            }
            fence_async_smem();
            __syncwarp();
            if (lane == 0) mbar_arrive(sb + BAR_OA + pass * 8);
        }
        {
            const uint32_t ot = opaque_tid(), oc = opaque_cta();
            const int lane = ot & 31, i = oc >> 3, j = oc & 7;
            if (wg != 0) {
                const int u = 4 * (3 - wg) + warp;
                uint4 v[12];
                const uint8_t* src[3];
                uint32_t entry = u + 1;
#pragma unroll
                for (int t = 0; t < 3; t++) {
                    const int s = min(3 * u + t, 34), h = (s * 37) >> 8;
                    const int g = 5 * ((j + 1 + s - 7 * h) & 7) + 4 - h;
                    src[t] = g_ox + (i * 40 + g) * 2048 + lane * 16;
                    entry |= g << (8 * t + 8);
                }
#pragma unroll
                for (int k = 0; k < 12; k++) v[k] = make_uint4(k >= 8 && u == 11 ? 0u : ~0u, 0u, 0u, 0u);
                const uint8_t* const probe = (lane < 8 ? src[0] : lane < 16 ? src[1] : src[2]) - lane * 16 + (lane & 6) * 256 + (lane & 1) * 128 + 368;
                uint32_t wait = u == 11 ? 0xFFFFu : 0xFFFFFFu;
                mbar_wait(sb + BAR_A0, 0);
#pragma unroll 1
                for (uint32_t spin = 0; spin < (1u << 16); spin++) {
                    uint4 p = make_uint4(0u, 0u, 0u, 0u);
                    if (mbar_test(sb + BAR_OA + 8, 0)) wait = 0;
                    if ((wait >> lane) & 1) p = ld_relaxed128(probe);
#pragma unroll
                    for (int k = 0; k < 12; k++) if (!((wait >> (2 * (k & 12))) & 0xFF) && v[k].x == ~0u) v[k] = ld_relaxed128(src[k >> 2] + (k & 3) * 512);
                    wait = __ballot_sync(~0u, p.x == ~0u || p.w == ~0u);
                    bool ok = true;
#pragma unroll
                    for (int k = 0; k < 12; k++) {
                        if (v[k].y == ~0u || v[k].z == ~0u || v[k].w == ~0u) v[k].x = ~0u;
                        ok = ok && v[k].x != ~0u;
                    }
                    if (__all_sync(~0u, ok)) break;
                }
                mbar_wait(sb + BAR_OA + 8, 0);
#pragma unroll
                for (int k = 0; k < 12; k++) sts128(sb + OFF_RING + u * 6144 + k * 512 + lane * 16, v[k].x, v[k].y, v[k].z, v[k].w);
                fence_async_smem();
                __syncwarp();
                if (lane == 0) {
                    uint32_t n;
                    asm volatile("atom.relaxed.cta.shared::cta.add.u32 %0, [%1], 1;" : "=r"(n) : "r"(sb + OFF_QUEUE + 48) : "memory");
                    asm volatile("st.release.cta.shared::cta.u32 [%0], %1;" :: "r"(sb + OFF_QUEUE + n * 4), "r"(entry) : "memory");
                }
            } else {
                float a[40];
                mbar_wait(sb + BAR_WA, 0);
                mbar_wait(sb + BAR_OA + 8, 0);
                const uint64_t dw = desc(sb + OFF_WA, 2048, SW32 | 16);
                {
                    const uint64_t da = desc(sb + OFF_Q + 10240, 128, 16);
                    WG_FENCE();
#pragma unroll
                    for (int t = 0; t < 5; t++) {
                        const uint32_t g = 5 * j + t;
                        if (t == 0) wg_ss_n80_ta0_tb1_initd(a, da, dw + (g >> 2) * 640 + (g & 3) * 32);
                        else wg_ss_n80_ta0_tb1_d(a, da + 128 * t, dw + (g >> 2) * 640 + (g & 3) * 32);
                    }
                    WG_COMMIT();
                }
#pragma unroll 1
                for (int n = 0; n < 12; n++) {
                    const uint32_t e = __shfl_sync(~0u, queue_wait(sb + OFF_QUEUE + n * 4), 0);
                    const uint64_t da = desc(sb + OFF_RING - 6144 + (e & 15) * 6144, 128, 16);
                    WG_FENCE();
#pragma unroll
                    for (int t = 0; t < 3; t++) {
                        const uint32_t g = (e >> (8 * t + 8)) & 63;
                        wg_ss_n80_ta0_tb1_d(a, da + 128 * t, dw + (g >> 2) * 640 + (g & 3) * 32);
                    }
                    WG_COMMIT();
                }
                WG_WAIT(0);
                fence_regs(a);
                bar_sync(8, 128);
                store_tile(sb + OFF_Q + 10240 + warp * 2560, P.out + (128 * i + 64 + 16 * warp) * 1280 + 80 * j, lane, a);
            }
        }
    } else {
        asm volatile("setmaxnreg.inc.sync.aligned.u32 128;");
        const uint32_t mrow = 16 * warp + (lane & 15), mcol = lane >> 4;
        const uint32_t xrow = mrow * 160 + mcol * 16, xgrp = (mrow & 7) * 16 + mcol * 128;
        bar_sync(2, 384);
#pragma unroll 1
        for (int half = 0; half < 2; half++) {
            float a[40];
            gemm_half<true>(sb, 10 * half, a);
            if (half && lane == 0) { mbar_arrive(sb + BAR_EMPTY_G); mbar_arrive(sb + BAR_EMPTY_G + 8); mbar_arrive(sb + BAR_EMPTY_G + 16); }
            stage_tile<1>(sb + OFF_Q + half * 10240 + xrow, 16, a);
            __syncwarp();
            if (lane == 0) mbar_arrive(sb + BAR_Q + half * 8);
        }
#pragma unroll 1
        for (int pass = 1; pass < 5; pass++) {
        if (pass == 4) {
        mbar_wait(sb + BAR_KVB, 0);
        if (tid < 592) {
            const int m = tid - 512, h = m / 20;
            const uint32_t x0 = sb + OFF_KVB + (m >> 3) * 1408 + (m & 7) * 16;
#pragma unroll
            for (int e = 0; e < 5; e++) {
                const uint4 v = lds128(sb + OFF_PST + m * 96 + e * 16);
                const int n = 20 * h + 4 * e;
                sts64(x0 + (n >> 3) * 128 + (n & 4) * 2, pack_bf16(__uint_as_float(v.x), __uint_as_float(v.y)), pack_bf16(__uint_as_float(v.z), __uint_as_float(v.w)));
            }
            sts16(x0 + 1280 + h * 2, (uint16_t)pack_bf16(__uint_as_float(lds32(sb + OFF_PST + m * 96 + 80)), 0.f));
        }
        fence_async_smem();
        bar_sync(6, 128);
#pragma unroll 1
        for (int half = 0; half < 2; half++) linear_out(sb, half, sb + OFF_PK + half * 10240 + xrow, q);
        fence_async_smem();
        __syncwarp();
        if (lane == 0) mbar_arrive(sb + BAR_OB);
        }
        float a[40], b[40];
        gemm_pass(sb, pass, a, b);
        if (pass == 1 || pass == 3) {
        stage_tile<2>(sb + OFF_PK + (mrow >> 3) * 1280 + xgrp, 128, a);
        stage_tile<2>(sb + OFF_PK + (8 + (mrow >> 3)) * 1280 + xgrp, 128, b);
        } else if (pass == 2) {
        stage_tile<0>(sb + OFF_V + 128 + (mrow >> 3) * 1536 + xgrp, 128, a);
        stage_tile<0>(sb + OFF_V + 128 + (8 + (mrow >> 3)) * 1536 + xgrp, 128, b);
        {
            const uint32_t x = sb + OFF_V + ((tid - 512) >> 3) * 1536 + (tid & 7) * 16;
            sts128(x, 0x3F80u, 0u, 0u, 0u);
            sts128(x + 11 * 128, 0x3F80u, 0u, 0u, 0u);
        }
        fence_async_smem();
        bar_sync(6, 128);
        {
            float d1[36], d2[16]; zero_regs(d1); zero_regs(d2);
            const uint64_t da = desc(sb + OFF_PK, 1280, 8), db = desc(sb + OFF_V, 1536, 8);
            WG_FENCE();
#pragma unroll
            for (int k = 0; k < 8; k++) {
                wg_ss_n72_ta1_tb1_d(d1, da + 160 * k, db + 192 * k);
                wg_ss_n32_ta1_tb1_d(d2, da + 16 + 160 * k, db + 64 + 192 * k);
            }
            WG_COMMIT();
            WG_WAIT(0);
            fence_regs(d1); fence_regs(d2);
            bar_sync(6, 128);
#pragma unroll
            for (int u = 0; u < 7; u++) if (u < 6 || tid < 624) sts128(sb + OFF_KVB + (tid - 512 + 128 * u) * 16, 0u, 0u, 0u, 0u);
            const uint32_t part = sb + OFF_PST;
#pragma unroll
            for (int hh = 0; hh < 2; hh++) {
                const int m = r0 + 8 * hh;
                if (m < 60) {
                    const int h20 = (m / 20) * 20;
                    if (q == 0) sts128(part + m * 96 + 80, __float_as_uint(d1[2 * hh]), 0u, 0u, 0u);
#pragma unroll
                    for (int k = 1; k < 9; k++) {
                        const int e = 8 * (k - 1) + 2 * q - h20;
                        if (e >= 0 && e < 20) sts64(part + m * 96 + e * 4, __float_as_uint(d1[4 * k + 2 * hh]), __float_as_uint(d1[4 * k + 2 * hh + 1]));
                    }
                }
                if (m >= 44) {
                    if (q == 0) sts128(part + (m + 16) * 96 + 80, __float_as_uint(d2[12 + 2 * hh]), 0u, 0u, 0u);
#pragma unroll
                    for (int k = 0; k < 3; k++) {
                        const int e = 8 * k + 2 * q - 4;
                        if (e >= 0) sts64(part + (m + 16) * 96 + e * 4, __float_as_uint(d2[4 * k + 2 * hh]), __float_as_uint(d2[4 * k + 2 * hh + 1]));
                    }
                }
            }
            fence_async_smem();
            __syncwarp();
            if (lane == 0) mbar_arrive(sb + BAR_PART);
        }
        } else {
        __nv_bfloat16* out = P.out + (128 * i + 16 * warp) * 1280 + 80 * j + 640;
        mbar_wait(sb + BAR_A0, 0);
        store_tile(sb + OFF_Q + warp * 2560, out, lane, a);
        store_tile(sb + OFF_Q + warp * 2560, out + 64 * 1280, lane, b);
        }
        }
        {
            mbar_wait(sb + BAR_WA, 0);
            float a[40];
            gemm_half<false>(sb, 20, a);
            store_tile(sb + OFF_Q + warp * 2560, P.out + (128 * i + 16 * warp) * 1280 + 80 * j, lane, a);
        }
        if (cta == 0 && tid == 512) *(volatile uint32_t*)&g_epoch = tag;
    }
}

typedef CUresult (*EncodeFn)(CUtensorMap*, CUtensorMapDataType, cuuint32_t, void*, const cuuint64_t*, const cuuint64_t*,
                             const cuuint32_t*, const cuuint32_t*, CUtensorMapInterleave, CUtensorMapSwizzle,
                             CUtensorMapL2promotion, CUtensorMapFloatOOBfill);

void make_map(EncodeFn enc, CUtensorMap* m, const void* p, uint32_t box_cols, uint32_t box_rows, uint64_t rows = 2048) {
    cuuint64_t dims[2] = {640, rows}, strides[1] = {1280};
    cuuint32_t box[2] = {box_cols, box_rows}, es[2] = {1, 1};
    enc(m, CU_TENSOR_MAP_DATA_TYPE_BFLOAT16, 2, const_cast<void*>(p), dims, strides, box, es, CU_TENSOR_MAP_INTERLEAVE_NONE,
        box_cols == 64 ? CU_TENSOR_MAP_SWIZZLE_128B : box_cols == 16 ? CU_TENSOR_MAP_SWIZZLE_32B : CU_TENSOR_MAP_SWIZZLE_NONE, CU_TENSOR_MAP_L2_PROMOTION_L2_128B, CU_TENSOR_MAP_FLOAT_OOB_FILL_NONE);
}
void make_x16map(EncodeFn enc, CUtensorMap* m, const void* p) {
    cuuint64_t dims[3] = {64, 2048, 10}, strides[2] = {1280, 128};
    cuuint32_t box[3] = {64, 16, 10}, es[3] = {1, 1, 1};
    enc(m, CU_TENSOR_MAP_DATA_TYPE_BFLOAT16, 3, const_cast<void*>(p), dims, strides, box, es, CU_TENSOR_MAP_INTERLEAVE_NONE,
        CU_TENSOR_MAP_SWIZZLE_128B, CU_TENSOR_MAP_L2_PROMOTION_L2_128B, CU_TENSOR_MAP_FLOAT_OOB_FILL_NONE);
}
void make_wmap(EncodeFn enc, CUtensorMap* m, const void* p, uint64_t cols) {
    cuuint64_t dims[3] = {16, 640, cols / 16}, strides[2] = {cols * 2, 32};
    cuuint32_t box[3] = {16, 64, 5}, es[3] = {1, 1, 1};
    enc(m, CU_TENSOR_MAP_DATA_TYPE_BFLOAT16, 3, const_cast<void*>(p), dims, strides, box, es, CU_TENSOR_MAP_INTERLEAVE_NONE,
        CU_TENSOR_MAP_SWIZZLE_32B, CU_TENSOR_MAP_L2_PROMOTION_L2_128B, CU_TENSOR_MAP_FLOAT_OOB_FILL_NONE);
}

}

extern "C" void kernel_launch(void* const* d_in, const int* in_sizes, int n_in, void* d_out, int out_size) {
    static EncodeFn enc = nullptr;
    static void *oa = nullptr, *ob = nullptr;
    static int sms = 0;
    if (!enc) {
        void* fn = nullptr;
        cudaDriverEntryPointQueryResult qr;
        cudaGetDriverEntryPoint("cuTensorMapEncodeTiled", &fn, cudaEnableDefault, &qr);
        enc = (EncodeFn)fn;
        int dev = 0;
        cudaGetDevice(&dev);
        cudaDeviceGetAttribute(&sms, cudaDevAttrMultiProcessorCount, dev);
        cudaGetSymbolAddress(&oa, g_oa);
        cudaGetSymbolAddress(&ob, g_ob);
        cudaFuncSetAttribute(fused_kernel, cudaFuncAttributeMaxDynamicSharedMemorySize, SMEM_BYTES);
    }
    Params P;
    make_map(enc, &P.xa, d_in[0], 64, 64);
    make_x16map(enc, &P.xa16, d_in[0]);
    make_map(enc, &P.wq64, d_in[1], 64, 64, 640);
    make_map(enc, &P.wq16, d_in[1], 16, 64, 640);
    make_map(enc, &P.xb, d_in[5], 64, 128);
    make_wmap(enc, &P.wqkv, d_in[6], 1920);
    make_wmap(enc, &P.woa, d_in[4], 640);
    make_wmap(enc, &P.wob, d_in[7], 640);
    make_map(enc, &P.oa, oa, 64, 64);
    make_map(enc, &P.ob, ob, 64, 128);
    make_map(enc, &P.oa_st, oa, 80, 64);
    make_map(enc, &P.ob_st, ob, 80, 128);
    for (int k = 0; k < 8; k++) P.in[k] = (const uint8_t*)d_in[k];
    P.out = (__nv_bfloat16*)d_out;
    P.helpers = sms >= NCTA + 4;
    fused_kernel<<<P.helpers ? NCTA + 4 : NCTA, NTHR, SMEM_BYTES, cudaStreamPerThread>>>(P);
}
```

```cpp
#include <cuda_runtime.h>
#include <cuda_bf16.h>
#include <cuda.h>
#include <stdint.h>

namespace {

constexpr int NCTA = 128;
constexpr int NTHR = 768;

constexpr uint32_t OFF_STAGE = 0;
constexpr uint32_t STAGE_BYTES = 26624;
constexpr uint32_t OFF_PK = 79872;
constexpr uint32_t OFF_V = 100352;
constexpr uint32_t OFF_KVB = OFF_V;
constexpr uint32_t OFF_PST = OFF_V + 14336;
constexpr uint32_t OFF_WA = 0;
constexpr uint32_t OFF_XA = 102400;
constexpr uint32_t OFF_RING = 135168;
constexpr uint32_t RING_BYTES = 24576;
constexpr uint32_t OFF_WRAW = OFF_RING;
constexpr uint32_t OFF_KVP = OFF_RING + 51200;
constexpr uint32_t OFF_Q = 208896;
constexpr uint32_t OFF_X16 = OFF_Q;
constexpr uint32_t OFF_MISC = 229376;
constexpr uint32_t OFF_BAR = OFF_MISC;
constexpr uint32_t BAR_FULL_G = OFF_BAR, BAR_EMPTY_G = OFF_BAR + 24, BAR_FULL_KV = OFF_BAR + 48, BAR_EMPTY_KV = OFF_BAR + 72;
constexpr uint32_t BAR_OA = OFF_BAR + 96, BAR_WA = OFF_BAR + 112, BAR_FULL_X = OFF_BAR + 120, BAR_EMPTY_X = OFF_BAR + 152, BAR_A0 = OFF_BAR + 184;
constexpr uint32_t OFF_QUEUE = OFF_BAR + 192;
constexpr uint32_t BAR_PART = OFF_BAR + 264, BAR_KVB = OFF_BAR + 272, BAR_OB = OFF_BAR + 280, BAR_KVIN = OFF_BAR + 288;
constexpr uint32_t OFF_PUB = OFF_BAR + 296;
constexpr uint32_t OFF_STAT = OFF_BAR + 304;
constexpr uint32_t BAR_Q = OFF_BAR + 336, BAR_C0 = OFF_BAR + 352, BAR_WQ = OFF_BAR + 360;
constexpr uint32_t OFF_KST = OFF_MISC + 384;
constexpr uint32_t OFF_TS = OFF_KST + 256;
constexpr uint32_t SMEM_BYTES = OFF_TS + 256;

#define MUFU_MASK 0x92

constexpr float LOG2E = 1.4426950408889634f;
constexpr float QSCALE = 0.22360679774997896f * LOG2E;

struct Params {
    CUtensorMap xa, xa16, wq64, wq16, xb, wqkv, woa, wob, oa, ob, oa_st, ob_st;
    const uint8_t* in[8];
    __nv_bfloat16* out;
    int helpers;
};

}

__device__ __align__(1024) uint8_t g_kv[256 * 768];
__device__ __align__(1024) __nv_bfloat16 g_oa[2048 * 640];
__device__ __align__(1024) __nv_bfloat16 g_ob[2048 * 640];
__device__ __align__(1024) uint8_t g_ox[16 * 40 * 2048];
__device__ __align__(128) float g_part[8 * 1920];
__device__ __align__(1024) unsigned long long g_kt[16 * 384];
__device__ __align__(128) uint32_t g_stat[128];
__device__ __align__(128) uint16_t g_flag_kv[128];
__device__ __align__(128) uint16_t g_flag_b1[128];
__device__ __align__(128) uint16_t g_flag_b2[128];
__device__ __align__(128) uint16_t g_flag_a[128];
__device__ __align__(128) uint16_t g_flag_w[32];
__device__ __align__(1024) uint8_t g_wt[320 * 10240];
__device__ uint32_t g_epoch;

namespace {

__device__ __forceinline__ void wg_rs_n24_tb1_d(float (&d)[12], uint32_t a0, uint32_t a1, uint32_t a2, uint32_t a3, uint64_t db) {
    asm volatile("{\n.reg .pred p;\nsetp.ne.b32 p, 1, 0;\n"
        "wgmma.mma_async.sync.aligned.m64n24k16.f32.bf16.bf16 {%0, %1, %2, %3, %4, %5, %6, %7, %8, %9, %10, %11}, {%12, %13, %14, %15}, %16, p, 1, 1, 1;\n}\n"
        : "+f"(d[0]), "+f"(d[1]), "+f"(d[2]), "+f"(d[3]), "+f"(d[4]), "+f"(d[5]), "+f"(d[6]), "+f"(d[7]), "+f"(d[8]), "+f"(d[9]), "+f"(d[10]), "+f"(d[11])
        : "r"(a0), "r"(a1), "r"(a2), "r"(a3), "l"(db));
}
__device__ __forceinline__ void wg_rs_n64_tb0_d(float (&d)[32], uint32_t a0, uint32_t a1, uint32_t a2, uint32_t a3, uint64_t db) {
    asm volatile("{\n.reg .pred p;\nsetp.ne.b32 p, 1, 0;\n"
        "wgmma.mma_async.sync.aligned.m64n64k16.f32.bf16.bf16 {%0, %1, %2, %3, %4, %5, %6, %7, %8, %9, %10, %11, %12, %13, %14, %15, %16, %17, %18, %19, %20, %21, %22, %23, %24, %25, %26, %27, %28, %29, %30, %31}, {%32, %33, %34, %35}, %36, p, 1, 1, 0;\n}\n"
        : "+f"(d[0]), "+f"(d[1]), "+f"(d[2]), "+f"(d[3]), "+f"(d[4]), "+f"(d[5]), "+f"(d[6]), "+f"(d[7]), "+f"(d[8]), "+f"(d[9]), "+f"(d[10]), "+f"(d[11]), "+f"(d[12]), "+f"(d[13]), "+f"(d[14]), "+f"(d[15]), "+f"(d[16]), "+f"(d[17]), "+f"(d[18]), "+f"(d[19]), "+f"(d[20]), "+f"(d[21]), "+f"(d[22]), "+f"(d[23]), "+f"(d[24]), "+f"(d[25]), "+f"(d[26]), "+f"(d[27]), "+f"(d[28]), "+f"(d[29]), "+f"(d[30]), "+f"(d[31])
        : "r"(a0), "r"(a1), "r"(a2), "r"(a3), "l"(db));
}
__device__ __forceinline__ void wg_rs_n64_tb0_initd(float (&d)[32], uint32_t a0, uint32_t a1, uint32_t a2, uint32_t a3, uint64_t db) {
    asm volatile("{\n.reg .pred p;\nsetp.ne.b32 p, 0, 0;\n"
        "wgmma.mma_async.sync.aligned.m64n64k16.f32.bf16.bf16 {%0, %1, %2, %3, %4, %5, %6, %7, %8, %9, %10, %11, %12, %13, %14, %15, %16, %17, %18, %19, %20, %21, %22, %23, %24, %25, %26, %27, %28, %29, %30, %31}, {%32, %33, %34, %35}, %36, p, 1, 1, 0;\n}\n"
        : "=f"(d[0]), "=f"(d[1]), "=f"(d[2]), "=f"(d[3]), "=f"(d[4]), "=f"(d[5]), "=f"(d[6]), "=f"(d[7]), "=f"(d[8]), "=f"(d[9]), "=f"(d[10]), "=f"(d[11]), "=f"(d[12]), "=f"(d[13]), "=f"(d[14]), "=f"(d[15]), "=f"(d[16]), "=f"(d[17]), "=f"(d[18]), "=f"(d[19]), "=f"(d[20]), "=f"(d[21]), "=f"(d[22]), "=f"(d[23]), "=f"(d[24]), "=f"(d[25]), "=f"(d[26]), "=f"(d[27]), "=f"(d[28]), "=f"(d[29]), "=f"(d[30]), "=f"(d[31])
        : "r"(a0), "r"(a1), "r"(a2), "r"(a3), "l"(db));
}
__device__ __forceinline__ void wg_ss_n16_ta0_tb1_d(float (&d)[8], uint64_t da, uint64_t db) {
    asm volatile("{\n.reg .pred p;\nsetp.ne.b32 p, 1, 0;\n"
        "wgmma.mma_async.sync.aligned.m64n16k16.f32.bf16.bf16 {%0, %1, %2, %3, %4, %5, %6, %7}, %8, %9, p, 1, 1, 0, 1;\n}\n"
        : "+f"(d[0]), "+f"(d[1]), "+f"(d[2]), "+f"(d[3]), "+f"(d[4]), "+f"(d[5]), "+f"(d[6]), "+f"(d[7])
        : "l"(da), "l"(db));
}
__device__ __forceinline__ void wg_ss_n32_ta1_tb1_d(float (&d)[16], uint64_t da, uint64_t db) {
    asm volatile("{\n.reg .pred p;\nsetp.ne.b32 p, 1, 0;\n"
        "wgmma.mma_async.sync.aligned.m64n32k16.f32.bf16.bf16 {%0, %1, %2, %3, %4, %5, %6, %7, %8, %9, %10, %11, %12, %13, %14, %15}, %16, %17, p, 1, 1, 1, 1;\n}\n"
        : "+f"(d[0]), "+f"(d[1]), "+f"(d[2]), "+f"(d[3]), "+f"(d[4]), "+f"(d[5]), "+f"(d[6]), "+f"(d[7]), "+f"(d[8]), "+f"(d[9]), "+f"(d[10]), "+f"(d[11]), "+f"(d[12]), "+f"(d[13]), "+f"(d[14]), "+f"(d[15])
        : "l"(da), "l"(db));
}
__device__ __forceinline__ void wg_ss_n64_ta0_tb1_d(float (&d)[32], uint64_t da, uint64_t db) {
    asm volatile("{\n.reg .pred p;\nsetp.ne.b32 p, 1, 0;\n"
        "wgmma.mma_async.sync.aligned.m64n64k16.f32.bf16.bf16 {%0, %1, %2, %3, %4, %5, %6, %7, %8, %9, %10, %11, %12, %13, %14, %15, %16, %17, %18, %19, %20, %21, %22, %23, %24, %25, %26, %27, %28, %29, %30, %31}, %32, %33, p, 1, 1, 0, 1;\n}\n"
        : "+f"(d[0]), "+f"(d[1]), "+f"(d[2]), "+f"(d[3]), "+f"(d[4]), "+f"(d[5]), "+f"(d[6]), "+f"(d[7]), "+f"(d[8]), "+f"(d[9]), "+f"(d[10]), "+f"(d[11]), "+f"(d[12]), "+f"(d[13]), "+f"(d[14]), "+f"(d[15]), "+f"(d[16]), "+f"(d[17]), "+f"(d[18]), "+f"(d[19]), "+f"(d[20]), "+f"(d[21]), "+f"(d[22]), "+f"(d[23]), "+f"(d[24]), "+f"(d[25]), "+f"(d[26]), "+f"(d[27]), "+f"(d[28]), "+f"(d[29]), "+f"(d[30]), "+f"(d[31])
        : "l"(da), "l"(db));
}
__device__ __forceinline__ void wg_ss_n72_ta1_tb1_d(float (&d)[36], uint64_t da, uint64_t db) {
    asm volatile("{\n.reg .pred p;\nsetp.ne.b32 p, 1, 0;\n"
        "wgmma.mma_async.sync.aligned.m64n72k16.f32.bf16.bf16 {%0, %1, %2, %3, %4, %5, %6, %7, %8, %9, %10, %11, %12, %13, %14, %15, %16, %17, %18, %19, %20, %21, %22, %23, %24, %25, %26, %27, %28, %29, %30, %31, %32, %33, %34, %35}, %36, %37, p, 1, 1, 1, 1;\n}\n"
        : "+f"(d[0]), "+f"(d[1]), "+f"(d[2]), "+f"(d[3]), "+f"(d[4]), "+f"(d[5]), "+f"(d[6]), "+f"(d[7]), "+f"(d[8]), "+f"(d[9]), "+f"(d[10]), "+f"(d[11]), "+f"(d[12]), "+f"(d[13]), "+f"(d[14]), "+f"(d[15]), "+f"(d[16]), "+f"(d[17]), "+f"(d[18]), "+f"(d[19]), "+f"(d[20]), "+f"(d[21]), "+f"(d[22]), "+f"(d[23]), "+f"(d[24]), "+f"(d[25]), "+f"(d[26]), "+f"(d[27]), "+f"(d[28]), "+f"(d[29]), "+f"(d[30]), "+f"(d[31]), "+f"(d[32]), "+f"(d[33]), "+f"(d[34]), "+f"(d[35])
        : "l"(da), "l"(db));
}
__device__ __forceinline__ void wg_ss_n80_ta0_tb1_d(float (&d)[40], uint64_t da, uint64_t db) {
    asm volatile("{\n.reg .pred p;\nsetp.ne.b32 p, 1, 0;\n"
        "wgmma.mma_async.sync.aligned.m64n80k16.f32.bf16.bf16 {%0, %1, %2, %3, %4, %5, %6, %7, %8, %9, %10, %11, %12, %13, %14, %15, %16, %17, %18, %19, %20, %21, %22, %23, %24, %25, %26, %27, %28, %29, %30, %31, %32, %33, %34, %35, %36, %37, %38, %39}, %40, %41, p, 1, 1, 0, 1;\n}\n"
        : "+f"(d[0]), "+f"(d[1]), "+f"(d[2]), "+f"(d[3]), "+f"(d[4]), "+f"(d[5]), "+f"(d[6]), "+f"(d[7]), "+f"(d[8]), "+f"(d[9]), "+f"(d[10]), "+f"(d[11]), "+f"(d[12]), "+f"(d[13]), "+f"(d[14]), "+f"(d[15]), "+f"(d[16]), "+f"(d[17]), "+f"(d[18]), "+f"(d[19]), "+f"(d[20]), "+f"(d[21]), "+f"(d[22]), "+f"(d[23]), "+f"(d[24]), "+f"(d[25]), "+f"(d[26]), "+f"(d[27]), "+f"(d[28]), "+f"(d[29]), "+f"(d[30]), "+f"(d[31]), "+f"(d[32]), "+f"(d[33]), "+f"(d[34]), "+f"(d[35]), "+f"(d[36]), "+f"(d[37]), "+f"(d[38]), "+f"(d[39])
        : "l"(da), "l"(db));
}
__device__ __forceinline__ void wg_ss_n80_ta0_tb1_initd(float (&d)[40], uint64_t da, uint64_t db) {
    asm volatile("{\n.reg .pred p;\nsetp.ne.b32 p, 0, 0;\n"
        "wgmma.mma_async.sync.aligned.m64n80k16.f32.bf16.bf16 {%0, %1, %2, %3, %4, %5, %6, %7, %8, %9, %10, %11, %12, %13, %14, %15, %16, %17, %18, %19, %20, %21, %22, %23, %24, %25, %26, %27, %28, %29, %30, %31, %32, %33, %34, %35, %36, %37, %38, %39}, %40, %41, p, 1, 1, 0, 1;\n}\n"
        : "=f"(d[0]), "=f"(d[1]), "=f"(d[2]), "=f"(d[3]), "=f"(d[4]), "=f"(d[5]), "=f"(d[6]), "=f"(d[7]), "=f"(d[8]), "=f"(d[9]), "=f"(d[10]), "=f"(d[11]), "=f"(d[12]), "=f"(d[13]), "=f"(d[14]), "=f"(d[15]), "=f"(d[16]), "=f"(d[17]), "=f"(d[18]), "=f"(d[19]), "=f"(d[20]), "=f"(d[21]), "=f"(d[22]), "=f"(d[23]), "=f"(d[24]), "=f"(d[25]), "=f"(d[26]), "=f"(d[27]), "=f"(d[28]), "=f"(d[29]), "=f"(d[30]), "=f"(d[31]), "=f"(d[32]), "=f"(d[33]), "=f"(d[34]), "=f"(d[35]), "=f"(d[36]), "=f"(d[37]), "=f"(d[38]), "=f"(d[39])
        : "l"(da), "l"(db));
}
__device__ __forceinline__ void wg_ss_n88_ta0_tb1_d(float (&d)[44], uint64_t da, uint64_t db) {
    asm volatile("{\n.reg .pred p;\nsetp.ne.b32 p, 1, 0;\n"
        "wgmma.mma_async.sync.aligned.m64n88k16.f32.bf16.bf16 {%0, %1, %2, %3, %4, %5, %6, %7, %8, %9, %10, %11, %12, %13, %14, %15, %16, %17, %18, %19, %20, %21, %22, %23, %24, %25, %26, %27, %28, %29, %30, %31, %32, %33, %34, %35, %36, %37, %38, %39, %40, %41, %42, %43}, %44, %45, p, 1, 1, 0, 1;\n}\n"
        : "+f"(d[0]), "+f"(d[1]), "+f"(d[2]), "+f"(d[3]), "+f"(d[4]), "+f"(d[5]), "+f"(d[6]), "+f"(d[7]), "+f"(d[8]), "+f"(d[9]), "+f"(d[10]), "+f"(d[11]), "+f"(d[12]), "+f"(d[13]), "+f"(d[14]), "+f"(d[15]), "+f"(d[16]), "+f"(d[17]), "+f"(d[18]), "+f"(d[19]), "+f"(d[20]), "+f"(d[21]), "+f"(d[22]), "+f"(d[23]), "+f"(d[24]), "+f"(d[25]), "+f"(d[26]), "+f"(d[27]), "+f"(d[28]), "+f"(d[29]), "+f"(d[30]), "+f"(d[31]), "+f"(d[32]), "+f"(d[33]), "+f"(d[34]), "+f"(d[35]), "+f"(d[36]), "+f"(d[37]), "+f"(d[38]), "+f"(d[39]), "+f"(d[40]), "+f"(d[41]), "+f"(d[42]), "+f"(d[43])
        : "l"(da), "l"(db));
}

#define WG_FENCE() asm volatile("wgmma.fence.sync.aligned;" ::: "memory")
#define WG_COMMIT() asm volatile("wgmma.commit_group.sync.aligned;" ::: "memory")
#define WG_WAIT(n) asm volatile("wgmma.wait_group.sync.aligned %0;" :: "n"(n) : "memory")
template <int NR> __device__ __forceinline__ void fence_regs(float (&d)[NR]) {
#pragma unroll
    for (int i = 0; i < NR; i++) asm volatile("" : "+f"(d[i]) :: "memory");
}
template <int NR> __device__ __forceinline__ void zero_regs(float (&d)[NR]) {
#pragma unroll
    for (int i = 0; i < NR; i++) asm volatile("mov.b32 %0, 0;" : "=f"(d[i]) :: "memory");
}
constexpr uint32_t SW128 = 1u << 30, SW32 = 3u << 30;
__device__ __forceinline__ constexpr uint32_t dlo(uint32_t lbo) { return (lbo >> 4) << 16; }

__device__ __forceinline__ void bar_sync(int id, int n) { asm volatile("bar.sync %0, %1;" :: "r"(id), "r"(n) : "memory"); }
__device__ __forceinline__ void bar_arrive(int id, int n) { asm volatile("bar.arrive %0, %1;" :: "r"(id), "r"(n) : "memory"); }
__device__ __forceinline__ void mbar_init(uint32_t bar, uint32_t cnt) { asm volatile("mbarrier.init.shared::cta.b64 [%0], %1;" :: "r"(bar), "r"(cnt) : "memory"); }
__device__ __forceinline__ void mbar_arrive(uint32_t bar) { asm volatile("mbarrier.arrive.shared::cta.b64 _, [%0];" :: "r"(bar) : "memory"); }
__device__ __forceinline__ void mbar_expect(uint32_t bar, uint32_t bytes) { asm volatile("mbarrier.arrive.expect_tx.shared::cta.b64 _, [%0], %1;" :: "r"(bar), "r"(bytes) : "memory"); }
__device__ __forceinline__ void mbar_wait(uint32_t bar, uint32_t parity) {
    asm volatile("{\n.reg .pred p;\n.reg .u32 n;\nmov.u32 n, 0;\n"
                 "MW_LOOP:\nmbarrier.try_wait.parity.shared::cta.b64 p, [%0], %1;\n@p bra.uni MW_DONE;\n"
                 "add.u32 n, n, 1;\nsetp.lt.u32 p, n, 32768;\n@p bra.uni MW_LOOP;\nMW_DONE:\n}"
                 :: "r"(bar), "r"(parity) : "memory");
}
__device__ __forceinline__ bool mbar_test(uint32_t bar, uint32_t parity) {
    uint32_t r;
    asm volatile("{\n.reg .pred p;\nmbarrier.test_wait.parity.shared::cta.b64 p, [%1], %2;\nselp.u32 %0, 1, 0, p;\n}" : "=r"(r) : "r"(bar), "r"(parity) : "memory");
    return r;
}
__device__ __forceinline__ void count_wait(uint32_t addr, uint32_t seen, uint32_t need) {
    asm volatile("{\n.reg .pred p;\n.reg .u32 n, v;\nmov.u32 n, 0;\nmov.u32 v, %1;\n"
                 "CW_LOOP:\nsetp.ge.u32 p, v, %2;\n@p bra.uni CW_DONE;\nld.volatile.shared.u32 v, [%0];\n"
                 "add.u32 n, n, 1;\nsetp.lt.u32 p, n, 0x400000;\n@p bra.uni CW_LOOP;\nCW_DONE:\n}"
                 :: "r"(addr), "r"(seen), "r"(need) : "memory");
}
__device__ __forceinline__ uint32_t queue_wait(uint32_t addr) {
    uint32_t v;
    asm volatile("{\n.reg .pred p;\n.reg .u32 n;\nmov.u32 n, 0;\n"
                 "QW_LOOP:\nld.acquire.cta.shared::cta.u32 %0, [%1];\nsetp.ne.u32 p, %0, 0;\n@p bra.uni QW_DONE;\n"
                 "add.u32 n, n, 1;\nsetp.lt.u32 p, n, 0x400000;\n@p bra.uni QW_LOOP;\nmov.u32 %0, 1;\nQW_DONE:\n}"
                 : "=r"(v) : "r"(addr) : "memory");
    return v;
}
__device__ __forceinline__ void tma2d(uint32_t dst, const CUtensorMap* m, int x, int y, uint32_t bar) {
    asm volatile("cp.async.bulk.tensor.2d.shared::cluster.global.mbarrier::complete_tx::bytes [%0], [%1, {%2, %3}], [%4];"
                 :: "r"(dst), "l"(m), "r"(x), "r"(y), "r"(bar) : "memory");
}
__device__ __forceinline__ void bulk1d(uint32_t dst, const void* src, uint32_t bytes, uint32_t bar) {
    asm volatile("cp.async.bulk.shared::cluster.global.mbarrier::complete_tx::bytes [%0], [%1], %2, [%3];"
                 :: "r"(dst), "l"(src), "r"(bytes), "r"(bar) : "memory");
}
__device__ __forceinline__ void tma3d(uint32_t dst, const CUtensorMap* m, int y, int z, uint32_t bar) {
    asm volatile("cp.async.bulk.tensor.3d.shared::cluster.global.mbarrier::complete_tx::bytes [%0], [%1, {0, %2, %3}], [%4];"
                 :: "r"(dst), "l"(m), "r"(y), "r"(z), "r"(bar) : "memory");
}
__device__ __forceinline__ void tma2d_store(const CUtensorMap* m, int x, int y, uint32_t src) {
    asm volatile("cp.async.bulk.tensor.2d.global.shared::cta.bulk_group [%0, {%1, %2}], [%3];" :: "l"(m), "r"(x), "r"(y), "r"(src) : "memory");
}
__device__ __forceinline__ void bulk_store(void* dst, uint32_t src, uint32_t bytes) {
    asm volatile("cp.async.bulk.global.shared::cta.bulk_group [%0], [%1], %2;" :: "l"(dst), "r"(src), "r"(bytes) : "memory");
}
__device__ __forceinline__ void bulk_add_f32(void* dst, uint32_t src, uint32_t bytes) {
    asm volatile("cp.reduce.async.bulk.global.shared::cta.bulk_group.add.f32 [%0], [%1], %2;" :: "l"(dst), "r"(src), "r"(bytes) : "memory");
}
__device__ __forceinline__ void bulk_commit() { asm volatile("cp.async.bulk.commit_group;" ::: "memory"); }
__device__ __forceinline__ void bulk_wait() {
    asm volatile("cp.async.bulk.wait_group 0;\nfence.proxy.async.global;" ::: "memory");
}
__device__ __forceinline__ void prefetch_l2(const void* p, uint32_t bytes) { asm volatile("cp.async.bulk.prefetch.L2.global [%0], %1;" :: "l"(p), "r"(bytes) : "memory"); }
__device__ __forceinline__ void prefetch_map(const CUtensorMap* m) { asm volatile("prefetch.tensormap [%0];" :: "l"(m) : "memory"); }
__device__ __forceinline__ uint32_t opaque_tid() { uint32_t t; asm volatile("mov.u32 %0, %tid.x;" : "=r"(t) :: "memory"); return t; }
__device__ __forceinline__ uint32_t opaque_cta() { uint32_t t; asm volatile("mov.u32 %0, %ctaid.x;" : "=r"(t) :: "memory"); return t; }
__device__ __forceinline__ bool elect_one() {
    uint32_t p;
    asm volatile("{\n.reg .pred p;\nelect.sync _|p, 0xffffffff;\nselp.u32 %0, 1, 0, p;\n}" : "=r"(p));
    return p;
}
__device__ __forceinline__ void fence_async() { asm volatile("fence.proxy.async.global;" ::: "memory"); }
__device__ __forceinline__ void fence_async_smem() { asm volatile("fence.proxy.async.shared::cta;" ::: "memory"); }
__device__ __forceinline__ void st_flag(uint16_t* p, uint32_t v) { asm volatile("st.release.gpu.global.u16 [%0], %1;" :: "l"(p), "h"((uint16_t)v) : "memory"); }
__device__ __forceinline__ void st_relaxed(void* p, uint32_t v) { asm volatile("st.relaxed.gpu.global.u32 [%0], %1;" :: "l"(p), "r"(v) : "memory"); }
__device__ __forceinline__ void st_relaxed64(void* p, unsigned long long v) { asm volatile("st.relaxed.gpu.global.u64 [%0], %1;" :: "l"(p), "l"(v) : "memory"); }
__device__ __forceinline__ uint4 ld_relaxed2x64(const void* p) {
    uint4 v;
    asm volatile("{\n.reg .b64 a, b;\nld.relaxed.gpu.global.v2.u64 {a, b}, [%4];\nmov.b64 {%0, %1}, a;\nmov.b64 {%2, %3}, b;\n}" : "=r"(v.x), "=r"(v.y), "=r"(v.z), "=r"(v.w) : "l"(p) : "memory");
    return v;
}
__device__ __forceinline__ uint4 ld_relaxed128(const void* p) { uint4 v; asm volatile("ld.relaxed.gpu.global.v4.u32 {%0, %1, %2, %3}, [%4];" : "=r"(v.x), "=r"(v.y), "=r"(v.z), "=r"(v.w) : "l"(p) : "memory"); return v; }
__device__ __forceinline__ uint4 ld_acquire128(const void* p) { uint4 v; asm volatile("ld.acquire.gpu.global.v4.u32 {%0, %1, %2, %3}, [%4];" : "=r"(v.x), "=r"(v.y), "=r"(v.z), "=r"(v.w) : "l"(p) : "memory"); return v; }
__device__ __forceinline__ void poll1(const uint16_t* p, uint32_t tag) {
#pragma unroll 1
    for (uint32_t spin = 0; spin < (1u << 17); spin++) {
        uint16_t v;
        asm volatile("ld.acquire.gpu.global.u16 %0, [%1];" : "=h"(v) : "l"(p) : "memory");
        if (v == (uint16_t)tag) break;
    }
    fence_async();
}
__device__ __forceinline__ void poll8(const uint16_t* p, uint32_t tag) {
    const uint32_t t2 = (tag & 0xFFFFu) * 0x10001u;
#pragma unroll 1
    for (uint32_t spin = 0; spin < (1u << 17); spin++) {
        const uint4 a = ld_acquire128(p);
        if (a.x == t2 && a.y == t2 && a.z == t2 && a.w == t2) break;
    }
    fence_async();
}
__device__ __forceinline__ uint32_t lds32(uint32_t a) { uint32_t v; asm volatile("ld.shared.u32 %0, [%1];" : "=r"(v) : "r"(a) : "memory"); return v; }
__device__ __forceinline__ void sts32(uint32_t a, uint32_t v) { asm volatile("st.shared.u32 [%0], %1;" :: "r"(a), "r"(v) : "memory"); }
__device__ __forceinline__ void sts16(uint32_t a, uint16_t v) { asm volatile("st.shared.u16 [%0], %1;" :: "r"(a), "h"(v) : "memory"); }
__device__ __forceinline__ void sts64(uint32_t a, uint32_t x, uint32_t y) { asm volatile("st.shared.v2.u32 [%0], {%1, %2};" :: "r"(a), "r"(x), "r"(y) : "memory"); }
__device__ __forceinline__ void sts128(uint32_t a, uint32_t x, uint32_t y, uint32_t z, uint32_t w) { asm volatile("st.shared.v4.u32 [%0], {%1, %2, %3, %4};" :: "r"(a), "r"(x), "r"(y), "r"(z), "r"(w) : "memory"); }
__device__ __forceinline__ uint2 lds64(uint32_t a) { uint2 v; asm volatile("ld.shared.v2.u32 {%0, %1}, [%2];" : "=r"(v.x), "=r"(v.y) : "r"(a) : "memory"); return v; }
__device__ __forceinline__ uint4 lds128(uint32_t a) { uint4 v; asm volatile("ld.shared.v4.u32 {%0, %1, %2, %3}, [%4];" : "=r"(v.x), "=r"(v.y), "=r"(v.z), "=r"(v.w) : "r"(a) : "memory"); return v; }
__device__ __forceinline__ float ex2f(float x) { float y; asm("ex2.approx.ftz.f32 %0, %1;" : "=f"(y) : "f"(x)); return y; }
__device__ __forceinline__ float rcpf(float x) { float y; asm("rcp.approx.ftz.f32 %0, %1;" : "=f"(y) : "f"(x)); return y; }
__device__ __forceinline__ void stsm4(uint32_t a, uint32_t x, uint32_t y, uint32_t z, uint32_t w) {
    asm volatile("stmatrix.sync.aligned.m8n8.x4.shared.b16 [%0], {%1, %2, %3, %4};" :: "r"(a), "r"(x), "r"(y), "r"(z), "r"(w) : "memory");
}
__device__ __forceinline__ uint32_t pack_bf16(float lo, float hi) { uint32_t r; asm("cvt.rn.bf16x2.f32 %0, %1, %2;" : "=r"(r) : "f"(hi), "f"(lo)); return r; }
__device__ __forceinline__ float bf_lo(uint32_t v) { return __uint_as_float(v << 16); }
__device__ __forceinline__ float bf_hi(uint32_t v) { return __uint_as_float(v & 0xFFFF0000u); }
__device__ __forceinline__ uint32_t phi2(float t0, float t1) {
    uint32_t r;
    asm("{\n.reg .b32 one, eps, p, e;\nmov.b32 one, 0x3F803F80;\nmov.b32 eps, 0x35863586;\n"
        "add.rn.bf16x2 p, %1, one;\nmin.bf16x2 e, %2, one;\nmax.NaN.bf16x2 p, p, e;\nadd.rn.bf16x2 %0, p, eps;\n}"
        : "=r"(r) : "r"(pack_bf16(t0, t1)), "r"(pack_bf16(ex2f(t0 * LOG2E), ex2f(t1 * LOG2E))));
    return r;
}
template <int MODE> __device__ __forceinline__ void stage_tile(uint32_t x, uint32_t step, const float (&a)[40]) {
#pragma unroll
    for (int k = 0; k < 5; k++) {
        uint32_t r[4];
#pragma unroll
        for (int e = 0; e < 4; e++) {
            const float t0 = a[8 * k + 2 * e], t1 = a[8 * k + 2 * e + 1];
            r[e] = MODE == 0 ? pack_bf16(t0, t1) : MODE == 1 ? pack_bf16(t0 * QSCALE, t1 * QSCALE) : phi2(t0, t1);
        }
        stsm4(x + 2 * k * step, r[0], r[1], r[2], r[3]);
    }
}

__device__ __forceinline__ uint32_t exp2_pair(float t0, float t1, uint32_t ca) {
    uint32_t y, u, g;
    asm("prmt.b32 %0, %1, %2, 0x6521;" : "=r"(y) : "r"(__float_as_uint(t0)), "r"(__float_as_uint(t1)));
    u = y & 0x007F007Fu;
    asm("{.reg .b32 c; mov.b32 c, 0xF963F963; fma.rn.f16x2 %0, %1, c, %2;}" : "=r"(g) : "r"(u), "r"(ca));
    asm("mul.rn.f16x2 %0, %1, %2;" : "=r"(g) : "r"(g), "r"(u));
    return y - g;
}

__device__ __forceinline__ uint64_t desc(uint32_t addr, uint32_t lbo, uint32_t hi) { return ((uint64_t)hi << 32) | ((addr >> 4) + dlo(lbo)); }
template <int J> __device__ __forceinline__ void exp_steps(const float (&s)[32], uint32_t (&p)[16], float (&o)[12], uint64_t& dv, uint32_t ca) {
    if constexpr (J < 4) {
#pragma unroll
        for (int i = 0; i < 4; i++) {
            const int h = 4 * J + (i ^ 2);
            p[h] = ((MUFU_MASK >> (h >> 1)) & 1) ? pack_bf16(ex2f(s[2 * h]), ex2f(s[2 * h + 1])) : exp2_pair(s[2 * h], s[2 * h + 1], ca);
        }
        WG_FENCE();
        wg_rs_n24_tb1_d(o, p[4 * J], p[4 * J + 1], p[4 * J + 2], p[4 * J + 3], dv);
        dv += 96;
        exp_steps<J + 1>(s, p, o, dv, ca);
    }
}

struct Ring { uint32_t slot, phase; };
__device__ __forceinline__ void next_stage(Ring& r) { if (++r.slot == 3) { r.slot = 0; r.phase ^= 1; } }

template <bool FAST>
__device__ __forceinline__ void attend(uint32_t sb, uint32_t& slot, int pass, const uint32_t (&q)[6], float (&o)[12], uint32_t ca, uint32_t z0, uint32_t z1) {
    float m0 = -INFINITY, m1 = -INFINITY;
    constexpr int UNR = FAST ? 4 : 1;
#pragma unroll 1
    for (int c = 0; c < 8; c++) {
        const uint32_t base = sb + OFF_RING + slot * RING_BYTES;
        uint64_t dk = desc(base, 128, 768 >> 4), dv = desc(base + 384, 768, 128 >> 4);
        uint32_t seen;
#pragma unroll UNR
        for (int b = 0; b < 4; b++) {
            float s[32];
            uint32_t p[16];
            WG_FENCE();
            wg_rs_n64_tb0_initd(s, q[0], q[1], q[2], q[3], dk);
            dk += 16;
            wg_rs_n64_tb0_d(s, q[4], q[5], z0, z1, dk);
            dk += 368;
            WG_COMMIT();
            if (UNR < 4 || b == 3) seen = lds32(sb + OFF_PUB);
            WG_WAIT(0);
            fence_regs(s);
            if constexpr (FAST) {
                exp_steps<0>(s, p, o, dv, ca);
            } else {
                fence_regs(o);
                float x0 = m0, x1 = m1;
#pragma unroll
                for (int g = 0; g < 8; g++) {
                    if (!((MUFU_MASK >> g) & 1)) {
#pragma unroll
                        for (int e = 0; e < 4; e++) s[4 * g + e] *= 2.f;
                    }
                    x0 = fmaxf(x0, fmaxf(s[4 * g], s[4 * g + 1]));
                    x1 = fmaxf(x1, fmaxf(s[4 * g + 2], s[4 * g + 3]));
                }
                x0 = fmaxf(x0, __shfl_xor_sync(~0u, x0, 1)); x0 = fmaxf(x0, __shfl_xor_sync(~0u, x0, 2));
                x1 = fmaxf(x1, __shfl_xor_sync(~0u, x1, 1)); x1 = fmaxf(x1, __shfl_xor_sync(~0u, x1, 2));
                const float a0 = ex2f(m0 - x0), a1 = ex2f(m1 - x1);
                m0 = x0; m1 = x1;
#pragma unroll
                for (int b = 0; b < 3; b++) { o[4 * b] *= a0; o[4 * b + 1] *= a0; o[4 * b + 2] *= a1; o[4 * b + 3] *= a1; }
#pragma unroll
                for (int g = 0; g < 8; g++) {
                    p[2 * g] = pack_bf16(ex2f(s[4 * g] - x0), ex2f(s[4 * g + 1] - x0));
                    p[2 * g + 1] = pack_bf16(ex2f(s[4 * g + 2] - x1), ex2f(s[4 * g + 3] - x1));
                }
            }
            if constexpr (!FAST) {
                WG_FENCE();
#pragma unroll
                for (int k = 0; k < 4; k++) { wg_rs_n24_tb1_d(o, p[4 * k], p[4 * k + 1], p[4 * k + 2], p[4 * k + 3], dv); dv += 96; }
            }
            WG_COMMIT();
            WG_WAIT(0);
            fence_regs(o);
        }
        if ((threadIdx.x & 31) == 0) mbar_arrive(sb + BAR_EMPTY_KV + slot * 8);
        slot = slot == 2 ? 0 : slot + 1;
        count_wait(sb + OFF_PUB, seen, min(pass * 8 + c + 2, 16));
    }
}

__device__ __forceinline__ void gemm_pass(uint32_t sb, int pass, float (&a)[40], float (&b)[40]) {
    zero_regs(a); zero_regs(b);
    const uint32_t n0 = (__shfl_sync(~0u, pass, 0) - 1) * 10;
    uint32_t slot = n0 % 3, phase = (n0 / 3) & 1;
    const bool lead = (threadIdx.x & 31) == 0;
#pragma unroll 1
    for (int c = 0; c < 10; c++) {
        mbar_wait(sb + BAR_FULL_G + slot * 8, phase);
        const uint32_t st = sb + OFF_STAGE + slot * STAGE_BYTES;
        const uint64_t dx = desc(st, 16, SW128 | 64), dw = desc(st + 16384, 2048, SW32 | 16);
        WG_FENCE();
#pragma unroll
        for (int k = 0; k < 4; k++) {
            wg_ss_n80_ta0_tb1_d(a, dx + 2 * k, dw + 32 * k);
            wg_ss_n80_ta0_tb1_d(b, dx + 512 + 2 * k, dw + 32 * k);
        }
        WG_COMMIT();
        WG_WAIT(0);
        if (lead) mbar_arrive(sb + BAR_EMPTY_G + slot * 8);
        if (++slot == 3) { slot = 0; phase ^= 1; }
    }
    fence_regs(a); fence_regs(b);
}

template <bool SPLIT> __device__ __forceinline__ void gemm_half(uint32_t sb, uint32_t n0_, float (&a)[40]) {
    zero_regs(a);
    const uint32_t n0 = __shfl_sync(~0u, n0_, 0);
    const bool lead = (threadIdx.x & 31) == 0;
#pragma unroll 1
    for (uint32_t c = 0; c < 10; c++) {
        const uint32_t n = n0 + c;
        if (SPLIT && (n == 4 || n == 7)) mbar_wait(sb + BAR_WQ + (n == 4 ? 0 : 8), 0);
        mbar_wait(sb + BAR_FULL_X + (n & 3) * 8, (n >> 2) & 1);
        const uint64_t dx = desc(sb + OFF_XA + (n & 3) * 8192, 16, SW128 | 64), dw = desc(sb + OFF_WA + c * 10240 + (SPLIT ? 8192 : 0), 2048, SW32 | 16);
        const uint64_t dv = desc(sb + OFF_WA + c * 10240, 8192, SW128 | 64);
        WG_FENCE();
#pragma unroll
        for (int k = 0; k < 4; k++) {
            if constexpr (SPLIT) {
                wg_ss_n64_ta0_tb1_d(*reinterpret_cast<float(*)[32]>(&a[0]), dx + 2 * k, dv + 128 * k);
                wg_ss_n16_ta0_tb1_d(*reinterpret_cast<float(*)[8]>(&a[32]), dx + 2 * k, dw + 32 * k);
            } else {
                wg_ss_n80_ta0_tb1_d(a, dx + 2 * k, dw + 32 * k);
            }
        }
        WG_COMMIT();
        WG_WAIT(1);
        if (lead && c) mbar_arrive(sb + BAR_EMPTY_X + ((n - 1) & 3) * 8);
    }
    WG_WAIT(0);
    if (lead) mbar_arrive(sb + BAR_EMPTY_X + ((n0 + 9) & 3) * 8);
    fence_regs(a);
}

__device__ __forceinline__ void mma16816(float (&d)[4], uint32_t a0, uint32_t a1, uint32_t a2, uint32_t a3, uint32_t b0, uint32_t b1) {
    asm volatile("mma.sync.aligned.m16n8k16.row.col.f32.bf16.bf16.f32 {%0, %1, %2, %3}, {%4, %5, %6, %7}, {%8, %9}, {%0, %1, %2, %3};"
                 : "+f"(d[0]), "+f"(d[1]), "+f"(d[2]), "+f"(d[3]) : "r"(a0), "r"(a1), "r"(a2), "r"(a3), "r"(b0), "r"(b1));
}

__device__ __forceinline__ void store_tile(uint32_t stage, __nv_bfloat16* dst, int lane, const float (&a)[40]) {
    stage_tile<0>(stage + (lane & 15) * 160 + (lane >> 4) * 16, 16, a);
    __syncwarp();
#pragma unroll
    for (int u = 0; u < 5; u++) {
        const int x = lane + 32 * u, row = (x * 205) >> 11;
        const uint4 v = lds128(stage + x * 16);
        *reinterpret_cast<uint4*>(dst + row * (1280 - 80) + x * 8) = v;
    }
    __syncwarp();
}

__device__ __forceinline__ void linear_out(uint32_t sb, int half, uint32_t dst, int q) {
    float d[44]; zero_regs(d);
    const uint64_t da = desc(sb + OFF_PK + half * 10240, 128, 80), db = desc(sb + OFF_KVB, 1408, 8);
    WG_FENCE();
#pragma unroll
    for (int k = 0; k < 5; k++) wg_ss_n88_ta0_tb1_d(d, da + 16 * k, db + 176 * k);
    WG_COMMIT();
    WG_WAIT(0);
    fence_regs(d);
    bar_sync(6, 128);
    float r0[4], r1[4];
    const int base = (threadIdx.x & 31) & ~3;
#pragma unroll
    for (int e = 0; e < 4; e++) d[40 + e] = rcpf(d[40 + e] + 1e-6f);
#pragma unroll
    for (int h = 0; h < 4; h++) {
        r0[h] = __shfl_sync(~0u, d[40 + (h & 1)], base + (h >> 1));
        r1[h] = __shfl_sync(~0u, d[42 + (h & 1)], base + (h >> 1));
    }
    uint32_t r[20];
#pragma unroll
    for (int b = 0; b < 10; b++) {
        const int hl = (8 * b) / 20, hh = (8 * b + 6) / 20;
        const bool up = hl != hh && q >= 2;
        const float s0 = up ? r0[hh] : r0[hl], s1 = up ? r1[hh] : r1[hl];
        r[2 * b] = pack_bf16(d[4 * b] * s0, d[4 * b + 1] * s0);
        r[2 * b + 1] = pack_bf16(d[4 * b + 2] * s1, d[4 * b + 3] * s1);
    }
#pragma unroll
    for (int k = 0; k < 5; k++) stsm4(dst + 32 * k, r[4 * k], r[4 * k + 1], r[4 * k + 2], r[4 * k + 3]);
}

__global__ void __launch_bounds__(NTHR, 1) fused_kernel(const __grid_constant__ Params P) {
    extern __shared__ __align__(1024) uint8_t smem[];
    const uint32_t sb = (uint32_t)__cvta_generic_to_shared(smem);
    const int tid = threadIdx.x, lane = tid & 31;
    const int wg = __shfl_sync(~0u, tid >> 7, 0), warp = __shfl_sync(~0u, (tid >> 5) & 3, 0);
    const int cta = blockIdx.x, i = cta >> 3, j = cta & 7;
    const int q = lane & 3, r0 = 16 * warp + (lane >> 2);

    const uint32_t tag = *(volatile uint32_t*)&g_epoch + 1;

    if (cta >= NCTA) {
        if (tid < 64 && elect_one()) {
            const int jj = 2 * (cta - NCTA) + warp;
            const uint32_t buf = sb + warp * 102400, bar = sb + OFF_BAR + warp * 80;
#pragma unroll 1
            for (int s = 0; s < 10; s++) mbar_init(bar + s * 8, 1);
            asm volatile("fence.mbarrier_init.release.cluster;" ::: "memory");
            int lp = 0, lc = 0;
#pragma unroll 1
            for (int n = -8; n < 40; n++) {
                if (n >= 0) {
                    const int part = n / 10, c = n - 10 * part;
                    mbar_wait(bar + c * 8, part & 1);
                    bulk_store(g_wt + ((part * 8 + jj) * 10 + c) * 10240, buf + c * 10240, 10240);
                    bulk_commit();
                    if (c == 9) { bulk_wait(); st_flag(g_flag_w + part * 8 + jj, tag); }
                    else asm volatile("cp.async.bulk.wait_group.read 2;" ::: "memory");
                }
                if (lp < 4) {
                    mbar_expect(bar + lc * 8, 10240);
                    tma3d(buf + lc * 10240, lp < 2 ? &P.wqkv : lp == 2 ? &P.wob : &P.woa, 64 * lc, 5 * jj + (lp == 0 ? 80 : 0), bar + lc * 8);
                    if (++lc == 10) { lc = 0; lp++; }
                }
            }
        }
        return;
    }
    if (tid == 640) {
        mbar_init(sb + BAR_KVIN, 1);
        asm volatile("fence.mbarrier_init.release.cluster;" ::: "memory");
        mbar_expect(sb + BAR_KVIN, 51200 + 20480);
        tma3d(sb + OFF_X16, &P.xa16, 16 * cta, 0, sb + BAR_KVIN);
#pragma unroll
        for (int u = 0; u < 4; u++) {
            const int v = (u + cta) & 3;
            bulk1d(sb + OFF_WRAW + v * 12800, P.in[2 + (v >> 1)] + (v & 1) * 12800, 12800, sb + BAR_KVIN);
        }
    } else if (tid == 672) {
#pragma unroll
        for (int s = 0; s < 3; s++) {
            mbar_init(sb + BAR_FULL_G + s * 8, 2);
            mbar_init(sb + BAR_EMPTY_G + s * 8, 4);
            mbar_init(sb + BAR_FULL_KV + s * 8, 1);
            mbar_init(sb + BAR_EMPTY_KV + s * 8, 16);
        }
        mbar_init(sb + BAR_OA, 16);
        mbar_init(sb + BAR_OA + 8, 16);
        asm volatile("fence.mbarrier_init.release.cluster;" ::: "memory");
    } else if (tid == 704) {
        prefetch_map(&P.xa);
        prefetch_map(&P.wq64);
        prefetch_map(&P.wq16);
        prefetch_l2(P.in[1] + cta * 6400, 6400);
        mbar_init(sb + BAR_WA, 1);
        mbar_init(sb + BAR_PART, 4);
        mbar_init(sb + BAR_KVB, 1);
        mbar_init(sb + BAR_OB, 4);
        sts32(sb + OFF_PUB, 0);
        sts128(sb + OFF_STAT + 16, 0x357F357Fu, 0u, 0u, 0u);
        asm volatile("fence.mbarrier_init.release.cluster;" ::: "memory");
    } else if (tid == 736) {
#pragma unroll
        for (int s = 0; s < 4; s++) { mbar_init(sb + BAR_FULL_X + s * 8, 1); mbar_init(sb + BAR_EMPTY_X + s * 8, 4); }
#pragma unroll
        for (int s = 0; s < 4; s++) sts128(sb + OFF_QUEUE + s * 16, 0u, 0u, 0u, 0u);
        mbar_init(sb + BAR_A0, 1);
        mbar_init(sb + BAR_Q, 4);
        mbar_init(sb + BAR_Q + 8, 4);
        mbar_init(sb + BAR_C0, 16);
        for (int s = 0; s < 2; s++) mbar_init(sb + BAR_WQ + s * 8, 1);
        asm volatile("fence.mbarrier_init.release.cluster;" ::: "memory");
    }
    __syncthreads();

    if (wg == 5) {
        asm volatile("setmaxnreg.dec.sync.aligned.u32 32;");
        if (warp == 0) {
            if (elect_one()) {
#pragma unroll 1
                for (int n = 0; n < 20; n++) {
                    const uint32_t s = n & 3, bar = sb + BAR_FULL_X + s * 8;
                    if (n >= 4) mbar_wait(sb + BAR_EMPTY_X + s * 8, ((n >> 2) - 1) & 1);
                    mbar_expect(bar, n < 4 ? 18432 : 8192);
                    tma2d(sb + OFF_XA + s * 8192, &P.xa, n < 10 ? 64 * n : 64 * n - 640, 128 * i + (n < 10 ? 0 : 64), bar);
                    if (n < 4) {
                        tma2d(sb + OFF_WA + n * 10240, &P.wq64, 80 * j, 64 * n, bar);
                        tma2d(sb + OFF_WA + n * 10240 + 8192, &P.wq16, 80 * j + 64, 64 * n, bar);
                    }
                    if (n == 3) {
                        mbar_expect(sb + BAR_WQ, 30720);
                        mbar_expect(sb + BAR_WQ + 8, 30720);
#pragma unroll 1
                        for (int c = 4; c < 10; c++) {
                            tma2d(sb + OFF_WA + c * 10240, &P.wq64, 80 * j, 64 * c, sb + BAR_WQ + (c < 7 ? 0 : 8));
                            tma2d(sb + OFF_WA + c * 10240 + 8192, &P.wq16, 80 * j + 64, 64 * c, sb + BAR_WQ + (c < 7 ? 0 : 8));
                        }
                    }
                }
                Ring r{0, 0};
#pragma unroll 1
                for (int pass = 1; pass < 5; pass++) {
                    const CUtensorMap* m = pass <= 3 ? &P.xb : &P.ob;
                    if (pass == 4) {
                        mbar_wait(sb + BAR_OB, 0);
                        tma2d_store(&P.ob_st, 80 * j, 128 * i, sb + OFF_PK);
                        bulk_commit();
                        bulk_wait();
                        st_flag(g_flag_b2 + cta, tag);
                        poll8(g_flag_b2 + i * 8, tag);
                    }
#pragma unroll 1
                    for (int c = 0; c < 10; c++) {
                        if (pass == 3 && c == 3) {
                            mbar_wait(sb + BAR_PART, 0);
                            bulk_add_f32(g_part + j * 1920, sb + OFF_PST, 7680);
                            bulk_commit();
                        }
                        mbar_wait(sb + BAR_EMPTY_G + r.slot * 8, r.phase);
                        mbar_expect(sb + BAR_FULL_G + r.slot * 8, 16384);
                        tma2d(sb + OFF_STAGE + r.slot * STAGE_BYTES, m, 64 * c, 128 * i, sb + BAR_FULL_G + r.slot * 8);
                        next_stage(r);
                        if (pass == 3 && c == 3) {
                            bulk_wait();
                            st_flag(g_flag_b1 + j * 16 + i, tag);
                        }
                    }
                }
                {
                    poll8(g_flag_a + i * 8, tag);
                    mbar_arrive(sb + BAR_A0);
#pragma unroll 1
                    for (int c = 0; c < 10; c++) {
                        const uint32_t s = c & 3;
                        mbar_wait(sb + BAR_EMPTY_X + s * 8, (c >> 2) & 1);
                        mbar_expect(sb + BAR_FULL_X + s * 8, 8192);
                        tma2d(sb + OFF_XA + s * 8192, &P.oa, 64 * c, 128 * i, sb + BAR_FULL_X + s * 8);
                    }
                }
            }
        } else if (warp == 2) {
            if (elect_one()) {
                Ring r{0, 0};
#pragma unroll 1
                for (int pass = 1; pass < 5; pass++) {
                    const CUtensorMap* m = pass <= 3 ? &P.wqkv : &P.wob;
                    const int col = 5 * j + (pass == 1 ? 40 : pass == 2 ? 80 : 0);
                    const bool pre = pass >= 2 && P.helpers;
                    if (pre) poll1(g_flag_w + (pass - 2) * 8 + j, tag);
#pragma unroll 1
                    for (int c = 0; c < 10; c++) {
                        mbar_wait(sb + BAR_EMPTY_G + r.slot * 8, r.phase);
                        const uint32_t bar = sb + BAR_FULL_G + r.slot * 8;
                        mbar_expect(bar, 10240);
                        const uint32_t dst = sb + OFF_STAGE + r.slot * STAGE_BYTES + 16384;
                        if (pre) bulk1d(dst, g_wt + (((pass - 2) * 8 + j) * 10 + c) * 10240, 10240, bar);
                        else tma3d(dst, m, 64 * c, col, bar);
                        next_stage(r);
                    }
                }
                {
                    if (P.helpers) poll1(g_flag_w + 24 + j, tag);
#pragma unroll 1
                    for (int c = 0; c < 3; c++) { mbar_wait(sb + BAR_EMPTY_G + r.slot * 8, r.phase); next_stage(r); }
                    mbar_expect(sb + BAR_WA, 102400);
                    if (P.helpers) bulk1d(sb + OFF_WA, g_wt + (24 + j) * 102400, 102400, sb + BAR_WA);
                    else {
#pragma unroll 1
                        for (int c = 0; c < 10; c++) tma3d(sb + OFF_WA + c * 10240, &P.woa, 64 * c, 5 * j, sb + BAR_WA);
                    }
                }
            }
        } else if (warp == 3) {
            bar_sync(12, 96);
            if (elect_one()) {
                st_flag(g_flag_kv + cta, tag);
                prefetch_l2(P.in[5] + cta * 20480, 20480);
#pragma unroll 1
                for (int u = 0; u < 5; u++) prefetch_l2(P.in[6] + (cta * 5 + u) * 3840 + 1280, 1280);
            }
            __syncwarp();
            {
                if (elect_one()) {
                    poll8(g_flag_b1 + j * 16, tag);
                    poll8(g_flag_b1 + j * 16 + 8, tag);
                    mbar_expect(sb + BAR_KVB, 7680);
                    bulk1d(sb + OFF_PST, g_part + j * 1920, 7680, sb + BAR_KVB);
                }
            }
            if (elect_one()) {
                mbar_wait(sb + BAR_OA, 0);
                tma2d_store(&P.oa_st, 80 * j, 128 * i, sb + OFF_Q);
                bulk_commit();
                bulk_wait();
                st_flag(g_flag_a + cta, tag);
            }
        } else if (warp == 1) {
            uint32_t sk, spin = 0;
            bar_sync(12, 96);
            __nanosleep(800);
#pragma unroll 1
            while (true) {
                const uint4 f = ld_relaxed128(g_stat + 4 * lane);
                const uint32_t t = tag << 16;
                sk = max(max(f.x ^ t, f.y ^ t), max(f.z ^ t, f.w ^ t));
                sk = __reduce_max_sync(~0u, sk);
                if (sk < 0x10000u || ++spin > (1u << 17)) break;
            }
            if (lane == 0) {
                sts32(sb + OFF_STAT, sk << 16);
            }
            mbar_wait(sb + BAR_C0, 0);
            if (lane == 0) {
                mbar_arrive(sb + BAR_FULL_KV);
                asm volatile("st.release.cta.shared::cta.u32 [%0], %1;" :: "r"(sb + OFF_PUB), "r"(1) : "memory");
            }
            __syncwarp();
            __nanosleep(300);
            const uint32_t t2 = (tag & 0xFFFFu) * 0x10001u;
#pragma unroll 1
            for (spin = 0; spin < (1u << 17); spin++) {
                const uint4 f = ld_acquire128(g_flag_kv + 8 * (lane & 15));
                if (__all_sync(~0u, f.x == t2 && f.y == t2 && f.z == t2 && f.w == t2)) break;
            }
            if (elect_one()) {
                fence_async();
#pragma unroll 1
                for (int n = 1; n < 3; n++) {
                    mbar_expect(sb + BAR_FULL_KV + n * 8, RING_BYTES);
                    bulk1d(sb + OFF_RING + n * RING_BYTES, g_kv + n * RING_BYTES, RING_BYTES, sb + BAR_FULL_KV + n * 8);
                }
                Ring r{1, 0};
#pragma unroll 1
                for (int n = 1; n < 16; n++) {
                    if (n >= 3) {
                        mbar_wait(sb + BAR_EMPTY_KV + r.slot * 8, r.phase ^ 1);
                        mbar_expect(sb + BAR_FULL_KV + r.slot * 8, RING_BYTES);
                        bulk1d(sb + OFF_RING + r.slot * RING_BYTES, g_kv + (n & 7) * RING_BYTES, RING_BYTES, sb + BAR_FULL_KV + r.slot * 8);
                    }
                    mbar_wait(sb + BAR_FULL_KV + r.slot * 8, r.phase);
                    asm volatile("st.release.cta.shared::cta.u32 [%0], %1;" :: "r"(sb + OFF_PUB), "r"(n + 1) : "memory");
                    next_stage(r);
                }
            }
        }
    } else if (wg < 4) {
        if (tid < 30) reinterpret_cast<uint4*>(g_part + j * 1920 + i * 120)[tid] = make_uint4(0u, 0u, 0u, 0u);
        if (wg < 2) {
            const uint32_t kw = 4 * wg + warp, g = lane >> 2;
            const uint32_t w0 = sb + OFF_WRAW + (80 * kw + 4 * q) * 40;
            const uint32_t wa[3] = {w0 + g * 4, w0 + g * 4 + 25608, w0 + 32 + (g & 1) * 4 + (g & 2) * 12784};
            float d[3][2][4];
#pragma unroll
            for (int e = 0; e < 24; e++) (&d[0][0][0])[e] = 0.f;
            mbar_wait(sb + BAR_KVIN, 0);
            uint2 x[2][2];
            uint32_t u[2][12];
#pragma unroll
            for (int s = 0; s < 6; s++) {
                if (s < 5) {
                    const uint32_t st = 5 * kw + s;
                    const uint32_t xa = sb + OFF_X16 + (st >> 2) * 2048 + g * 128 + (((2 * (st & 3) + (q >> 1)) ^ g) << 4) + (q & 1) * 8;
                    x[s & 1][0] = lds64(xa); x[s & 1][1] = lds64(xa + 1024);
#pragma unroll
                    for (int e = 0; e < 12; e++) u[s & 1][e] = lds32(wa[e >> 2] + s * 640 + (e & 3) * 40);
                }
                if (s > 0) {
                    const int p = (s - 1) & 1;
#pragma unroll
                    for (int t = 0; t < 3; t++) {
                        const uint32_t a0 = __byte_perm(u[p][4 * t], u[p][4 * t + 1], 0x5410), a1 = __byte_perm(u[p][4 * t], u[p][4 * t + 1], 0x7632);
                        const uint32_t a2 = __byte_perm(u[p][4 * t + 2], u[p][4 * t + 3], 0x5410), a3 = __byte_perm(u[p][4 * t + 2], u[p][4 * t + 3], 0x7632);
                        mma16816(d[t][0], a0, a1, a2, a3, x[p][0].x, x[p][0].y);
                        mma16816(d[t][1], a0, a1, a2, a3, x[p][1].x, x[p][1].y);
                    }
                }
            }
            bar_arrive(2, 384);
#pragma unroll
            for (int t = 0; t < 3; t++) {
                const uint32_t pr = t == 0 ? g : t == 1 ? 12 + g : 8 + g;
                if (t < 2 || g < 4) {
#pragma unroll
                    for (int h = 0; h < 2; h++) {
                        const uint32_t a = sb + OFF_KVP + kw * 2560 + ((8 * h + 2 * q) * 20 + pr) * 8;
                        sts64(a, __float_as_uint(d[t][h][0]), __float_as_uint(d[t][h][2]));
                        sts64(a + 160, __float_as_uint(d[t][h][1]), __float_as_uint(d[t][h][3]));
                    }
                }
            }
        }
        bar_sync(1, 512);
        if (wg < 3) {
            const uint32_t ch = 4 * wg + warp, grp = ch >= 6, c6 = ch - 6 * grp, isv = c6 >= 3, c3 = c6 - 3 * isv;
            const uint32_t key = 8 * grp + (lane >> 2);
            const bool mu = (MUFU_MASK >> ((2 * cta + grp) & 7)) & 1;
            uint32_t word;
            if (c3 == 2 && q >= 2) {
                word = isv ? (q == 2 ? 0x00003F80u : 0u) : mu ? 0u : q == 2 ? 0x3F00433Fu : 0x00003B4Au;
            } else {
                const uint32_t a = sb + OFF_KVP + (key * 20 + 10 * isv + 4 * c3 + q) * 8;
                float s0 = 0.f, s1 = 0.f;
#pragma unroll
                for (int u = 0; u < 8; u++) { const uint2 v = lds64(a + u * 2560); s0 += __uint_as_float(v.x); s1 += __uint_as_float(v.y); }
                const float sc = (isv || mu) ? 1.f : 0.5f;
                word = pack_bf16(s0 * sc, s1 * sc);
            }
            if (cta < 16) st_relaxed64(g_kt + cta * 384 + tid, ((unsigned long long)tag << 32) | word);
            reinterpret_cast<uint32_t*>(g_kv + cta * 1536)[tid] = word;
            if (c3 == 2 && q >= 2) word = 0;
            if (isv) {
                const uint32_t mx = __reduce_max_sync(~0u, max(word & 0x7FFFu, (word >> 16) & 0x7FFFu));
                if (lane == 0) sts32(sb + OFF_KST + 192 + (3 * grp + c3) * 4, mx);
            } else {
                float n2 = fmaf(bf_lo(word), bf_lo(word), bf_hi(word) * bf_hi(word));
                n2 += __shfl_xor_sync(~0u, n2, 1);
                n2 += __shfl_xor_sync(~0u, n2, 2);
                if (q == 0) sts32(sb + OFF_KST + (c3 * 16 + key) * 4, __float_as_uint(mu ? n2 : 4.f * n2));
            }
            if (wg | warp) bar_arrive(3, 384);
            else {
                bar_sync(3, 384);
                const uint32_t a = sb + OFF_KST + (lane & 15) * 4;
                const float n2 = __uint_as_float(lds32(a)) + __uint_as_float(lds32(a + 64)) + __uint_as_float(lds32(a + 128));
                const uint32_t sk = __reduce_max_sync(~0u, min(((__float_as_uint(n2) & 0x7FFFFFFFu) + 0xFFFFu) >> 16, 0x7FFFu));
                const uint32_t sv = __reduce_max_sync(~0u, lds32(sb + OFF_KST + 192 + min(lane, 5) * 4));
                if (lane == 0) {
                    const bool vok = sv == 0 || (sv >= ((127 - 40) << 7) && sv <= ((127 + 40) << 7));
                    st_relaxed(g_stat + cta, (tag << 16) | (vok ? sk : 0x7FFFu));
                }
                __syncwarp();
                bar_arrive(12, 96);
            }
        }
        {
            const unsigned long long* src = g_kt + tid * 2;
            uint4 v[6];
#pragma unroll
            for (int u = 0; u < 6; u++) v[u] = make_uint4(0u, ~tag, 0u, 0u);
            __nanosleep(400);
#pragma unroll 1
            for (uint32_t spin = 0; spin < (1u << 16); spin++) {
#pragma unroll
                for (int u = 0; u < 6; u++) if (v[u].y != tag) v[u] = ld_relaxed2x64(src + u * 1024);
                bool ok = true;
#pragma unroll
                for (int u = 0; u < 6; u++) { if (v[u].w != tag) v[u].y = ~tag; ok = ok && v[u].y == tag; }
                if (__all_sync(~0u, ok)) break;
            }
#pragma unroll
            for (int u = 0; u < 6; u++) sts64(sb + OFF_RING + tid * 8 + u * 4096, v[u].x, v[u].z);
            fence_async_smem();
            __syncwarp();
            if (lane == 0) mbar_arrive(sb + BAR_C0);
        }
        uint32_t slot = 0;
        const uint4 cz = lds128(sb + OFF_STAT + 16);
#pragma unroll 1
        for (int pass = 0; pass < 2; pass++) {
            uint32_t qf[6];
            mbar_wait(sb + BAR_Q + pass * 8, 0);
            const uint32_t qa = sb + OFF_Q + pass * 10240 + r0 * 160 + wg * 40 + q * 4;
            qf[0] = lds32(qa); qf[1] = lds32(qa + 8 * 160);
            qf[2] = lds32(qa + 16); qf[3] = lds32(qa + 8 * 160 + 16);
            qf[4] = q < 2 ? lds32(qa + 32) : 0u; qf[5] = q < 2 ? lds32(qa + 8 * 160 + 32) : 0u;
            if (pass == 0) { count_wait(sb + OFF_PUB, 0, 1); }
            float n0 = 0.f, n1 = 0.f;
#pragma unroll
            for (int e = 0; e < 3; e++) {
                n0 = fmaf(bf_lo(qf[2 * e]), bf_lo(qf[2 * e]), fmaf(bf_hi(qf[2 * e]), bf_hi(qf[2 * e]), n0));
                n1 = fmaf(bf_lo(qf[2 * e + 1]), bf_lo(qf[2 * e + 1]), fmaf(bf_hi(qf[2 * e + 1]), bf_hi(qf[2 * e + 1]), n1));
            }
            n0 += __shfl_xor_sync(~0u, n0, 1); n0 += __shfl_xor_sync(~0u, n0, 2);
            n1 += __shfl_xor_sync(~0u, n1, 1); n1 += __shfl_xor_sync(~0u, n1, 2);
            const float k2 = __uint_as_float(lds32(sb + OFF_STAT));
            const uint32_t bad = !(n0 * k2 <= 4000.f && n1 * k2 <= 4000.f);
            uint32_t anybad;
            asm volatile("{\n.reg .pred p, r;\nsetp.ne.u32 p, %1, 0;\nbar.red.or.pred r, %2, 128, p;\nselp.u32 %0, 1, 0, r;\n}" : "=r"(anybad) : "r"(bad), "r"(8 + wg) : "memory");
            float o[12];
#pragma unroll
            for (int k = 0; k < 12; k++) o[k] = 0.f;
            fence_regs(o);
            if (!__shfl_sync(~0u, anybad, 0)) {
                if (q >= 2) qf[4] = qf[5] = q == 2 ? 0x3F803F80u : 0x00003F80u;
                attend<true>(sb, slot, pass, qf, o, cz.x, cz.y, cz.z);
            } else {
                attend<false>(sb, slot, pass, qf, o, cz.x, cz.y, cz.z);
            }
            const float i0 = rcpf(__shfl_sync(~0u, o[8], (lane & ~3) | 2)), i1 = rcpf(__shfl_sync(~0u, o[10], (lane & ~3) | 2));
            const uint32_t ot = opaque_tid(), ol = ot & 31, oq = ot & 3;
            uint8_t* const gx = g_ox + opaque_cta() * 10240;
#pragma unroll
            for (int b = 0; b < 3; b++) {
                if (b < 2 || oq < 2) {
                    const uint32_t v0 = pack_bf16(o[4 * b] * i0, o[4 * b + 1] * i0), v1 = pack_bf16(o[4 * b + 2] * i1, o[4 * b + 3] * i1);
                    const uint32_t col = 20 * (ot >> 7) + 8 * b + 2 * oq;
                    const uint32_t x = (col >> 4) * 2048 + (ot & 96) * 16 + (col & 8) * 16 + (ol >> 2) * 16 + (col & 7) * 2;
                    st_relaxed(gx + x, pass ? v0 : ~0u);
                    st_relaxed(gx + x + 256, pass ? v1 : ~0u);
                    const uint32_t dst = sb + OFF_Q + (pass ? 10240 + x : (((ot & 96) >> 1) + (ol >> 2)) * 160 + col * 2);
                    sts32(dst, v0);
                    sts32(dst + (pass ? 256 : 8 * 160), v1);
                }
            }
            fence_async_smem();
            __syncwarp();
            if (lane == 0) mbar_arrive(sb + BAR_OA + pass * 8);
        }
        {
            const uint32_t ot = opaque_tid(), oc = opaque_cta();
            const int lane = ot & 31, i = oc >> 3, j = oc & 7;
            if (wg != 0) {
                const int u = 4 * (3 - wg) + warp;
                uint4 v[12];
                const uint8_t* src[3];
                uint32_t entry = u + 1;
#pragma unroll
                for (int t = 0; t < 3; t++) {
                    const int s = min(3 * u + t, 34), h = (s * 37) >> 8;
                    const int g = 5 * ((j + 1 + s - 7 * h) & 7) + 4 - h;
                    src[t] = g_ox + (i * 40 + g) * 2048 + lane * 16;
                    entry |= g << (8 * t + 8);
                }
#pragma unroll
                for (int k = 0; k < 12; k++) v[k] = make_uint4(k >= 8 && u == 11 ? 0u : ~0u, 0u, 0u, 0u);
                const uint8_t* const probe = (lane < 8 ? src[0] : lane < 16 ? src[1] : src[2]) - lane * 16 + (lane & 6) * 256 + (lane & 1) * 128 + 368;
                uint32_t wait = u == 11 ? 0xFFFFu : 0xFFFFFFu;
                mbar_wait(sb + BAR_A0, 0);
#pragma unroll 1
                for (uint32_t spin = 0; spin < (1u << 16); spin++) {
                    uint4 p = make_uint4(0u, 0u, 0u, 0u);
                    if (mbar_test(sb + BAR_OA + 8, 0)) wait = 0;
                    if ((wait >> lane) & 1) p = ld_relaxed128(probe);
#pragma unroll
                    for (int k = 0; k < 12; k++) if (!((wait >> (2 * (k & 12))) & 0xFF) && v[k].x == ~0u) v[k] = ld_relaxed128(src[k >> 2] + (k & 3) * 512);
                    wait = __ballot_sync(~0u, p.x == ~0u || p.w == ~0u);
                    bool ok = true;
#pragma unroll
                    for (int k = 0; k < 12; k++) {
                        if (v[k].y == ~0u || v[k].z == ~0u || v[k].w == ~0u) v[k].x = ~0u;
                        ok = ok && v[k].x != ~0u;
                    }
                    if (__all_sync(~0u, ok)) break;
                }
                mbar_wait(sb + BAR_OA + 8, 0);
#pragma unroll
                for (int k = 0; k < 12; k++) sts128(sb + OFF_RING + u * 6144 + k * 512 + lane * 16, v[k].x, v[k].y, v[k].z, v[k].w);
                fence_async_smem();
                __syncwarp();
                if (lane == 0) {
                    uint32_t n;
                    asm volatile("atom.relaxed.cta.shared::cta.add.u32 %0, [%1], 1;" : "=r"(n) : "r"(sb + OFF_QUEUE + 48) : "memory");
                    asm volatile("st.release.cta.shared::cta.u32 [%0], %1;" :: "r"(sb + OFF_QUEUE + n * 4), "r"(entry) : "memory");
                }
            } else {
                float a[40];
                mbar_wait(sb + BAR_WA, 0);
                mbar_wait(sb + BAR_OA + 8, 0);
                const uint64_t dw = desc(sb + OFF_WA, 2048, SW32 | 16);
                {
                    const uint64_t da = desc(sb + OFF_Q + 10240, 128, 16);
                    WG_FENCE();
#pragma unroll
                    for (int t = 0; t < 5; t++) {
                        const uint32_t g = 5 * j + t;
                        if (t == 0) wg_ss_n80_ta0_tb1_initd(a, da, dw + (g >> 2) * 640 + (g & 3) * 32);
                        else wg_ss_n80_ta0_tb1_d(a, da + 128 * t, dw + (g >> 2) * 640 + (g & 3) * 32);
                    }
                    WG_COMMIT();
                }
#pragma unroll 1
                for (int n = 0; n < 12; n++) {
                    const uint32_t e = __shfl_sync(~0u, queue_wait(sb + OFF_QUEUE + n * 4), 0);
                    const uint64_t da = desc(sb + OFF_RING - 6144 + (e & 15) * 6144, 128, 16);
                    WG_FENCE();
#pragma unroll
                    for (int t = 0; t < 3; t++) {
                        const uint32_t g = (e >> (8 * t + 8)) & 63;
                        wg_ss_n80_ta0_tb1_d(a, da + 128 * t, dw + (g >> 2) * 640 + (g & 3) * 32);
                    }
                    WG_COMMIT();
                }
                WG_WAIT(0);
                fence_regs(a);
                bar_sync(8, 128);
                store_tile(sb + OFF_Q + 10240 + warp * 2560, P.out + (128 * i + 64 + 16 * warp) * 1280 + 80 * j, lane, a);
            }
        }
    } else {
        asm volatile("setmaxnreg.inc.sync.aligned.u32 128;");
        const uint32_t mrow = 16 * warp + (lane & 15), mcol = lane >> 4;
        const uint32_t xrow = mrow * 160 + mcol * 16, xgrp = (mrow & 7) * 16 + mcol * 128;
        bar_sync(2, 384);
#pragma unroll 1
        for (int half = 0; half < 2; half++) {
            float a[40];
            gemm_half<true>(sb, 10 * half, a);
            if (half && lane == 0) { mbar_arrive(sb + BAR_EMPTY_G); mbar_arrive(sb + BAR_EMPTY_G + 8); mbar_arrive(sb + BAR_EMPTY_G + 16); }
            stage_tile<1>(sb + OFF_Q + half * 10240 + xrow, 16, a);
            __syncwarp();
            if (lane == 0) mbar_arrive(sb + BAR_Q + half * 8);
        }
#pragma unroll 1
        for (int pass = 1; pass < 5; pass++) {
        if (pass == 4) {
        mbar_wait(sb + BAR_KVB, 0);
        if (tid < 592) {
            const int m = tid - 512, h = m / 20;
            const uint32_t x0 = sb + OFF_KVB + (m >> 3) * 1408 + (m & 7) * 16;
#pragma unroll
            for (int e = 0; e < 5; e++) {
                const uint4 v = lds128(sb + OFF_PST + m * 96 + e * 16);
                const int n = 20 * h + 4 * e;
                sts64(x0 + (n >> 3) * 128 + (n & 4) * 2, pack_bf16(__uint_as_float(v.x), __uint_as_float(v.y)), pack_bf16(__uint_as_float(v.z), __uint_as_float(v.w)));
            }
            sts16(x0 + 1280 + h * 2, (uint16_t)pack_bf16(__uint_as_float(lds32(sb + OFF_PST + m * 96 + 80)), 0.f));
        }
        fence_async_smem();
        bar_sync(6, 128);
#pragma unroll 1
        for (int half = 0; half < 2; half++) linear_out(sb, half, sb + OFF_PK + half * 10240 + xrow, q);
        fence_async_smem();
        __syncwarp();
        if (lane == 0) mbar_arrive(sb + BAR_OB);
        }
        float a[40], b[40];
        gemm_pass(sb, pass, a, b);
        if (pass == 1 || pass == 3) {
        stage_tile<2>(sb + OFF_PK + (mrow >> 3) * 1280 + xgrp, 128, a);
        stage_tile<2>(sb + OFF_PK + (8 + (mrow >> 3)) * 1280 + xgrp, 128, b);
        } else if (pass == 2) {
        stage_tile<0>(sb + OFF_V + 128 + (mrow >> 3) * 1536 + xgrp, 128, a);
        stage_tile<0>(sb + OFF_V + 128 + (8 + (mrow >> 3)) * 1536 + xgrp, 128, b);
        {
            const uint32_t x = sb + OFF_V + ((tid - 512) >> 3) * 1536 + (tid & 7) * 16;
            sts128(x, 0x3F80u, 0u, 0u, 0u);
            sts128(x + 11 * 128, 0x3F80u, 0u, 0u, 0u);
        }
        fence_async_smem();
        bar_sync(6, 128);
        {
            float d1[36], d2[16]; zero_regs(d1); zero_regs(d2);
            const uint64_t da = desc(sb + OFF_PK, 1280, 8), db = desc(sb + OFF_V, 1536, 8);
            WG_FENCE();
#pragma unroll
            for (int k = 0; k < 8; k++) {
                wg_ss_n72_ta1_tb1_d(d1, da + 160 * k, db + 192 * k);
                wg_ss_n32_ta1_tb1_d(d2, da + 16 + 160 * k, db + 64 + 192 * k);
            }
            WG_COMMIT();
            WG_WAIT(0);
            fence_regs(d1); fence_regs(d2);
            bar_sync(6, 128);
#pragma unroll
            for (int u = 0; u < 7; u++) if (u < 6 || tid < 624) sts128(sb + OFF_KVB + (tid - 512 + 128 * u) * 16, 0u, 0u, 0u, 0u);
            const uint32_t part = sb + OFF_PST;
#pragma unroll
            for (int hh = 0; hh < 2; hh++) {
                const int m = r0 + 8 * hh;
                if (m < 60) {
                    const int h20 = (m / 20) * 20;
                    if (q == 0) sts128(part + m * 96 + 80, __float_as_uint(d1[2 * hh]), 0u, 0u, 0u);
#pragma unroll
                    for (int k = 1; k < 9; k++) {
                        const int e = 8 * (k - 1) + 2 * q - h20;
                        if (e >= 0 && e < 20) sts64(part + m * 96 + e * 4, __float_as_uint(d1[4 * k + 2 * hh]), __float_as_uint(d1[4 * k + 2 * hh + 1]));
                    }
                }
                if (m >= 44) {
                    if (q == 0) sts128(part + (m + 16) * 96 + 80, __float_as_uint(d2[12 + 2 * hh]), 0u, 0u, 0u);
#pragma unroll
                    for (int k = 0; k < 3; k++) {
                        const int e = 8 * k + 2 * q - 4;
                        if (e >= 0) sts64(part + (m + 16) * 96 + e * 4, __float_as_uint(d2[4 * k + 2 * hh]), __float_as_uint(d2[4 * k + 2 * hh + 1]));
                    }
                }
            }
            fence_async_smem();
            __syncwarp();
            if (lane == 0) mbar_arrive(sb + BAR_PART);
        }
        } else {
        __nv_bfloat16* out = P.out + (128 * i + 16 * warp) * 1280 + 80 * j + 640;
        mbar_wait(sb + BAR_A0, 0);
        store_tile(sb + OFF_Q + warp * 2560, out, lane, a);
        store_tile(sb + OFF_Q + warp * 2560, out + 64 * 1280, lane, b);
        }
        }
        {
            mbar_wait(sb + BAR_WA, 0);
            float a[40];
            gemm_half<false>(sb, 20, a);
            store_tile(sb + OFF_Q + warp * 2560, P.out + (128 * i + 16 * warp) * 1280 + 80 * j, lane, a);
        }
        if (cta == 0 && tid == 512) *(volatile uint32_t*)&g_epoch = tag;
    }
}

typedef CUresult (*EncodeFn)(CUtensorMap*, CUtensorMapDataType, cuuint32_t, void*, const cuuint64_t*, const cuuint64_t*,
                             const cuuint32_t*, const cuuint32_t*, CUtensorMapInterleave, CUtensorMapSwizzle,
                             CUtensorMapL2promotion, CUtensorMapFloatOOBfill);

void make_map(EncodeFn enc, CUtensorMap* m, const void* p, uint32_t box_cols, uint32_t box_rows, uint64_t rows = 2048) {
    cuuint64_t dims[2] = {640, rows}, strides[1] = {1280};
    cuuint32_t box[2] = {box_cols, box_rows}, es[2] = {1, 1};
    enc(m, CU_TENSOR_MAP_DATA_TYPE_BFLOAT16, 2, const_cast<void*>(p), dims, strides, box, es, CU_TENSOR_MAP_INTERLEAVE_NONE,
        box_cols == 64 ? CU_TENSOR_MAP_SWIZZLE_128B : box_cols == 16 ? CU_TENSOR_MAP_SWIZZLE_32B : CU_TENSOR_MAP_SWIZZLE_NONE, CU_TENSOR_MAP_L2_PROMOTION_L2_128B, CU_TENSOR_MAP_FLOAT_OOB_FILL_NONE);
}
void make_x16map(EncodeFn enc, CUtensorMap* m, const void* p) {
    cuuint64_t dims[3] = {64, 2048, 10}, strides[2] = {1280, 128};
    cuuint32_t box[3] = {64, 16, 10}, es[3] = {1, 1, 1};
    enc(m, CU_TENSOR_MAP_DATA_TYPE_BFLOAT16, 3, const_cast<void*>(p), dims, strides, box, es, CU_TENSOR_MAP_INTERLEAVE_NONE,
        CU_TENSOR_MAP_SWIZZLE_128B, CU_TENSOR_MAP_L2_PROMOTION_L2_128B, CU_TENSOR_MAP_FLOAT_OOB_FILL_NONE);
}
void make_wmap(EncodeFn enc, CUtensorMap* m, const void* p, uint64_t cols) {
    cuuint64_t dims[3] = {16, 640, cols / 16}, strides[2] = {cols * 2, 32};
    cuuint32_t box[3] = {16, 64, 5}, es[3] = {1, 1, 1};
    enc(m, CU_TENSOR_MAP_DATA_TYPE_BFLOAT16, 3, const_cast<void*>(p), dims, strides, box, es, CU_TENSOR_MAP_INTERLEAVE_NONE,
        CU_TENSOR_MAP_SWIZZLE_32B, CU_TENSOR_MAP_L2_PROMOTION_L2_128B, CU_TENSOR_MAP_FLOAT_OOB_FILL_NONE);
}

}

extern "C" void kernel_launch(void* const* d_in, const int* in_sizes, int n_in, void* d_out, int out_size) {
    static EncodeFn enc = nullptr;
    static void *oa = nullptr, *ob = nullptr;
    static int sms = 0;
    if (!enc) {
        void* fn = nullptr;
        cudaDriverEntryPointQueryResult qr;
        cudaGetDriverEntryPoint("cuTensorMapEncodeTiled", &fn, cudaEnableDefault, &qr);
        enc = (EncodeFn)fn;
        int dev = 0;
        cudaGetDevice(&dev);
        cudaDeviceGetAttribute(&sms, cudaDevAttrMultiProcessorCount, dev);
        cudaGetSymbolAddress(&oa, g_oa);
        cudaGetSymbolAddress(&ob, g_ob);
        cudaFuncSetAttribute(fused_kernel, cudaFuncAttributeMaxDynamicSharedMemorySize, SMEM_BYTES);
    }
    Params P;
    make_map(enc, &P.xa, d_in[0], 64, 64);
    make_x16map(enc, &P.xa16, d_in[0]);
    make_map(enc, &P.wq64, d_in[1], 64, 64, 640);
    make_map(enc, &P.wq16, d_in[1], 16, 64, 640);
    make_map(enc, &P.xb, d_in[5], 64, 128);
    make_wmap(enc, &P.wqkv, d_in[6], 1920);
    make_wmap(enc, &P.woa, d_in[4], 640);
    make_wmap(enc, &P.wob, d_in[7], 640);
    make_map(enc, &P.oa, oa, 64, 64);
    make_map(enc, &P.ob, ob, 64, 128);
    make_map(enc, &P.oa_st, oa, 80, 64);
    make_map(enc, &P.ob_st, ob, 80, 128);
    for (int k = 0; k < 8; k++) P.in[k] = (const uint8_t*)d_in[k];
    P.out = (__nv_bfloat16*)d_out;
    P.helpers = sms >= NCTA + 4;
    fused_kernel<<<P.helpers ? NCTA + 4 : NCTA, NTHR, SMEM_BYTES, cudaStreamPerThread>>>(P);
}
```
